```python
import torch

def _softmax(x, axis=-1):
    return torch.softmax(x, dim=axis)
def _gelu(x):
    return torch.nn.functional.gelu(x, approximate="tanh")
def _silu(x):
    return torch.nn.functional.silu(x)
def _sigmoid(x):
    return torch.sigmoid(x)
def _layernorm(x, axis=-1, eps=1e-5):
    m = x.mean(dim=axis, keepdim=True)
    v = x.var(dim=axis, keepdim=True, unbiased=False)
    return (x - m) / torch.sqrt(v + eps)
def _scatter_add(tgt, idx, src, axis=0):
    return tgt.clone().index_add_(axis, idx, src)
def _segment_sum(src, seg, n):
    out = torch.zeros((n,) + src.shape[1:], dtype=src.dtype)
    return out.index_add_(0, seg, src)
def _pad(x, pw):
    flat = tuple(v for pair in reversed(pw) for v in pair)
    return torch.nn.functional.pad(x, flat)

kernel_name = 'recurrent_scan__ssm_conv_s4__mixer_channel_mlp__prompt'

def setup_inputs():

    _w = (lambda a: (lambda t: t.to(torch.bfloat16) if t.is_floating_point() else t)(torch.as_tensor(a)))
    def _A_setup():
        B, L, D, N = 1, 2048, 448, 256
        A_re = -(lambda _x: torch.exp(torch.as_tensor(_x)))((lambda *s: torch.randn(*s, dtype=torch.bfloat16) * 3.2)(D, N))
        A_im = torch.pi * (lambda *s: torch.randn(*s, dtype=torch.bfloat16) * 0.2)(D, N)
        B_re = (lambda *s: torch.randn(*s, dtype=torch.bfloat16) * 0.2)(D, N)
        B_im = (lambda *s: torch.randn(*s, dtype=torch.bfloat16) * 0.2)(D, N)
        C_re = (lambda *s: torch.randn(*s, dtype=torch.bfloat16) * 0.2)(D, N)
        C_im = (lambda *s: torch.randn(*s, dtype=torch.bfloat16) * 0.2)(D, N)
        log_dt = (lambda *s: torch.randn(*s, dtype=torch.bfloat16) * 0.2)(D) * 0.5 - 4.0
        Dskip = (lambda *s: torch.randn(*s, dtype=torch.bfloat16) * 0.2)(D)
        return {
            "u": _w((lambda *s: torch.randn(*s, dtype=torch.bfloat16) * 0.05)(B, L, D)),
            "A_re": _w(A_re),
            "A_im": _w(A_im),
            "B_re": _w(B_re),
            "B_im": _w(B_im),
            "C_re": _w(C_re),
            "C_im": _w(C_im),
            "log_dt": _w(log_dt),
            "Dskip": _w(Dskip),
        }
    _A_in = _A_setup()

    def _B_setup():
        B, S, D, F = 1, 2048, 448, 1792
        return {
            "x": _w((lambda *s: torch.randn(*s, dtype=torch.bfloat16) * 0.05)(B, S, D)),
            "w1": _w((lambda *s: torch.randn(*s, dtype=torch.bfloat16) * 3.2)(D, F) * (D ** -0.5)),
            "b1": _w((lambda *s: torch.randn(*s, dtype=torch.bfloat16) * 1.6)(F)),
            "w2": _w((lambda *s: torch.randn(*s, dtype=torch.bfloat16) * 0.1)(F, D) * (F ** -0.5)),
            "b2": _w((lambda *s: torch.randn(*s, dtype=torch.bfloat16) * 0.2)(D)),
        }
    _B_in = _B_setup()

    return {
        "A_u": _A_in["u"],
        "A_A_re": _A_in["A_re"],
        "A_A_im": _A_in["A_im"],
        "A_B_re": _A_in["B_re"],
        "A_B_im": _A_in["B_im"],
        "A_C_re": _A_in["C_re"],
        "A_C_im": _A_in["C_im"],
        "A_log_dt": _A_in["log_dt"],
        "A_Dskip": _A_in["Dskip"],
        "B_x": _B_in["x"],
        "B_w1": _B_in["w1"],
        "B_b1": _B_in["b1"],
        "B_w2": _B_in["w2"],
        "B_b2": _B_in["b2"],
    }

def reference(A_u, A_A_re, A_A_im, A_B_re, A_B_im, A_C_re, A_C_im, A_log_dt, A_Dskip, B_x, B_w1, B_b1, B_w2, B_b2):
    def _A_ref(u, A_re, A_im, B_re, B_im, C_re, C_im, log_dt, Dskip):
        Bsz, L, D = u.shape
        dt = torch.exp(log_dt)[:, None]
        A = A_re + 1j * A_im
        Bc = B_re + 1j * B_im
        Cc = C_re + 1j * C_im
        logdA = dt * A
        dB = dt * Bc
        l = (lambda x, dt: x.to(dt))(torch.arange(L), A_re.dtype)
        P = torch.exp(logdA[:, :, None] * l[None, None, :])
        K = torch.einsum("dn,dnl,dn->dl", Cc, P, dB).real
        L2 = 2 * L
        Kp = _pad(K, ((0, 0), (0, L)))
        up = (lambda x, *d: x.permute(*d))(u, 0, 2, 1)
        up = _pad(up, ((0, 0), (0, 0), (0, L)))
        Kf = (lambda x, axes=(-2,-1): torch.fft.rfft2(x.float(), dim=axes))(Kp[:, None, :], axes=(-2, -1))
        Uf = (lambda x, axes=(-2,-1): torch.fft.rfft2(x.float(), dim=axes))(up[:, :, None, :], axes=(-2, -1))
        Yf = Uf * Kf[None, :, :, :]
        y = (lambda x, s, axes=(-2,-1): torch.fft.irfft2(x, s=s, dim=axes).to(torch.bfloat16))(Yf, (1, L2), axes=(-2, -1))[:, :, 0, :L]
        y = (lambda x, *d: x.permute(*d))(y, 0, 2, 1) + u * Dskip[None, None, :]
        return y

    def _B_ref(x, w1, b1, w2, b2):
        y = _layernorm(x, axis=-1)
        h = _gelu(torch.einsum("bsd,df->bsf", y, w1) + b1)
        return torch.einsum("bsf,fd->bsd", h, w2) + b2

    x = A_u
    xn = _layernorm(x, axis=-1)
    s = _A_ref(xn, A_A_re, A_A_im, A_B_re, A_B_im, A_C_re, A_C_im, A_log_dt, A_Dskip)
    g = _silu(_B_ref(xn, B_w1, B_b1, B_w2, B_b2))
    return x + s * g
```

```cpp
#include <cuda_runtime.h>
#include <cuda_bf16.h>
#include <cuda_fp16.h>
#include <cuda.h>
#include <stdint.h>

namespace {

constexpr int D_ = 448, NST = 256, F_ = 1792;
constexpr int NRK = 7, NMLP = 112, NCTA = 132;
constexpr int SPIN_MAX = 1 << 21;

__device__ uint4 g_xnT[128 * 448 * 2];
__device__ float2 g_stats[2048];
__device__ float g_cs[F_];
__device__ uint4 g_part[16 * 7 * 6 * 1024];
__device__ uint4 g_s2[16 * 224 * 32];
__device__ unsigned g_cntA;
__device__ unsigned g_cntB[16 * 32];
__device__ unsigned g_epoch;
#define TSTAMP(i)

constexpr int TBL = 5248;
constexpr int TBL_C1 = 2624;
constexpr int SIG = 17536;
constexpr int SIG_U = 0, U_LBO = 656, SIG_V3 = 5248, SIG_V5 = 8320, SIG_V7 = 11392, SIG_V9 = 13440, SIG_V2 = 15488;
constexpr int Y2B = 6528, Y3B = 4352;
constexpr int KREC = 160, KSTG = 32 * KREC;
constexpr int OFF_W = 0, OFF_X = 98304, OFF_A = 147456, OFF_B = 188416, OFF_C = 203008, OFF_FF = 209536, OFF_M = 217728;
constexpr int M_BC = 0, M_RS = 2048, M_B2 = 3072, M_BAR = 3328, M_REL = 3456, M_SC = 3520, M_CSR = 3712, M_END = 4096;
constexpr int SMEM_BYTES = OFF_M + M_END + 1024;
constexpr int S_WORK = 65536, S_WGB = 28672;

struct Params {
  const __nv_bfloat16 *x, *a_re, *a_im, *b_re, *b_im, *c_re, *c_im, *log_dt, *dskip, *w1, *b1, *w2, *b2;
};

__device__ __forceinline__ uint32_t smem_u32(const void* p) { return (uint32_t)__cvta_generic_to_shared(p); }
__device__ __forceinline__ void mbar_init(uint32_t bar, int cnt) { asm volatile("mbarrier.init.shared::cta.b64 [%0], %1;" ::"r"(bar), "r"(cnt)); }
__device__ __forceinline__ void mbar_expect(uint32_t bar, uint32_t bytes) {
  asm volatile("mbarrier.arrive.expect_tx.shared::cta.b64 _, [%0], %1;" ::"r"(bar), "r"(bytes) : "memory");
}
__device__ __forceinline__ void mbar_wait(uint32_t bar, uint32_t parity) {
  uint32_t done = 0;
  for (int it = 0; it < SPIN_MAX; it++) {
    asm volatile("{.reg .pred p; mbarrier.try_wait.parity.shared::cta.b64 p, [%1], %2; selp.u32 %0,1,0,p;}"
                 : "=r"(done) : "r"(bar), "r"(parity) : "memory");
    if (done) break;
  }
}
__device__ __forceinline__ void tma_2d(uint32_t dst, const CUtensorMap* m, int c0, int c1, uint32_t bar) {
  asm volatile("cp.async.bulk.tensor.2d.shared::cluster.global.mbarrier::complete_tx::bytes [%0], [%1, {%3, %4}], [%2];"
               ::"r"(dst), "l"(m), "r"(bar), "r"(c0), "r"(c1) : "memory");
}
__device__ __forceinline__ void tma_3d(uint32_t dst, const CUtensorMap* m, int c0, int c1, int c2, uint32_t bar) {
  asm volatile("cp.async.bulk.tensor.3d.shared::cluster.global.mbarrier::complete_tx::bytes [%0], [%1, {%3, %4, %5}], [%2];"
               ::"r"(dst), "l"(m), "r"(bar), "r"(c0), "r"(c1), "r"(c2) : "memory");
}
__device__ __forceinline__ void tma_store_2d(const CUtensorMap* m, uint32_t src, int c0, int c1) {
  asm volatile("cp.async.bulk.tensor.2d.global.shared::cta.bulk_group [%0, {%2, %3}], [%1];"
               ::"l"(m), "r"(src), "r"(c0), "r"(c1) : "memory");
}
__device__ __forceinline__ void bulk_s2g(void* dst, uint32_t src, uint32_t bytes) {
  asm volatile("cp.async.bulk.global.shared::cta.bulk_group [%0], [%1], %2;" ::"l"(dst), "r"(src), "r"(bytes) : "memory");
}
__device__ __forceinline__ void bulk_commit() { asm volatile("cp.async.bulk.commit_group;" ::: "memory"); }
__device__ __forceinline__ void bulk_wait0() { asm volatile("cp.async.bulk.wait_group 0;" ::: "memory"); }
__device__ __forceinline__ void bulk_wait0_read() { asm volatile("cp.async.bulk.wait_group.read 0;" ::: "memory"); }
__device__ __forceinline__ void fence_async() { asm volatile("fence.proxy.async.shared::cta;" ::: "memory"); }
__device__ __forceinline__ void bar_sync(int id, int n) { asm volatile("bar.sync %0, %1;" ::"r"(id), "r"(n) : "memory"); }
__device__ __forceinline__ void bar_arrive(int id, int n) { asm volatile("bar.arrive %0, %1;" ::"r"(id), "r"(n) : "memory"); }
__device__ __forceinline__ void wg_fence() { asm volatile("wgmma.fence.sync.aligned;" ::: "memory"); }
__device__ __forceinline__ void wg_commit() { asm volatile("wgmma.commit_group.sync.aligned;" ::: "memory"); }
template <int N> __device__ __forceinline__ void wg_wait() { asm volatile("wgmma.wait_group.sync.aligned %0;" ::"n"(N) : "memory"); }
template <int N> __device__ __forceinline__ void fence_regs(float* d) {
#pragma unroll
  for (int i = 0; i < N; i++) asm volatile("" : "+f"(d[i])::"memory");
}
__device__ __forceinline__ uint64_t mkdesc(uint32_t addr, uint32_t lbo, uint32_t sbo, uint32_t sw) {
  return (uint64_t)((addr & 0x3FFFF) >> 4) | ((uint64_t)(lbo >> 4) << 16) | ((uint64_t)(sbo >> 4) << 32) | ((uint64_t)sw << 62);
}
__device__ __forceinline__ uint32_t lds32(uint32_t a) { uint32_t v; asm volatile("ld.shared.b32 %0, [%1];" : "=r"(v) : "r"(a) : "memory"); return v; }
__device__ __forceinline__ float lds32f(uint32_t a) { float v; asm volatile("ld.shared.f32 %0, [%1];" : "=f"(v) : "r"(a) : "memory"); return v; }
__device__ __forceinline__ float2 lds64f(uint32_t a) { float2 v; asm volatile("ld.shared.v2.f32 {%0,%1}, [%2];" : "=f"(v.x), "=f"(v.y) : "r"(a) : "memory"); return v; }
__device__ __forceinline__ uint4 lds128(uint32_t a) {
  uint4 v; asm volatile("ld.shared.v4.b32 {%0,%1,%2,%3}, [%4];" : "=r"(v.x), "=r"(v.y), "=r"(v.z), "=r"(v.w) : "r"(a) : "memory"); return v;
}
__device__ __forceinline__ void sts16(uint32_t a, uint16_t v) { asm volatile("st.shared.b16 [%0], %1;" ::"r"(a), "h"(v) : "memory"); }
__device__ __forceinline__ void sts32f(uint32_t a, float v) { asm volatile("st.shared.f32 [%0], %1;" ::"r"(a), "f"(v) : "memory"); }
__device__ __forceinline__ void sts64f(uint32_t a, float x, float y) { asm volatile("st.shared.v2.f32 [%0], {%1,%2};" ::"r"(a), "f"(x), "f"(y) : "memory"); }
__device__ __forceinline__ void sts128(uint32_t a, uint32_t x, uint32_t y, uint32_t z, uint32_t w) {
  asm volatile("st.shared.v4.b32 [%0], {%1,%2,%3,%4};" ::"r"(a), "r"(x), "r"(y), "r"(z), "r"(w) : "memory");
}
__device__ __forceinline__ void ldsm4(uint32_t a, uint32_t& r0, uint32_t& r1, uint32_t& r2, uint32_t& r3) {
  asm volatile("ldmatrix.sync.aligned.m8n8.x4.shared.b16 {%0,%1,%2,%3}, [%4];" : "=r"(r0), "=r"(r1), "=r"(r2), "=r"(r3) : "r"(a) : "memory");
}
__device__ __forceinline__ void ldsm4t(uint32_t a, uint32_t& r0, uint32_t& r1, uint32_t& r2, uint32_t& r3) {
  asm volatile("ldmatrix.sync.aligned.m8n8.x4.trans.shared.b16 {%0,%1,%2,%3}, [%4];" : "=r"(r0), "=r"(r1), "=r"(r2), "=r"(r3) : "r"(a) : "memory");
}
__device__ __forceinline__ void stsm4(uint32_t a, uint32_t r0, uint32_t r1, uint32_t r2, uint32_t r3) {
  asm volatile("stmatrix.sync.aligned.m8n8.x4.shared.b16 [%0], {%1,%2,%3,%4};" ::"r"(a), "r"(r0), "r"(r1), "r"(r2), "r"(r3) : "memory");
}
__device__ __forceinline__ void mma_f16(float* c, uint32_t a0, uint32_t a1, uint32_t a2, uint32_t a3, uint32_t b0, uint32_t b1) {
  asm volatile("mma.sync.aligned.m16n8k16.row.col.f32.f16.f16.f32 {%0,%1,%2,%3},{%4,%5,%6,%7},{%8,%9},{%0,%1,%2,%3};"
               : "+f"(c[0]), "+f"(c[1]), "+f"(c[2]), "+f"(c[3]) : "r"(a0), "r"(a1), "r"(a2), "r"(a3), "r"(b0), "r"(b1));
}
__device__ __forceinline__ uint4 ld_relaxed4(const void* p) {
  uint4 v; asm volatile("ld.relaxed.gpu.global.v4.b32 {%0,%1,%2,%3}, [%4];" : "=r"(v.x), "=r"(v.y), "=r"(v.z), "=r"(v.w) : "l"(p) : "memory"); return v;
}
__device__ __forceinline__ uint2 ld_relaxed2(const void* p) {
  uint2 v; asm volatile("ld.relaxed.gpu.global.v2.b32 {%0,%1}, [%2];" : "=r"(v.x), "=r"(v.y) : "l"(p) : "memory"); return v;
}
__device__ __forceinline__ void st_relaxed4(void* p, uint32_t x, uint32_t y, uint32_t z, uint32_t w) {
  asm volatile("st.relaxed.gpu.global.v4.b32 [%0], {%1,%2,%3,%4};" ::"l"(p), "r"(x), "r"(y), "r"(z), "r"(w) : "memory");
}
__device__ __forceinline__ unsigned ld_acquire(const unsigned* p) {
  unsigned v; asm volatile("ld.acquire.gpu.global.u32 %0, [%1];" : "=r"(v) : "l"(p) : "memory"); return v;
}
__device__ __forceinline__ void red_release(unsigned* p) {
  asm volatile("red.release.gpu.global.add.u32 [%0], 1;" ::"l"(p) : "memory");
}
__device__ __forceinline__ void wait_count(const unsigned* p, unsigned target) {
  for (int it = 0; it < SPIN_MAX; it++) {
    if ((int)(ld_acquire(p) - target) >= 0) break;
  }
}
__device__ __forceinline__ uint32_t pack_h2(float lo, float hi) { uint32_t r; asm("cvt.rn.f16x2.f32 %0, %1, %2;" : "=r"(r) : "f"(hi), "f"(lo)); return r; }
__device__ __forceinline__ uint32_t pack_bf2(float lo, float hi) { uint32_t r; asm("cvt.rn.bf16x2.f32 %0, %1, %2;" : "=r"(r) : "f"(hi), "f"(lo)); return r; }
__device__ __forceinline__ float bf_lo(uint32_t w) { return __uint_as_float(w << 16); }
__device__ __forceinline__ float bf_hi(uint32_t w) { return __uint_as_float(w & 0xffff0000u); }
__device__ __forceinline__ float rbf(float v) { return __bfloat162float(__float2bfloat16_rn(v)); }
__device__ __forceinline__ float2 h2f(uint32_t w) { return __half22float2(*reinterpret_cast<__half2*>(&w)); }
__device__ __forceinline__ float ex2f(float v) { float r; asm("ex2.approx.ftz.f32 %0, %1;" : "=f"(r) : "f"(v)); return r; }
__device__ __forceinline__ float tanhf_(float v) { float r; asm("tanh.approx.f32 %0, %1;" : "=f"(r) : "f"(v)); return r; }
__device__ __forceinline__ uint32_t umax3(uint32_t a, uint32_t b, uint32_t c) { return max(max(a, b), c); }

__device__ __forceinline__ void wg_ss_bf16_n256(float* d, uint64_t da, uint64_t db, int sc) {
  asm volatile("{.reg .pred p; setp.ne.b32 p, %130, 0;\n"
    "wgmma.mma_async.sync.aligned.m64n256k16.f32.bf16.bf16 {%0, %1, %2, %3, %4, %5, %6, %7, %8, %9, %10, %11, %12, %13, %14, %15, %16, %17, %18, %19, %20, %21, %22, %23, %24, %25, %26, %27, %28, %29, %30, %31, %32, %33, %34, %35, %36, %37, %38, %39, %40, %41, %42, %43, %44, %45, %46, %47, %48, %49, %50, %51, %52, %53, %54, %55, %56, %57, %58, %59, %60, %61, %62, %63, %64, %65, %66, %67, %68, %69, %70, %71, %72, %73, %74, %75, %76, %77, %78, %79, %80, %81, %82, %83, %84, %85, %86, %87, %88, %89, %90, %91, %92, %93, %94, %95, %96, %97, %98, %99, %100, %101, %102, %103, %104, %105, %106, %107, %108, %109, %110, %111, %112, %113, %114, %115, %116, %117, %118, %119, %120, %121, %122, %123, %124, %125, %126, %127}, %128, %129, p, 1, 1, 0, 1;}\n"
    : "+f"(d[0]), "+f"(d[1]), "+f"(d[2]), "+f"(d[3]), "+f"(d[4]), "+f"(d[5]), "+f"(d[6]), "+f"(d[7]), "+f"(d[8]), "+f"(d[9]), "+f"(d[10]), "+f"(d[11]), "+f"(d[12]), "+f"(d[13]), "+f"(d[14]), "+f"(d[15]), "+f"(d[16]), "+f"(d[17]), "+f"(d[18]), "+f"(d[19]), "+f"(d[20]), "+f"(d[21]), "+f"(d[22]), "+f"(d[23]), "+f"(d[24]), "+f"(d[25]), "+f"(d[26]), "+f"(d[27]), "+f"(d[28]), "+f"(d[29]), "+f"(d[30]), "+f"(d[31]), "+f"(d[32]), "+f"(d[33]), "+f"(d[34]), "+f"(d[35]), "+f"(d[36]), "+f"(d[37]), "+f"(d[38]), "+f"(d[39]), "+f"(d[40]), "+f"(d[41]), "+f"(d[42]), "+f"(d[43]), "+f"(d[44]), "+f"(d[45]), "+f"(d[46]), "+f"(d[47]), "+f"(d[48]), "+f"(d[49]), "+f"(d[50]), "+f"(d[51]), "+f"(d[52]), "+f"(d[53]), "+f"(d[54]), "+f"(d[55]), "+f"(d[56]), "+f"(d[57]), "+f"(d[58]), "+f"(d[59]), "+f"(d[60]), "+f"(d[61]), "+f"(d[62]), "+f"(d[63]), "+f"(d[64]), "+f"(d[65]), "+f"(d[66]), "+f"(d[67]), "+f"(d[68]), "+f"(d[69]), "+f"(d[70]), "+f"(d[71]), "+f"(d[72]), "+f"(d[73]), "+f"(d[74]), "+f"(d[75]), "+f"(d[76]), "+f"(d[77]), "+f"(d[78]), "+f"(d[79]), "+f"(d[80]), "+f"(d[81]), "+f"(d[82]), "+f"(d[83]), "+f"(d[84]), "+f"(d[85]), "+f"(d[86]), "+f"(d[87]), "+f"(d[88]), "+f"(d[89]), "+f"(d[90]), "+f"(d[91]), "+f"(d[92]), "+f"(d[93]), "+f"(d[94]), "+f"(d[95]), "+f"(d[96]), "+f"(d[97]), "+f"(d[98]), "+f"(d[99]), "+f"(d[100]), "+f"(d[101]), "+f"(d[102]), "+f"(d[103]), "+f"(d[104]), "+f"(d[105]), "+f"(d[106]), "+f"(d[107]), "+f"(d[108]), "+f"(d[109]), "+f"(d[110]), "+f"(d[111]), "+f"(d[112]), "+f"(d[113]), "+f"(d[114]), "+f"(d[115]), "+f"(d[116]), "+f"(d[117]), "+f"(d[118]), "+f"(d[119]), "+f"(d[120]), "+f"(d[121]), "+f"(d[122]), "+f"(d[123]), "+f"(d[124]), "+f"(d[125]), "+f"(d[126]), "+f"(d[127])
    : "l"(da), "l"(db), "r"(sc));
}

__device__ __forceinline__ void wg_rs_bf16_n64(float* d, uint32_t a0, uint32_t a1, uint32_t a2, uint32_t a3, uint64_t db, int sc) {
  asm volatile("{.reg .pred p; setp.ne.b32 p, %37, 0;\n"
    "wgmma.mma_async.sync.aligned.m64n64k16.f32.bf16.bf16 {%0, %1, %2, %3, %4, %5, %6, %7, %8, %9, %10, %11, %12, %13, %14, %15, %16, %17, %18, %19, %20, %21, %22, %23, %24, %25, %26, %27, %28, %29, %30, %31}, {%32,%33,%34,%35}, %36, p, 1, 1, 1;}\n"
    : "+f"(d[0]), "+f"(d[1]), "+f"(d[2]), "+f"(d[3]), "+f"(d[4]), "+f"(d[5]), "+f"(d[6]), "+f"(d[7]), "+f"(d[8]), "+f"(d[9]), "+f"(d[10]), "+f"(d[11]), "+f"(d[12]), "+f"(d[13]), "+f"(d[14]), "+f"(d[15]), "+f"(d[16]), "+f"(d[17]), "+f"(d[18]), "+f"(d[19]), "+f"(d[20]), "+f"(d[21]), "+f"(d[22]), "+f"(d[23]), "+f"(d[24]), "+f"(d[25]), "+f"(d[26]), "+f"(d[27]), "+f"(d[28]), "+f"(d[29]), "+f"(d[30]), "+f"(d[31])
    : "r"(a0), "r"(a1), "r"(a2), "r"(a3), "l"(db), "r"(sc));
}

__device__ __forceinline__ void wg_rs_f16_n32k(float* d, uint32_t a0, uint32_t a1, uint32_t a2, uint32_t a3, uint64_t db, int sc) {
  asm volatile("{.reg .pred p; setp.ne.b32 p, %21, 0;\n"
    "wgmma.mma_async.sync.aligned.m64n32k16.f32.f16.f16 {%0, %1, %2, %3, %4, %5, %6, %7, %8, %9, %10, %11, %12, %13, %14, %15}, {%16,%17,%18,%19}, %20, p, 1, 1, 0;}\n"
    : "+f"(d[0]), "+f"(d[1]), "+f"(d[2]), "+f"(d[3]), "+f"(d[4]), "+f"(d[5]), "+f"(d[6]), "+f"(d[7]), "+f"(d[8]), "+f"(d[9]), "+f"(d[10]), "+f"(d[11]), "+f"(d[12]), "+f"(d[13]), "+f"(d[14]), "+f"(d[15])
    : "r"(a0), "r"(a1), "r"(a2), "r"(a3), "l"(db), "r"(sc));
}

__device__ __forceinline__ void wg_rs_f16_n24t(float* d, uint32_t a0, uint32_t a1, uint32_t a2, uint32_t a3, uint64_t db, int sc) {
  asm volatile("{.reg .pred p; setp.ne.b32 p, %17, 0;\n"
    "wgmma.mma_async.sync.aligned.m64n24k16.f32.f16.f16 {%0, %1, %2, %3, %4, %5, %6, %7, %8, %9, %10, %11}, {%12,%13,%14,%15}, %16, p, 1, 1, 1;}\n"
    : "+f"(d[0]), "+f"(d[1]), "+f"(d[2]), "+f"(d[3]), "+f"(d[4]), "+f"(d[5]), "+f"(d[6]), "+f"(d[7]), "+f"(d[8]), "+f"(d[9]), "+f"(d[10]), "+f"(d[11])
    : "r"(a0), "r"(a1), "r"(a2), "r"(a3), "l"(db), "r"(sc));
}

__device__ __forceinline__ void wg_rs_f16_n16t(float* d, uint32_t a0, uint32_t a1, uint32_t a2, uint32_t a3, uint64_t db, int sc) {
  asm volatile("{.reg .pred p; setp.ne.b32 p, %13, 0;\n"
    "wgmma.mma_async.sync.aligned.m64n16k16.f32.f16.f16 {%0, %1, %2, %3, %4, %5, %6, %7}, {%8,%9,%10,%11}, %12, p, 1, 1, 1;}\n"
    : "+f"(d[0]), "+f"(d[1]), "+f"(d[2]), "+f"(d[3]), "+f"(d[4]), "+f"(d[5]), "+f"(d[6]), "+f"(d[7])
    : "r"(a0), "r"(a1), "r"(a2), "r"(a3), "l"(db), "r"(sc));
}

struct cf { float x, y; };
__device__ __forceinline__ cf cmul(cf a, cf b) { cf r; r.x = fmaf(a.x, b.x, -a.y * b.y); r.y = fmaf(a.x, b.y, a.y * b.x); return r; }
__device__ __forceinline__ cf zpow(float rho2, float phi, float e) {
  float m = ex2f(rho2 * e);
  float t = phi * e;
  float f = t - __fadd_rn(__fadd_rn(t, 12582912.f), -12582912.f);
  float ang = f * 6.283185307179586f;
  cf r; r.x = m * __cosf(ang); r.y = m * __sinf(ang); return r;
}
__device__ __forceinline__ uint32_t hprod(uint32_t v, uint32_t vr, uint32_t r) {
  __half2 hv = *reinterpret_cast<__half2*>(&v), hvr = *reinterpret_cast<__half2*>(&vr), hr = *reinterpret_cast<__half2*>(&r);
  __half2 o = __hfma2(__high2half2(hr), hvr, __hmul2(__low2half2(hr), hv));
  return *reinterpret_cast<uint32_t*>(&o);
}
__device__ __forceinline__ uint32_t rot90(uint32_t v) { return __byte_perm(v, 0, 0x1032) ^ 0x00008000u; }

__device__ __forceinline__ void chan_scale(const Params& p, int d, int lane, float& dt, float& inv_sc, float& dsk) {
  const uint4 br = __ldg((const uint4*)(p.b_re + d * NST) + lane), bi = __ldg((const uint4*)(p.b_im + d * NST) + lane);
  const uint4 cr = __ldg((const uint4*)(p.c_re + d * NST) + lane), ci = __ldg((const uint4*)(p.c_im + d * NST) + lane);
  const uint32_t M = 0x7fff7fffu;
  uint32_t mb = __vmaxu2(__vmaxu2(__vmaxu2(br.x & M, br.y & M), __vmaxu2(br.z & M, br.w & M)),
                         __vmaxu2(__vmaxu2(bi.x & M, bi.y & M), __vmaxu2(bi.z & M, bi.w & M)));
  uint32_t mc = __vmaxu2(__vmaxu2(__vmaxu2(cr.x & M, cr.y & M), __vmaxu2(cr.z & M, cr.w & M)),
                         __vmaxu2(__vmaxu2(ci.x & M, ci.y & M), __vmaxu2(ci.z & M, ci.w & M)));
  mb = max(mb & 0xffffu, mb >> 16);
  mc = max(mc & 0xffffu, mc >> 16);
  mb = __reduce_max_sync(0xffffffffu, mb);
  mc = __reduce_max_sync(0xffffffffu, mc);
  dt = rbf(__expf(__bfloat162float(p.log_dt[d])));
  dsk = __bfloat162float(p.dskip[d]) / dt;
  float sc = fmaxf(2.f * __uint_as_float(mb << 16) * __uint_as_float(mc << 16), fabsf(dsk) * (1.f / 256.f)) * (1.f / 16.f);
  sc = fminf(fmaxf(sc, 1e-30f), 1e30f);
  inv_sc = 1.f / sc;
}

__device__ __forceinline__ void kgen_warp(const Params& p, int d, int wd0, int nw, float dt, float inv_sc, uint32_t stg, int lane, float* acc) {
  const int tq = lane & 3;
  const uint32_t st_base = stg + lane * KREC;
  const uint32_t st_x = ((lane >> 2) & 1) << 4;
  const int mat = lane >> 3, rowi = lane & 7;
  const uint32_t ld_base = stg + (4 * (mat & 1) + (rowi >> 1)) * KREC + ((((mat >> 1) * 2 + (rowi & 1)) << 4) ^ ((mat & 1) << 4));
  const uint32_t cb_lo = stg + tq * KREC + 128, cb_hi = stg + (tq + 4) * KREC + 144;
  const int off = d * (NST / 2) + lane * 4;
  const uint32_t* P[6] = {(const uint32_t*)p.a_re, (const uint32_t*)p.a_im, (const uint32_t*)p.b_re,
                          (const uint32_t*)p.b_im, (const uint32_t*)p.c_re, (const uint32_t*)p.c_im};
  uint32_t cur[6], nxt[6];
#pragma unroll
  for (int i = 0; i < 6; i++) nxt[i] = __ldg(P[i] + off + wd0);
  const float dl = dt * 1.4426950408889634f, dp = dt * 0.15915494309189535f;
#pragma unroll 1
  for (int it = 0; it < 2 * nw; it++) {
    if ((it & 1) == 0) {
#pragma unroll
      for (int i = 0; i < 6; i++) cur[i] = nxt[i];
      if (it + 2 < 2 * nw) {
#pragma unroll
        for (int i = 0; i < 6; i++) nxt[i] = __ldg(P[i] + off + wd0 + (it >> 1) + 1);
      }
    } else {
#pragma unroll
      for (int i = 0; i < 6; i++) cur[i] >>= 16;
    }
    const float rho2 = bf_lo(cur[0]) * dl, phi = bf_lo(cur[1]) * dp;
    cf bb = {bf_lo(cur[2]) * inv_sc, bf_lo(cur[3]) * inv_sc}, cc = {bf_lo(cur[4]), bf_lo(cur[5])};
    cf X[8];
    X[0] = cmul(cc, bb);
    const cf z1 = zpow(rho2, phi, 1.f), z8 = zpow(rho2, phi, 8.f), z64 = zpow(rho2, phi, 64.f);
    const cf y1 = zpow(rho2, phi, 256.f), y4 = zpow(rho2, phi, 1024.f);
    const cf z2 = cmul(z1, z1);
    X[1] = cmul(X[0], z1);
#pragma unroll
    for (int j = 2; j < 8; j++) X[j] = cmul(X[j - 2], z2);
    __syncwarp();
    sts128(st_base + (0 ^ st_x), pack_h2(X[0].x, X[1].x), pack_h2(X[2].x, X[3].x), pack_h2(X[4].x, X[5].x), pack_h2(X[6].x, X[7].x));
    sts128(st_base + (16 ^ st_x), pack_h2(-X[0].y, -X[1].y), pack_h2(-X[2].y, -X[3].y), pack_h2(-X[4].y, -X[5].y), pack_h2(-X[6].y, -X[7].y));
    {
      const cf a0 = cmul(X[0], y1), a1 = cmul(X[2], y1), a2 = cmul(X[4], y1), a3 = cmul(X[6], y1);
      const cf a4 = cmul(a0, y1), a5 = cmul(a2, y1);
      const cf a6 = cmul(a4, y1), a7 = cmul(a5, y1);
      sts128(st_base + (32 ^ st_x), pack_h2(a0.x, a1.x), pack_h2(a2.x, a3.x), pack_h2(a4.x, a5.x), pack_h2(a6.x, a7.x));
      sts128(st_base + (48 ^ st_x), pack_h2(-a0.y, -a1.y), pack_h2(-a2.y, -a3.y), pack_h2(-a4.y, -a5.y), pack_h2(-a6.y, -a7.y));
      const cf v0 = cmul(X[0], y4), v1 = cmul(a0, y4), v2 = cmul(a4, y4), v3 = cmul(a6, y4), v4 = cmul(v0, y4);
      sts128(st_base + (64 ^ st_x), pack_h2(v0.x, v1.x), pack_h2(v2.x, v3.x), pack_h2(v4.x, 0.f), 0u);
      sts128(st_base + (80 ^ st_x), pack_h2(-v0.y, -v1.y), pack_h2(-v2.y, -v3.y), pack_h2(-v4.y, 0.f), 0u);
    }
    {
      const cf f2 = cmul(z8, z8), f3 = cmul(f2, z8), f4 = cmul(f2, f2), f5 = cmul(f3, f2), f6 = cmul(f4, f2), f7 = cmul(f4, f3);
      sts128(st_base + (96 ^ st_x), pack_h2(1.f, z8.x), pack_h2(f2.x, f3.x), pack_h2(f4.x, f5.x), pack_h2(f6.x, f7.x));
      sts128(st_base + (112 ^ st_x), pack_h2(0.f, z8.y), pack_h2(f2.y, f3.y), pack_h2(f4.y, f5.y), pack_h2(f6.y, f7.y));
      const cf z128 = cmul(z64, z64), z192 = cmul(z128, z64);
      sts128(st_base + 128 + st_x, pack_h2(z64.x, z64.y), pack_h2(z128.x, z128.y), pack_h2(z192.x, z192.y), 0u);
    }
    __syncwarp();
#pragma unroll
    for (int ks = 0; ks < 4; ks++) {
      uint32_t b00, b01, b10, b11, b20, b21, al, ah;
      ldsm4t(ld_base + ks * 8 * KREC, b00, b01, b10, b11);
      ldsm4t(ld_base + ks * 8 * KREC + 64, b20, b21, al, ah);
      const uint4 rl = lds128(cb_lo + ks * 8 * KREC), rh = lds128(cb_hi + ks * 8 * KREC);
      const uint32_t alr = rot90(al), ahr = rot90(ah);
      const uint32_t a1 = hprod(al, alr, rl.x), a3 = hprod(ah, ahr, rh.x);
      const uint32_t c0 = hprod(al, alr, rl.y), c2 = hprod(ah, ahr, rh.y);
      const uint32_t c1 = hprod(al, alr, rl.z), c3 = hprod(ah, ahr, rh.z);
      mma_f16(acc + 0, al, a1, ah, a3, b00, b01);
      mma_f16(acc + 4, al, a1, ah, a3, b10, b11);
      mma_f16(acc + 8, al, a1, ah, a3, b20, b21);
      mma_f16(acc + 12, c0, c1, c2, c3, b00, b01);
      mma_f16(acc + 16, c0, c1, c2, c3, b10, b11);
      mma_f16(acc + 20, c0, c1, c2, c3, b20, b21);
    }
  }
}

__device__ __forceinline__ void tput(uint32_t tbl, int X, uint16_t h) {
  sts16(tbl + 2 * (1296 - X), h);
  sts16(tbl + TBL_C1 + 2 * (1297 - X), h);
}
__device__ __forceinline__ void ktab_scatter(const float* acc, int mt, uint32_t tbl, uint32_t k1024_addr, float skip, int lane) {
  const int g = lane >> 2, tq = lane & 3;
#pragma unroll
  for (int c = 0; c < 4; c++) {
    const int r = 16 * mt + g + 8 * (c >> 1), e = c & 1;
    float v0 = acc[c];
    if (r == 0 && tq == 0 && e == 0) v0 += skip;
    tput(tbl, 64 + 8 * r + 2 * tq + e, __half_as_ushort(__float2half_rn(v0)));
    const uint16_t h1 = __half_as_ushort(__float2half_rn(acc[4 + c]));
    if (e == 1) {
      tput(tbl, tq < 2 ? 64 + 256 + 8 * r + 4 * tq + 2 : 720 + 32 * (tq - 2) + r, h1);
    } else if (tq < 2) {
      const int X = 64 + 256 + 8 * r + 4 * tq;
      tput(tbl, X, h1); tput(tbl, X + 1, h1);
      if (X != 64 + 256) tput(tbl, X - 1, h1);
    } else {
      const int k = 32 * (tq - 2) + r - 1;
      if (k >= 0) tput(tbl, 912 + k, h1);
      else { tput(tbl, 64 + 511, h1); tput(tbl, 64 + 512, h1); tput(tbl, 64 + 513, h1); tput(tbl, 64 + 514, h1); }
    }
    const uint16_t h2 = __half_as_ushort(__float2half_rn(acc[8 + c]));
    if (tq < 2) {
      const int col = 2 * tq + e;
      const int k = 16 * col + (r >> 1) - 1;
      if (r & 1) tput(tbl, 1104 + k + 1, h2);
      else if (k >= 0) tput(tbl, 1232 + k, h2);
      else { tput(tbl, 912 + 63, h2); sts32f(k1024_addr, acc[8 + c]); }
    } else if (tq == 2 && e == 0 && r == 0) {
      tput(tbl, 1232 + 63, h2);
    }
  }
}

__device__ __forceinline__ void sig_store_u(uint32_t sig, int t, uint4 lo, uint4 hi) {
  const uint32_t a = sig + SIG_U + (2 * (t & 3)) * U_LBO + ((t >> 2) + 9) * 16;
  sts128(a, lo.x, lo.z, hi.x, hi.z);
  sts128(a + U_LBO, lo.y, lo.w, hi.y, hi.w);
  if (t < 72) sts128(sig + SIG_U + (t & 7) * U_LBO + (t >> 3) * 16, 0u, 0u, 0u, 0u);
}
__device__ __forceinline__ void sig_windows(uint32_t sig, int t) {
  if (t >= 96) return;
  float S[41];
  S[0] = 0.f;
#pragma unroll
  for (int c = 0; c < 5; c++) {
    const int kap = 2 * t - 3 + c + 72;
    const uint4 v = lds128(sig + SIG_U + (kap & 7) * U_LBO + (kap >> 3) * 16);
    const uint32_t w[4] = {v.x, v.y, v.z, v.w};
#pragma unroll
    for (int k = 0; k < 4; k++) {
      const float2 f = h2f(w[k]);
      S[8 * c + 2 * k + 1] = S[8 * c + 2 * k] + f.x;
      S[8 * c + 2 * k + 2] = S[8 * c + 2 * k + 1] + f.y;
    }
  }
#define WIN2(j, lo, hi) pack_h2(S[25 + (j) - (lo)] - S[24 + (j) - (hi)], S[26 + (j) - (lo)] - S[25 + (j) - (hi)])
#define WIN8(a, j, lo, hi) sts128(a, WIN2(j, lo, hi), WIN2(j + 2, lo, hi), WIN2(j + 4, lo, hi), WIN2(j + 6, lo, hi))
  WIN8(sig + SIG_V3 + t * 32, 0, 3, 5);
  WIN8(sig + SIG_V3 + t * 32 + 16, 8, 3, 5);
  WIN8(sig + SIG_V5 + t * 32, 0, 6, 10);
  WIN8(sig + SIG_V5 + t * 32 + 16, 8, 6, 10);
  if (t < 64) {
    WIN8(sig + SIG_V7 + t * 16, 0, 5, 11);
    WIN8(sig + SIG_V7 + 1024 + t * 16, 8, 5, 11);
    WIN8(sig + SIG_V9 + t * 16, 0, 12, 20);
    WIN8(sig + SIG_V9 + 1024 + t * 16, 8, 12, 20);
    WIN8(sig + SIG_V2 + t * 16, 0, 3, 4);
    WIN8(sig + SIG_V2 + 1024 + t * 16, 8, 3, 4);
  }
#undef WIN8
#undef WIN2
}

__device__ __forceinline__ void conv_channel(uint32_t tbl, uint32_t sig, uint32_t y2b, uint32_t y3b, float k1024,
                                             int w, int lane, int barid, float* res) {
  const int g = lane >> 2, tq = lane & 3;
  const uint32_t tb = tbl + ((g & 1) ? TBL_C1 + 2 : 0) + 2 * (1296 - (g - 2 * tq)) - 32 * w;
  float a2[12], a3[8];
#pragma unroll
  for (int i = 0; i < 16; i++) res[i] = 0.f;
#pragma unroll
  for (int i = 0; i < 12; i++) a2[i] = 0.f;
#pragma unroll
  for (int nt = 0; nt < 2; nt++)
#pragma unroll
    for (int h = 0; h < 2; h++) {
      const float2 f = h2f(lds32(sig + SIG_V2 + nt * 1024 + (16 * w + 8 * h + g) * 16 + tq * 4));
      a3[4 * nt + 2 * h] = k1024 * f.x;
      a3[4 * nt + 2 * h + 1] = k1024 * f.y;
    }
  const uint64_t dU = mkdesc(sig + SIG_U + 9 * 16, U_LBO, 128, 0);
  const uint64_t dV = mkdesc(sig, 128, 1024, 0);
  fence_regs<16>(res); fence_regs<12>(a2); fence_regs<8>(a3);
#define RM(B, m) lds32(tb - 2 * ((B) + 8 * (m)))
#define DESC_D(n) (dU + (uint64_t)(((2 * (3 - ((n) & 3))) * U_LBO - ((n) >> 2) * 16 + 4096) >> 4) - 256)
#pragma unroll
  for (int bt = 0; bt < 13; bt++) {
    uint32_t Rd[7], Rx[5];
    const int n0 = 3 * bt;
    const int nd = (bt < 12) ? 3 : 1;
#pragma unroll
    for (int i = 0; i < 2 * nd + 1; i++) Rd[i] = RM(64, 2 * (n0 - 3) - 1 + i);
    const int x0 = 2 * bt;
    const int xb = x0 < 8 ? 720 : x0 < 16 ? 912 : x0 < 20 ? 1104 : 1232;
    const int xs = x0 < 8 ? SIG_V3 : x0 < 16 ? SIG_V5 : x0 < 20 ? SIG_V7 : SIG_V9;
    const int xn = x0 < 16 ? (x0 & 7) : (x0 & 3);
    if (bt < 12) {
#pragma unroll
      for (int i = 0; i < 5; i++) Rx[i] = RM(xb, 2 * (xn - 3) - 1 + i);
    }
    wg_fence();
#pragma unroll
    for (int i = 0; i < nd; i++) {
      wg_rs_f16_n32k(res, Rd[2 * i + 1], Rd[2 * i + 2], Rd[2 * i], Rd[2 * i + 1], DESC_D(n0 + i), 1);
      if (bt < 12 && i < 2) {
        const int n = xn + i;
        const uint64_t dx = dV + (uint64_t)((xs + (3 - (n & 3)) * 256) >> 4);
        if (x0 >= 16) wg_rs_f16_n16t(a3, Rx[2 * i + 1], Rx[2 * i + 2], Rx[2 * i], Rx[2 * i + 1], dx, 1);
        else if (n < 4) wg_rs_f16_n24t(a2, Rx[2 * i + 1], Rx[2 * i + 2], Rx[2 * i], Rx[2 * i + 1], dx, 1);
        else wg_rs_f16_n16t(a2 + 4, Rx[2 * i + 1], Rx[2 * i + 2], Rx[2 * i], Rx[2 * i + 1], dx, 1);
      }
    }
    wg_commit();
    wg_wait<1>();
  }
#undef RM
#undef DESC_D
  wg_wait<0>();
  fence_regs<16>(res); fence_regs<12>(a2); fence_regs<8>(a3);
  bar_sync(barid, 128);
#pragma unroll
  for (int a = 0; a < 3; a++)
#pragma unroll
    for (int h = 0; h < 2; h++) {
      const int t = 512 * a + 8 * (16 * w + 8 * h + g) + 2 * tq;
      sts64f(y2b + (t + 8 * (t >> 7)) * 4, a2[4 * a + 2 * h], a2[4 * a + 2 * h + 1]);
    }
#pragma unroll
  for (int nt = 0; nt < 2; nt++)
#pragma unroll
    for (int h = 0; h < 2; h++) {
      const int t = 16 * (16 * w + 8 * h + g) + 8 * nt + 2 * tq;
      sts64f(y3b + (t + 8 * (t >> 7)) * 4, a3[4 * nt + 2 * h], a3[4 * nt + 2 * h + 1]);
    }
  bar_sync(barid, 128);
  const uint32_t go = (136 * tq + 16 * w + g) * 4;
#pragma unroll
  for (int nt = 1; nt < 4; nt++)
#pragma unroll
    for (int c = 0; c < 4; c++) {
      const int o = 64 * (c & 1) + 8 * (c >> 1);
      res[4 * nt + c] += lds32f(y2b + go + (544 * (nt - 1) + o) * 4);
      if (nt >= 2) res[4 * nt + c] += lds32f(y3b + go + (544 * (nt - 2) + o) * 4);
    }
}

__device__ __forceinline__ void write_pair(int pair, const float* r0, float s0, const float* r1, float s1, int w, int lane) {
  const int g = lane >> 2, tq = lane & 3;
#pragma unroll
  for (int nt = 0; nt < 4; nt++) {
    uint4* dst = g_s2 + ((size_t)(4 * nt + tq) * 224 + pair) * 32 + w * 8 + g;
    st_relaxed4(dst, pack_bf2(r0[4 * nt] * s0, r1[4 * nt] * s1), pack_bf2(r0[4 * nt + 2] * s0, r1[4 * nt + 2] * s1),
                pack_bf2(r0[4 * nt + 1] * s0, r1[4 * nt + 1] * s1), pack_bf2(r0[4 * nt + 3] * s0, r1[4 * nt + 3] * s1));
  }
}

__device__ __forceinline__ float red8(float v) {
  v += __shfl_xor_sync(0xffffffffu, v, 1); v += __shfl_xor_sync(0xffffffffu, v, 2); v += __shfl_xor_sync(0xffffffffu, v, 4);
  return v;
}
__device__ __forceinline__ void ln_block(const uint4* v, int rb, uint32_t stg, int w, int lane, int barid) {
  const int rl = 4 * w + (lane >> 3), j = lane & 7;
  float f[56];
#pragma unroll
  for (int i = 0; i < 7; i++) {
    const uint32_t u[4] = {v[i].x, v[i].y, v[i].z, v[i].w};
#pragma unroll
    for (int k = 0; k < 4; k++) { f[8 * i + 2 * k] = bf_lo(u[k]); f[8 * i + 2 * k + 1] = bf_hi(u[k]); }
  }
  float s = 0.f;
#pragma unroll
  for (int i = 0; i < 56; i++) s += f[i];
  const float mean = red8(s) * (1.f / D_);
  float q = 0.f;
#pragma unroll
  for (int i = 0; i < 56; i++) { const float t = f[i] - mean; q = fmaf(t, t, q); }
  const float m1 = rbf(mean);
  const float den = rbf(sqrtf(rbf(rbf(red8(q) * (1.f / D_)) + 1e-5f)));
  const float rden = 1.f / den;
  s = 0.f;
#pragma unroll
  for (int i = 0; i < 56; i += 2) {
    const uint32_t c = pack_bf2(f[i] - m1, f[i + 1] - m1);
    const uint32_t n = pack_bf2(bf_lo(c) * rden, bf_hi(c) * rden);
    f[i] = bf_lo(n); f[i + 1] = bf_hi(n);
    s += f[i] + f[i + 1];
  }
#pragma unroll
  for (int i = 0; i < 7; i++)
    sts128(stg + rl * 912 + (j + 8 * i) * 16, pack_h2(f[8 * i], f[8 * i + 1]), pack_h2(f[8 * i + 2], f[8 * i + 3]),
           pack_h2(f[8 * i + 4], f[8 * i + 5]), pack_h2(f[8 * i + 6], f[8 * i + 7]));
  const float mean2 = red8(s) * (1.f / D_);
  q = 0.f;
#pragma unroll
  for (int i = 0; i < 56; i++) { const float t = f[i] - mean2; q = fmaf(t, t, q); }
  const float m2 = rbf(mean2);
  const float den2 = rbf(sqrtf(rbf(rbf(red8(q) * (1.f / D_)) + 1e-5f)));
  const float rden2 = 1.f / den2;
  if (j == 0) { const float r = rden * rden2; g_stats[16 * rb + rl] = make_float2(r, fmaf(m1, r, m2 * rden2)); }
  bar_sync(barid, 128);
  const uint32_t la = stg + ((lane & 7) + 8 * ((lane >> 3) & 1)) * 912 + (lane >> 4) * 16;
  uint2* dst = (uint2*)(g_xnT + (size_t)rb * 896) + lane;
#pragma unroll
  for (int i = 0; i < 7; i++) {
    const int db = 2 * (7 * w + i);
    uint32_t r0, r1, r2, r3;
    ldsm4t(la + db * 16, r0, r1, r2, r3);
    dst[db * 32] = make_uint2(r0, r1);
    dst[db * 32 + 32] = make_uint2(r2, r3);
  }
}

__device__ __forceinline__ float gelu_tanh(float v) {
  const float t = tanhf_(v * fmaf(v * v, 0.0356774081363001f, 0.7978845608028654f));
  const float hv = 0.5f * v;
  return fmaf(hv, t, hv);
}

__device__ __forceinline__ void recv_part(const uint4* src, float* pre) {
  uint4 v[4];
  for (int it = 0; it < SPIN_MAX; it++) {
#pragma unroll
    for (int q = 0; q < 4; q++) v[q] = ld_relaxed4(src + q * 256);
    uint32_t m = 0;
#pragma unroll
    for (int q = 0; q < 4; q++) m = umax3(umax3(m, v[q].x, v[q].y), v[q].z, v[q].w);
    if (m != 0xffffffffu) break;
  }
#pragma unroll
  for (int q = 0; q < 4; q++) {
    const uint32_t u[4] = {v[q].x, v[q].y, v[q].z, v[q].w};
#pragma unroll
    for (int k = 0; k < 4; k++) { pre[8 * q + 2 * k] += bf_lo(u[k]); pre[8 * q + 2 * k + 1] += bf_hi(u[k]); }
  }
}
__device__ __forceinline__ void send_part(uint4* dst, const float* a) {
#pragma unroll
  for (int q = 0; q < 4; q++)
    st_relaxed4(dst + q * 256, pack_bf2(a[8 * q], a[8 * q + 1]), pack_bf2(a[8 * q + 2], a[8 * q + 3]),
                pack_bf2(a[8 * q + 4], a[8 * q + 5]), pack_bf2(a[8 * q + 6], a[8 * q + 7]));
}

__global__ void __launch_bounds__(384, 1)
fused_kernel(const __grid_constant__ CUtensorMap tm_x, const __grid_constant__ CUtensorMap tm_w1,
             const __grid_constant__ CUtensorMap tm_w2, const __grid_constant__ CUtensorMap tm_out, const Params p) {
  extern __shared__ uint8_t smem_raw[];
  const uint32_t sb = (smem_u32(smem_raw) + 1023) & ~1023u;
  const int tid = threadIdx.x, lane = tid & 31, warp = tid >> 5, wg = tid >> 7, w = warp & 3, t = tid & 127;
  const int b = blockIdx.x;
  const uint32_t ms = sb + OFF_M;

  if (b >= NMLP) {
    const int sidx = b - NMLP;
    const int npair = sidx < 12 ? 6 : 5;
    const int pair0 = 112 + (sidx < 12 ? 6 * sidx : 72 + 5 * (sidx - 12));
    unsigned epoch = 0;
    if (t == 0) epoch = *(volatile unsigned*)&g_epoch;
    if (tid == 0) { __threadfence(); }
    __syncthreads();
    if (tid == 0) red_release(&g_cntA);
    const uint32_t work = sb + S_WORK + wg * S_WGB;
    const int lp = wg + 3 * (w >> 1);
    if (lp < npair) {
      const int d = 2 * (pair0 + lp) + (w & 1);
      const uint32_t tbl = sb + warp * TBL;
      for (int i = lane; i < TBL / 16; i += 32) sts128(tbl + i * 16, 0u, 0u, 0u, 0u);
      float dt, inv_sc, dsk;
      chan_scale(p, d, lane, dt, inv_sc, dsk);
      float acc[24];
#pragma unroll
      for (int i = 0; i < 24; i++) acc[i] = 0.f;
      kgen_warp(p, d, 0, 4, dt, inv_sc, work + w * KSTG, lane, acc);
      ktab_scatter(acc, 0, tbl, ms + M_SC + warp * 8, dsk * inv_sc, lane);
      ktab_scatter(acc + 12, 1, tbl, ms + M_SC + warp * 8, 0.f, lane);
      if (lane == 0) sts32f(ms + M_SC + warp * 8 + 4, dt / inv_sc);
    }
    TSTAMP(1);
    if (t == 0) wait_count(&g_cntA, (epoch + 1) * NCTA);
    bar_sync(4 + wg, 128);
    TSTAMP(2);
#pragma unroll 1
    for (int pi = 0; pi < 2; pi++) {
      const int lpp = wg + 3 * pi;
      if (lpp >= npair) break;
      const int pair = pair0 + lpp;
      const uint4* src = g_xnT + ((size_t)t * 448 + 2 * pair) * 2;
      const uint4 l0 = ld_relaxed4(src), h0 = ld_relaxed4(src + 1), l1 = ld_relaxed4(src + 2), h1 = ld_relaxed4(src + 3);
      float r0[16], r1[16];
      float2 sc[2];
#pragma unroll
      for (int c = 0; c < 2; c++) {
        sig_store_u(work, t, c ? l1 : l0, c ? h1 : h0);
        bar_sync(4 + wg, 128);
        sig_windows(work, t);
        fence_async();
        bar_sync(4 + wg, 128);
        const int cw = 4 * wg + 2 * pi + c;
        sc[c] = lds64f(ms + M_SC + cw * 8);
        conv_channel(sb + cw * TBL, work, work + SIG, work + SIG + Y2B, sc[c].x, w, lane, 4 + wg, c ? r1 : r0);
      }
      write_pair(pair, r0, sc[0].y, r1, sc[1].y, w, lane);
      TSTAMP(3 + pi);
    }
    return;
  }

  const int G = b / NRK, rk = b - G * NRK;
  const uint32_t bar0 = ms + M_BAR;
  const int kc0 = (G + rk) % 7;
  if (tid == 0) {
    for (int i = 0; i < 15; i++) mbar_init(bar0 + 8 * i, 1);
    for (int i = 0; i < 10; i++) asm volatile("st.shared.b32 [%0], 0;" ::"r"(ms + M_REL + 4 * i) : "memory");
    asm volatile("fence.mbarrier_init.release.cluster;" ::: "memory");
    fence_async();
    for (int s = 0; s < 3; s++) {
      const int kc = (kc0 + s) % 7;
      mbar_expect(bar0 + 8 * s, 49152);
      tma_2d(sb + OFF_X + s * 16384, &tm_x, 64 * kc, 128 * G, bar0 + 8 * s);
      tma_3d(sb + OFF_W + s * 32768, &tm_w1, 0, 64 * kc, 4 * rk, bar0 + 8 * s);
    }
  }

  if (wg == 2) {
    asm volatile("setmaxnreg.dec.sync.aligned.u32 104;");
    unsigned epoch = 0;
    if (t == 0) epoch = *(volatile unsigned*)&g_epoch;
    uint4 xv[7], wv[7];
    {
      const uint4* xr = (const uint4*)(p.x + (size_t)(16 * b + 4 * w + (lane >> 3)) * D_) + (lane & 7);
      const uint4* wr = (const uint4*)(p.w1 + (size_t)(t >> 1) * F_ + 16 * b) + (t & 1);
#pragma unroll
      for (int i = 0; i < 7; i++) xv[i] = __ldg(xr + 8 * i);
#pragma unroll
      for (int i = 0; i < 7; i++) wv[i] = __ldg(wr + (size_t)i * 64 * (F_ / 8));
    }
#pragma unroll
    for (int i = 0; i < 4; i++) sts128(sb + OFF_FF + (t + 128 * i) * 16, ~0u, ~0u, ~0u, ~0u);
    fence_async();
    __syncthreads();
    if (t == 0) {
      uint8_t* dst = (uint8_t*)(g_s2 + ((size_t)G * 224 + 32 * rk) * 32);
      bulk_s2g(dst, sb + OFF_FF, 8192);
      bulk_s2g(dst + 8192, sb + OFF_FF, 8192);
      bulk_commit();
      asm volatile("cp.async.bulk.prefetch.L2.global [%0], %1;" ::"l"(p.w2 + (size_t)(256 * rk + 16 * G) * D_), "r"(16 * D_ * 2) : "memory");
    }
    {
      float cs[8];
#pragma unroll
      for (int k = 0; k < 8; k++) cs[k] = 0.f;
#pragma unroll
      for (int i = 0; i < 7; i++) {
        const uint32_t u[4] = {wv[i].x, wv[i].y, wv[i].z, wv[i].w};
#pragma unroll
        for (int k = 0; k < 4; k++) { cs[2 * k] += bf_lo(u[k]); cs[2 * k + 1] += bf_hi(u[k]); }
      }
#pragma unroll
      for (int k = 0; k < 8; k++) {
#pragma unroll
        for (int o = 2; o < 32; o <<= 1) cs[k] += __shfl_xor_sync(0xffffffffu, cs[k], o);
      }
      if (lane < 2) {
#pragma unroll
        for (int k = 0; k < 8; k++) sts32f(ms + M_CSR + (w * 16 + lane * 8 + k) * 4, cs[k]);
      }
    }
    ln_block(xv, b, sb + OFF_B, w, lane, 6);
    if (t < 16) g_cs[16 * b + t] = lds32f(ms + M_CSR + t * 4) + lds32f(ms + M_CSR + 64 + t * 4) + lds32f(ms + M_CSR + 128 + t * 4) + lds32f(ms + M_CSR + 192 + t * 4);
    if (b < 16) {
      const uint4* xr = (const uint4*)(p.x + (size_t)(16 * (NMLP + b) + 4 * w + (lane >> 3)) * D_) + (lane & 7);
#pragma unroll
      for (int i = 0; i < 7; i++) xv[i] = __ldg(xr + 8 * i);
      bar_sync(6, 128);
      ln_block(xv, NMLP + b, sb + OFF_B, w, lane, 6);
    }
    bar_sync(6, 128);
    if (t == 0) {
      bulk_wait0();
      __threadfence();
      red_release(&g_cntA);
      uint8_t* dst = (uint8_t*)(g_part + (size_t)(G * 7 + rk) * 6 * 1024);
      for (int i = 0; i < 12; i++) bulk_s2g(dst + i * 8192, sb + OFF_FF, 8192);
      bulk_commit();
    }
    TSTAMP(1);
    for (int i = t; i < 2 * TBL / 16; i += 128) sts128(sb + OFF_B + i * 16, 0u, 0u, 0u, 0u);
    bar_sync(1, 384);
    {
      const int c = w >> 1, mt = w & 1;
      float acc[12];
#pragma unroll
      for (int i = 0; i < 12; i++) {
        const uint32_t a = sb + OFF_A + 4 * c * KSTG + ((12 * mt + i) * 32 + lane) * 4;
        acc[i] = (lds32f(a) + lds32f(a + KSTG)) + (lds32f(a + 2 * KSTG) + lds32f(a + 3 * KSTG));
      }
      ktab_scatter(acc, mt, sb + OFF_B + c * TBL, ms + M_SC + c * 8, lds32f(ms + M_SC + 16 + c * 4), lane);
    }
    TSTAMP(2);
    if (t == 0) {
      wait_count(&g_cntA, (epoch + 1) * NCTA);
      if (b == 0) *(volatile unsigned*)&g_epoch = epoch + 1;
      asm volatile("st.shared.b32 [%0], %1;" ::"r"(ms + M_SC + 32), "r"(epoch) : "memory");
    }
    bar_sync(6, 128);
    TSTAMP(3);
    const uint4* src = g_xnT + ((size_t)t * 448 + 2 * b) * 2;
    const uint4 l0 = ld_relaxed4(src), h0 = ld_relaxed4(src + 1), l1 = ld_relaxed4(src + 2), h1 = ld_relaxed4(src + 3);
    {
      const uint2 st = ld_relaxed2(g_stats + 128 * G + t);
      const uint2 c2 = ld_relaxed2(g_cs + 256 * rk + 2 * t);
      const uint32_t bb = __ldg((const uint32_t*)(p.b1 + 256 * rk) + t);
      sts64f(ms + M_RS + t * 8, __uint_as_float(st.x), __uint_as_float(st.y));
      sts128(ms + M_BC + t * 16, __float_as_uint(bf_lo(bb)), c2.x, __float_as_uint(bf_hi(bb)), c2.y);
      if (t < 64) sts32f(ms + M_B2 + t * 4, __bfloat162float(p.b2[64 * rk + t]));
    }
    bar_arrive(2, 384);
    sig_store_u(sb + OFF_A, t, l0, h0);
    sig_store_u(sb + OFF_A + SIG, t, l1, h1);
    bar_sync(6, 128);
    sig_windows(sb + OFF_A, t);
    sig_windows(sb + OFF_A + SIG, t);
    fence_async();
    if (t == 0) { bulk_wait0(); __threadfence(); red_release(&g_cntB[G * 32]); }
    TSTAMP(4);
    bar_sync(3, 384);
    TSTAMP(5);
    float r0[16], r1[16];
    const float2 s0 = lds64f(ms + M_SC), s1 = lds64f(ms + M_SC + 8);
    conv_channel(sb + OFF_B, sb + OFF_A, sb + OFF_C, sb + OFF_A + 2 * SIG, s0.x, w, lane, 6, r0);
    conv_channel(sb + OFF_B + TBL, sb + OFF_A + SIG, sb + OFF_C, sb + OFF_A + 2 * SIG, s1.x, w, lane, 6, r1);
    write_pair(b, r0, s0.y, r1, s1.y, w, lane);
    TSTAMP(6);
  } else {
    asm volatile("setmaxnreg.inc.sync.aligned.u32 200;");
    __syncthreads();
    {
      const int d = 2 * b + wg;
      float dt, inv_sc, dsk;
      chan_scale(p, d, lane, dt, inv_sc, dsk);
      float acc[24];
#pragma unroll
      for (int i = 0; i < 24; i++) acc[i] = 0.f;
      const uint32_t stg = sb + OFF_A + warp * KSTG;
      kgen_warp(p, d, w, 1, dt, inv_sc, stg, lane, acc);
      __syncwarp();
#pragma unroll
      for (int i = 0; i < 24; i++) sts32f(stg + (i * 32 + lane) * 4, acc[i]);
      if (t == 0) { sts32f(ms + M_SC + wg * 8 + 4, dt / inv_sc); sts32f(ms + M_SC + 16 + wg * 4, dsk * inv_sc); }
      bar_arrive(1, 384);
    }
    TSTAMP(1);
    auto release = [&](int idx) {
      if (lane == 0) {
        unsigned old;
        asm volatile("atom.acq_rel.cta.shared.add.u32 %0, [%1], 1;" : "=r"(old) : "r"(ms + M_REL + 4 * idx) : "memory");
        if (old == 7) {
          if (idx < 4) {
            const int s = idx + 3, kc = (kc0 + s) % 7, sl = idx % 3;
            mbar_expect(bar0 + 8 * s, 49152);
            tma_2d(sb + OFF_X + sl * 16384, &tm_x, 64 * kc, 128 * G, bar0 + 8 * s);
            tma_3d(sb + OFF_W + sl * 32768, &tm_w1, 0, 64 * kc, 4 * rk, bar0 + 8 * s);
          } else {
            const int c = idx < 7 ? idx - 4 : idx - 3;
            const int sl = idx % 3;
            mbar_expect(bar0 + 8 * (7 + c), 32768);
            tma_2d(sb + OFF_W + sl * 32768, &tm_w2, 64 * ((rk + 1 + c) % 7), 256 * rk, bar0 + 8 * (7 + c));
            if (idx == 5) {
              mbar_expect(bar0 + 8 * 14, 16384);
              tma_2d(sb + OFF_X + 2 * 16384, &tm_x, 64 * rk, 128 * G, bar0 + 8 * 14);
            }
            if (idx == 6) {
              mbar_expect(bar0 + 8 * 10, 32768);
              tma_2d(sb + OFF_X, &tm_w2, 64 * ((rk + 4) % 7), 256 * rk, bar0 + 8 * 10);
            }
          }
        }
      }
    };
    uint32_t H[64];
    {
      float acc[128];
#pragma unroll 1
      for (int s = 0; s < 7; s++) {
        const int sl = s % 3;
        mbar_wait(bar0 + 8 * s, 0);
        const uint64_t da = mkdesc(sb + OFF_X + sl * 16384 + wg * 8192, 16, 1024, 1);
        const uint64_t db = mkdesc(sb + OFF_W + sl * 32768, 8192, 1024, 1);
        wg_fence();
#pragma unroll
        for (int k = 0; k < 4; k++) wg_ss_bf16_n256(acc, da + 2 * k, db + 128 * k, (s | k) != 0);
        wg_commit();
        if (s > 0) { wg_wait<1>(); release(s - 1); }
      }
      wg_wait<0>();
      fence_regs<128>(acc);
      release(6);
      bar_arrive(3, 384);
      TSTAMP(2);
      bar_sync(2, 384);
      const int g = lane >> 2, tq = lane & 3;
      const float2 ra = lds64f(ms + M_RS + (64 * wg + 16 * w + g) * 8), rb = lds64f(ms + M_RS + (64 * wg + 16 * w + g + 8) * 8);
#pragma unroll
      for (int i = 0; i < 32; i++) {
        const uint4 bc = lds128(ms + M_BC + (4 * i + tq) * 16);
        const float b0 = __uint_as_float(bc.x), c0 = __uint_as_float(bc.y), b1 = __uint_as_float(bc.z), c1 = __uint_as_float(bc.w);
        const float v00 = fmaf(ra.x, acc[4 * i], fmaf(-ra.y, c0, b0)), v01 = fmaf(ra.x, acc[4 * i + 1], fmaf(-ra.y, c1, b1));
        const float v10 = fmaf(rb.x, acc[4 * i + 2], fmaf(-rb.y, c0, b0)), v11 = fmaf(rb.x, acc[4 * i + 3], fmaf(-rb.y, c1, b1));
        H[2 * i] = pack_bf2(gelu_tanh(v00), gelu_tanh(v01));
        H[2 * i + 1] = pack_bf2(gelu_tanh(v10), gelu_tanh(v11));
      }
    }
    TSTAMP(3);
    float acc2[2][32], pre[32];
#pragma unroll
    for (int i = 0; i < 32; i++) pre[i] = 0.f;
    const uint4* inbox = g_part + (size_t)(G * 7 + rk) * 6 * 1024 + tid;
    auto issue2 = [&](int c, float* acc) {
      const uint32_t base = (c == 3) ? sb + OFF_X : sb + OFF_W + (((c < 3 ? c : c - 1) + 1) % 3) * 32768;
      mbar_wait(bar0 + 8 * (7 + c), 0);
      const uint64_t db = mkdesc(base, 8192, 1024, 1);
      wg_fence();
#pragma unroll
      for (int k = 0; k < 16; k++) wg_rs_bf16_n64(acc, H[4 * k], H[4 * k + 1], H[4 * k + 2], H[4 * k + 3], db + 128 * k, k != 0);
      wg_commit();
    };
    issue2(0, acc2[0]);
    {
      const unsigned epoch = lds32(ms + M_SC + 32);
      if (lane == 0) wait_count(&g_cntB[G * 32], (epoch + 1) * NRK);
      __syncwarp();
    }
#pragma unroll
    for (int s = 0; s < 6; s++) {
      issue2(s + 1, acc2[(s + 1) & 1]);
      wg_wait<1>();
      fence_regs<32>(acc2[s & 1]);
      if (s < 3) release(7 + s);
      send_part(g_part + ((size_t)(G * 7 + (rk + 1 + s) % 7) * 6 + s) * 1024 + tid, acc2[s & 1]);
      if (s >= 3) recv_part(inbox + (s - 3) * 1024, pre);
    }
    TSTAMP(4);
    recv_part(inbox + 3 * 1024, pre);
    const int g = lane >> 2, tq = lane & 3;
    uint2 sw[8];
    {
      const uint2* sp = (const uint2*)(g_s2 + ((size_t)G * 224 + 32 * rk + tq) * 32 + w * 8 + g) + wg;
      for (int it = 0; it < SPIN_MAX; it++) {
        uint32_t m = 0;
#pragma unroll
        for (int i = 0; i < 8; i++) { sw[i] = ld_relaxed2(sp + i * 4 * 64); m = umax3(m, sw[i].x, sw[i].y); }
        if (m != 0xffffffffu) break;
      }
    }
    TSTAMP(5);
    recv_part(inbox + 4 * 1024, pre);
    wg_wait<0>();
    fence_regs<32>(acc2[0]);
    TSTAMP(6);
#pragma unroll
    for (int i = 0; i < 8; i++) {
      const float2 bb = lds64f(ms + M_B2 + (8 * i + 2 * tq) * 4);
      pre[4 * i] += acc2[0][4 * i] + bb.x; pre[4 * i + 1] += acc2[0][4 * i + 1] + bb.y;
      pre[4 * i + 2] += acc2[0][4 * i + 2] + bb.x; pre[4 * i + 3] += acc2[0][4 * i + 3] + bb.y;
    }
    mbar_wait(bar0 + 8 * 14, 0);
    const int xrow = 64 * wg + 16 * w + (lane & 7) + 8 * ((lane >> 3) & 1);
    const uint32_t xa = sb + OFF_X + 2 * 16384 + xrow * 128;
    uint32_t xw[16];
#pragma unroll
    for (int q = 0; q < 4; q++) ldsm4(xa + (((2 * q + (lane >> 4)) ^ (lane & 7)) << 4), xw[4 * q], xw[4 * q + 1], xw[4 * q + 2], xw[4 * q + 3]);
    recv_part(inbox + 5 * 1024, pre);
    TSTAMP(7);
#pragma unroll
    for (int k = 0; k < 16; k++) {
      const uint32_t sv = (k & 1) ? sw[k >> 1].y : sw[k >> 1].x;
      const float o0 = pre[2 * k], o1 = pre[2 * k + 1];
      const float g0 = __fdividef(o0, 1.f + __expf(-o0)), g1 = __fdividef(o1, 1.f + __expf(-o1));
      xw[k] = pack_bf2(fmaf(bf_lo(sv), g0, bf_lo(xw[k])), fmaf(bf_hi(sv), g1, bf_hi(xw[k])));
    }
#pragma unroll
    for (int q = 0; q < 4; q++) stsm4(xa + (((2 * q + (lane >> 4)) ^ (lane & 7)) << 4), xw[4 * q], xw[4 * q + 1], xw[4 * q + 2], xw[4 * q + 3]);
    fence_async();
    __syncwarp();
    if (lane == 0) {
      tma_store_2d(&tm_out, sb + OFF_X + 2 * 16384 + (64 * wg + 16 * w) * 128, 64 * rk, 128 * G + 64 * wg + 16 * w);
      bulk_commit();
      bulk_wait0_read();
    }
    TSTAMP(8);
  }
}

typedef CUresult (*EncodeFn)(CUtensorMap*, CUtensorMapDataType, cuuint32_t, void*, const cuuint64_t*, const cuuint64_t*,
                             const cuuint32_t*, const cuuint32_t*, CUtensorMapInterleave, CUtensorMapSwizzle,
                             CUtensorMapL2promotion, CUtensorMapFloatOOBfill);

void make_map(EncodeFn fn, CUtensorMap* m, const void* ptr, int rank, const cuuint64_t* dims, const cuuint64_t* strides, const cuuint32_t* box) {
  const cuuint32_t es[3] = {1, 1, 1};
  fn(m, CU_TENSOR_MAP_DATA_TYPE_BFLOAT16, rank, const_cast<void*>(ptr), dims, strides, box, es, CU_TENSOR_MAP_INTERLEAVE_NONE,
     CU_TENSOR_MAP_SWIZZLE_128B, CU_TENSOR_MAP_L2_PROMOTION_L2_128B, CU_TENSOR_MAP_FLOAT_OOB_FILL_NONE);
}

}

extern "C" void kernel_launch(void* const* d_in, const int* in_sizes, int n_in, void* d_out, int out_size) {
  (void)in_sizes; (void)n_in; (void)out_size;
  void* fnp = nullptr;
  cudaDriverEntryPointQueryResult qr;
  cudaGetDriverEntryPoint("cuTensorMapEncodeTiled", &fnp, cudaEnableDefault, &qr);
  EncodeFn fn = (EncodeFn)fnp;
  Params p;
  p.x = (const __nv_bfloat16*)d_in[0];
  p.a_re = (const __nv_bfloat16*)d_in[1]; p.a_im = (const __nv_bfloat16*)d_in[2];
  p.b_re = (const __nv_bfloat16*)d_in[3]; p.b_im = (const __nv_bfloat16*)d_in[4];
  p.c_re = (const __nv_bfloat16*)d_in[5]; p.c_im = (const __nv_bfloat16*)d_in[6];
  p.log_dt = (const __nv_bfloat16*)d_in[7]; p.dskip = (const __nv_bfloat16*)d_in[8];
  p.w1 = (const __nv_bfloat16*)d_in[10]; p.b1 = (const __nv_bfloat16*)d_in[11];
  p.w2 = (const __nv_bfloat16*)d_in[12]; p.b2 = (const __nv_bfloat16*)d_in[13];
  CUtensorMap mx, mw1, mw2, mo;
  {
    const cuuint64_t dims[2] = {448, 2048}, str[1] = {896};
    const cuuint32_t box[2] = {64, 128}, boxo[2] = {64, 16};
    make_map(fn, &mx, p.x, 2, dims, str, box);
    make_map(fn, &mo, d_out, 2, dims, str, boxo);
  }
  {
    const cuuint64_t dims[3] = {64, 448, 28}, str[2] = {3584, 128};
    const cuuint32_t box[3] = {64, 64, 4};
    make_map(fn, &mw1, p.w1, 3, dims, str, box);
  }
  {
    const cuuint64_t dims[2] = {448, 1792}, str[1] = {896};
    const cuuint32_t box[2] = {64, 256};
    make_map(fn, &mw2, p.w2, 2, dims, str, box);
  }
  cudaFuncSetAttribute(fused_kernel, cudaFuncAttributeMaxDynamicSharedMemorySize, SMEM_BYTES);
  fused_kernel<<<NCTA, 384, SMEM_BYTES>>>(mx, mw1, mw2, mo, p);
}
```

```cpp
#include <cuda_runtime.h>
#include <cuda_bf16.h>
#include <cuda_fp16.h>
#include <cuda.h>
#include <stdint.h>

namespace {

constexpr int D_ = 448, NST = 256, F_ = 1792;
constexpr int NRK = 7, NMLP = 112, NCTA = 132;
constexpr int SPIN_MAX = 1 << 21;

__device__ uint4 g_xnT[128 * 448 * 2];
__device__ uint4 g_ax[2048];
__device__ float g_r[2048];
__device__ uint4 g_bx[F_];
__device__ uint4 g_part[16 * 7 * 6 * 1024];
__device__ uint4 g_s2[16 * 224 * 32];
__device__ unsigned g_cntA;
__device__ unsigned g_cntB[16 * 32];
__device__ unsigned g_epoch;
#define TSTAMP(i)

constexpr int TBL = 5248;
constexpr int TBL_C1 = 2624;
constexpr int SIG = 19584;
constexpr int SIG_U = 0, U_LBO = 656, SIG_V3 = 6272, SIG_V5 = 10368, SIG_V7 = 13440, SIG_V9 = 15488, SIG_V2 = 17536;
constexpr int Y2B = 6528, Y3B = 4352;
constexpr int KREC = 160, KSTG = 32 * KREC;
constexpr int OFF_W = 0, OFF_X = 98304, OFF_A = 147456, OFF_B = 190976, OFF_C = 205568, OFF_FF = 212096, OFF_M = 216192;
constexpr int M_AX = 0, M_BX = 2048, M_R = 6144, M_BAR = 6656, M_REL = 6784, M_SC = 6848, M_EP = 7040, M_CSR = 7168, M_END = 7424;
constexpr int SMEM_BYTES = OFF_M + M_END + 1024;
constexpr int S_WORK = 63488, S_WGB = 2 * SIG + Y2B + Y3B;

struct Params {
  const __nv_bfloat16 *x, *a_re, *a_im, *b_re, *b_im, *c_re, *c_im, *log_dt, *dskip, *w1, *b1, *w2, *b2;
};

__device__ __forceinline__ uint32_t smem_u32(const void* p) { return (uint32_t)__cvta_generic_to_shared(p); }
__device__ __forceinline__ void mbar_init(uint32_t bar, int cnt) { asm volatile("mbarrier.init.shared::cta.b64 [%0], %1;" ::"r"(bar), "r"(cnt)); }
__device__ __forceinline__ void mbar_expect(uint32_t bar, uint32_t bytes) {
  asm volatile("mbarrier.arrive.expect_tx.shared::cta.b64 _, [%0], %1;" ::"r"(bar), "r"(bytes) : "memory");
}
__device__ __forceinline__ void mbar_wait(uint32_t bar, uint32_t parity) {
  uint32_t done = 0;
#pragma unroll 1
  for (int it = 0; it < SPIN_MAX; it++) {
    asm volatile("{.reg .pred p; mbarrier.try_wait.parity.shared::cta.b64 p, [%1], %2; selp.u32 %0,1,0,p;}"
                 : "=r"(done) : "r"(bar), "r"(parity) : "memory");
    if (done) break;
  }
}
__device__ __forceinline__ void tma_2d(uint32_t dst, const CUtensorMap* m, int c0, int c1, uint32_t bar) {
  asm volatile("cp.async.bulk.tensor.2d.shared::cluster.global.mbarrier::complete_tx::bytes [%0], [%1, {%3, %4}], [%2];"
               ::"r"(dst), "l"(m), "r"(bar), "r"(c0), "r"(c1) : "memory");
}
__device__ __forceinline__ void tma_3d(uint32_t dst, const CUtensorMap* m, int c0, int c1, int c2, uint32_t bar) {
  asm volatile("cp.async.bulk.tensor.3d.shared::cluster.global.mbarrier::complete_tx::bytes [%0], [%1, {%3, %4, %5}], [%2];"
               ::"r"(dst), "l"(m), "r"(bar), "r"(c0), "r"(c1), "r"(c2) : "memory");
}
__device__ __forceinline__ void tma_store_2d(const CUtensorMap* m, uint32_t src, int c0, int c1) {
  asm volatile("cp.async.bulk.tensor.2d.global.shared::cta.bulk_group [%0, {%2, %3}], [%1];"
               ::"l"(m), "r"(src), "r"(c0), "r"(c1) : "memory");
}
__device__ __forceinline__ void bulk_s2g(void* dst, uint32_t src, uint32_t bytes) {
  asm volatile("cp.async.bulk.global.shared::cta.bulk_group [%0], [%1], %2;" ::"l"(dst), "r"(src), "r"(bytes) : "memory");
}
__device__ __forceinline__ void bulk_g2s(uint32_t dst, const void* src, uint32_t bytes, uint32_t bar) {
  asm volatile("cp.async.bulk.shared::cluster.global.mbarrier::complete_tx::bytes [%0], [%1], %2, [%3];"
               ::"r"(dst), "l"(src), "r"(bytes), "r"(bar) : "memory");
}
__device__ __forceinline__ void bulk_commit() { asm volatile("cp.async.bulk.commit_group;" ::: "memory"); }
__device__ __forceinline__ void bulk_wait0() { asm volatile("cp.async.bulk.wait_group 0;" ::: "memory"); }
__device__ __forceinline__ void bulk_wait0_read() { asm volatile("cp.async.bulk.wait_group.read 0;" ::: "memory"); }
__device__ __forceinline__ void fence_async() { asm volatile("fence.proxy.async.shared::cta;" ::: "memory"); }
__device__ __forceinline__ void bar_sync(int id, int n) { asm volatile("bar.sync %0, %1;" ::"r"(id), "r"(n) : "memory"); }
__device__ __forceinline__ void bar_arrive(int id, int n) { asm volatile("bar.arrive %0, %1;" ::"r"(id), "r"(n) : "memory"); }
__device__ __forceinline__ void wg_fence() { asm volatile("wgmma.fence.sync.aligned;" ::: "memory"); }
__device__ __forceinline__ void wg_commit() { asm volatile("wgmma.commit_group.sync.aligned;" ::: "memory"); }
template <int N> __device__ __forceinline__ void wg_wait() { asm volatile("wgmma.wait_group.sync.aligned %0;" ::"n"(N) : "memory"); }
template <int N> __device__ __forceinline__ void fence_regs(float* d) {
#pragma unroll
  for (int i = 0; i < N; i++) asm volatile("" : "+f"(d[i])::"memory");
}
__device__ __forceinline__ uint64_t mkdesc(uint32_t addr, uint32_t lbo, uint32_t sbo, uint32_t sw) {
  return (uint64_t)((addr & 0x3FFFF) >> 4) | ((uint64_t)(lbo >> 4) << 16) | ((uint64_t)(sbo >> 4) << 32) | ((uint64_t)sw << 62);
}
__device__ __forceinline__ uint32_t lds32(uint32_t a) { uint32_t v; asm volatile("ld.shared.b32 %0, [%1];" : "=r"(v) : "r"(a) : "memory"); return v; }
__device__ __forceinline__ float lds32f(uint32_t a) { float v; asm volatile("ld.shared.f32 %0, [%1];" : "=f"(v) : "r"(a) : "memory"); return v; }
__device__ __forceinline__ float2 lds64f(uint32_t a) { float2 v; asm volatile("ld.shared.v2.f32 {%0,%1}, [%2];" : "=f"(v.x), "=f"(v.y) : "r"(a) : "memory"); return v; }
__device__ __forceinline__ uint4 lds128(uint32_t a) {
  uint4 v; asm volatile("ld.shared.v4.b32 {%0,%1,%2,%3}, [%4];" : "=r"(v.x), "=r"(v.y), "=r"(v.z), "=r"(v.w) : "r"(a) : "memory"); return v;
}
__device__ __forceinline__ void sts16(uint32_t a, uint16_t v) { asm volatile("st.shared.b16 [%0], %1;" ::"r"(a), "h"(v) : "memory"); }
__device__ __forceinline__ void sts32f(uint32_t a, float v) { asm volatile("st.shared.f32 [%0], %1;" ::"r"(a), "f"(v) : "memory"); }
__device__ __forceinline__ void sts64f(uint32_t a, float x, float y) { asm volatile("st.shared.v2.f32 [%0], {%1,%2};" ::"r"(a), "f"(x), "f"(y) : "memory"); }
__device__ __forceinline__ void sts128(uint32_t a, uint32_t x, uint32_t y, uint32_t z, uint32_t w) {
  asm volatile("st.shared.v4.b32 [%0], {%1,%2,%3,%4};" ::"r"(a), "r"(x), "r"(y), "r"(z), "r"(w) : "memory");
}
__device__ __forceinline__ void ldsm4(uint32_t a, uint32_t& r0, uint32_t& r1, uint32_t& r2, uint32_t& r3) {
  asm volatile("ldmatrix.sync.aligned.m8n8.x4.shared.b16 {%0,%1,%2,%3}, [%4];" : "=r"(r0), "=r"(r1), "=r"(r2), "=r"(r3) : "r"(a) : "memory");
}
__device__ __forceinline__ void ldsm4t(uint32_t a, uint32_t& r0, uint32_t& r1, uint32_t& r2, uint32_t& r3) {
  asm volatile("ldmatrix.sync.aligned.m8n8.x4.trans.shared.b16 {%0,%1,%2,%3}, [%4];" : "=r"(r0), "=r"(r1), "=r"(r2), "=r"(r3) : "r"(a) : "memory");
}
__device__ __forceinline__ void stsm4(uint32_t a, uint32_t r0, uint32_t r1, uint32_t r2, uint32_t r3) {
  asm volatile("stmatrix.sync.aligned.m8n8.x4.shared.b16 [%0], {%1,%2,%3,%4};" ::"r"(a), "r"(r0), "r"(r1), "r"(r2), "r"(r3) : "memory");
}
__device__ __forceinline__ void mma_f16(float* c, uint32_t a0, uint32_t a1, uint32_t a2, uint32_t a3, uint32_t b0, uint32_t b1) {
  asm volatile("mma.sync.aligned.m16n8k16.row.col.f32.f16.f16.f32 {%0,%1,%2,%3},{%4,%5,%6,%7},{%8,%9},{%0,%1,%2,%3};"
               : "+f"(c[0]), "+f"(c[1]), "+f"(c[2]), "+f"(c[3]) : "r"(a0), "r"(a1), "r"(a2), "r"(a3), "r"(b0), "r"(b1));
}
__device__ __forceinline__ uint4 ld_relaxed4(const void* p) {
  uint4 v; asm volatile("ld.relaxed.gpu.global.v4.b32 {%0,%1,%2,%3}, [%4];" : "=r"(v.x), "=r"(v.y), "=r"(v.z), "=r"(v.w) : "l"(p) : "memory"); return v;
}
__device__ __forceinline__ uint2 ld_relaxed2(const void* p) {
  uint2 v; asm volatile("ld.relaxed.gpu.global.v2.b32 {%0,%1}, [%2];" : "=r"(v.x), "=r"(v.y) : "l"(p) : "memory"); return v;
}
__device__ __forceinline__ void st_relaxed4(void* p, uint32_t x, uint32_t y, uint32_t z, uint32_t w) {
  asm volatile("st.relaxed.gpu.global.v4.b32 [%0], {%1,%2,%3,%4};" ::"l"(p), "r"(x), "r"(y), "r"(z), "r"(w) : "memory");
}
__device__ __forceinline__ unsigned ld_acquire(const unsigned* p) {
  unsigned v; asm volatile("ld.acquire.gpu.global.u32 %0, [%1];" : "=r"(v) : "l"(p) : "memory"); return v;
}
__device__ __forceinline__ void red_release(unsigned* p) {
  asm volatile("red.release.gpu.global.add.u32 [%0], 1;" ::"l"(p) : "memory");
}
__device__ __forceinline__ void wait_count(const unsigned* p, unsigned target) {
#pragma unroll 1
  for (int it = 0; it < SPIN_MAX; it++) {
    if ((int)(ld_acquire(p) - target) >= 0) break;
  }
}
__device__ __forceinline__ uint32_t pack_h2(float lo, float hi) { uint32_t r; asm("cvt.rn.f16x2.f32 %0, %1, %2;" : "=r"(r) : "f"(hi), "f"(lo)); return r; }
__device__ __forceinline__ uint32_t pack_bf2(float lo, float hi) { uint32_t r; asm("cvt.rn.bf16x2.f32 %0, %1, %2;" : "=r"(r) : "f"(hi), "f"(lo)); return r; }
__device__ __forceinline__ float bf_lo(uint32_t w) { return __uint_as_float(w << 16); }
__device__ __forceinline__ float bf_hi(uint32_t w) { return __uint_as_float(w & 0xffff0000u); }
__device__ __forceinline__ float rbf(float v) { return __bfloat162float(__float2bfloat16_rn(v)); }
__device__ __forceinline__ float2 h2f(uint32_t w) { return __half22float2(*reinterpret_cast<__half2*>(&w)); }
__device__ __forceinline__ float ex2f(float v) { float r; asm("ex2.approx.ftz.f32 %0, %1;" : "=f"(r) : "f"(v)); return r; }
__device__ __forceinline__ float rcpf_(float v) { float r; asm("rcp.approx.f32 %0, %1;" : "=f"(r) : "f"(v)); return r; }
__device__ __forceinline__ float sqrtf_(float v) { float r; asm("sqrt.approx.f32 %0, %1;" : "=f"(r) : "f"(v)); return r; }
__device__ __forceinline__ float tanhf_(float v) { float r; asm("tanh.approx.f32 %0, %1;" : "=f"(r) : "f"(v)); return r; }
__device__ __forceinline__ uint32_t umax3(uint32_t a, uint32_t b, uint32_t c) { return max(max(a, b), c); }

__device__ __forceinline__ void wg_ss_bf16_n256(float* d, uint64_t da, uint64_t db, int sc) {
  asm volatile("{.reg .pred p; setp.ne.b32 p, %130, 0;\n"
    "wgmma.mma_async.sync.aligned.m64n256k16.f32.bf16.bf16 {%0, %1, %2, %3, %4, %5, %6, %7, %8, %9, %10, %11, %12, %13, %14, %15, %16, %17, %18, %19, %20, %21, %22, %23, %24, %25, %26, %27, %28, %29, %30, %31, %32, %33, %34, %35, %36, %37, %38, %39, %40, %41, %42, %43, %44, %45, %46, %47, %48, %49, %50, %51, %52, %53, %54, %55, %56, %57, %58, %59, %60, %61, %62, %63, %64, %65, %66, %67, %68, %69, %70, %71, %72, %73, %74, %75, %76, %77, %78, %79, %80, %81, %82, %83, %84, %85, %86, %87, %88, %89, %90, %91, %92, %93, %94, %95, %96, %97, %98, %99, %100, %101, %102, %103, %104, %105, %106, %107, %108, %109, %110, %111, %112, %113, %114, %115, %116, %117, %118, %119, %120, %121, %122, %123, %124, %125, %126, %127}, %128, %129, p, 1, 1, 0, 1;}\n"
    : "+f"(d[0]), "+f"(d[1]), "+f"(d[2]), "+f"(d[3]), "+f"(d[4]), "+f"(d[5]), "+f"(d[6]), "+f"(d[7]), "+f"(d[8]), "+f"(d[9]), "+f"(d[10]), "+f"(d[11]), "+f"(d[12]), "+f"(d[13]), "+f"(d[14]), "+f"(d[15]), "+f"(d[16]), "+f"(d[17]), "+f"(d[18]), "+f"(d[19]), "+f"(d[20]), "+f"(d[21]), "+f"(d[22]), "+f"(d[23]), "+f"(d[24]), "+f"(d[25]), "+f"(d[26]), "+f"(d[27]), "+f"(d[28]), "+f"(d[29]), "+f"(d[30]), "+f"(d[31]), "+f"(d[32]), "+f"(d[33]), "+f"(d[34]), "+f"(d[35]), "+f"(d[36]), "+f"(d[37]), "+f"(d[38]), "+f"(d[39]), "+f"(d[40]), "+f"(d[41]), "+f"(d[42]), "+f"(d[43]), "+f"(d[44]), "+f"(d[45]), "+f"(d[46]), "+f"(d[47]), "+f"(d[48]), "+f"(d[49]), "+f"(d[50]), "+f"(d[51]), "+f"(d[52]), "+f"(d[53]), "+f"(d[54]), "+f"(d[55]), "+f"(d[56]), "+f"(d[57]), "+f"(d[58]), "+f"(d[59]), "+f"(d[60]), "+f"(d[61]), "+f"(d[62]), "+f"(d[63]), "+f"(d[64]), "+f"(d[65]), "+f"(d[66]), "+f"(d[67]), "+f"(d[68]), "+f"(d[69]), "+f"(d[70]), "+f"(d[71]), "+f"(d[72]), "+f"(d[73]), "+f"(d[74]), "+f"(d[75]), "+f"(d[76]), "+f"(d[77]), "+f"(d[78]), "+f"(d[79]), "+f"(d[80]), "+f"(d[81]), "+f"(d[82]), "+f"(d[83]), "+f"(d[84]), "+f"(d[85]), "+f"(d[86]), "+f"(d[87]), "+f"(d[88]), "+f"(d[89]), "+f"(d[90]), "+f"(d[91]), "+f"(d[92]), "+f"(d[93]), "+f"(d[94]), "+f"(d[95]), "+f"(d[96]), "+f"(d[97]), "+f"(d[98]), "+f"(d[99]), "+f"(d[100]), "+f"(d[101]), "+f"(d[102]), "+f"(d[103]), "+f"(d[104]), "+f"(d[105]), "+f"(d[106]), "+f"(d[107]), "+f"(d[108]), "+f"(d[109]), "+f"(d[110]), "+f"(d[111]), "+f"(d[112]), "+f"(d[113]), "+f"(d[114]), "+f"(d[115]), "+f"(d[116]), "+f"(d[117]), "+f"(d[118]), "+f"(d[119]), "+f"(d[120]), "+f"(d[121]), "+f"(d[122]), "+f"(d[123]), "+f"(d[124]), "+f"(d[125]), "+f"(d[126]), "+f"(d[127])
    : "l"(da), "l"(db), "r"(sc));
}

__device__ __forceinline__ void wg_ss_bf16_n256k(float* d, uint64_t da, uint64_t db, int sc) {
  asm volatile("{.reg .pred p; setp.ne.b32 p, %130, 0;\n"
    "wgmma.mma_async.sync.aligned.m64n256k16.f32.bf16.bf16 {%0, %1, %2, %3, %4, %5, %6, %7, %8, %9, %10, %11, %12, %13, %14, %15, %16, %17, %18, %19, %20, %21, %22, %23, %24, %25, %26, %27, %28, %29, %30, %31, %32, %33, %34, %35, %36, %37, %38, %39, %40, %41, %42, %43, %44, %45, %46, %47, %48, %49, %50, %51, %52, %53, %54, %55, %56, %57, %58, %59, %60, %61, %62, %63, %64, %65, %66, %67, %68, %69, %70, %71, %72, %73, %74, %75, %76, %77, %78, %79, %80, %81, %82, %83, %84, %85, %86, %87, %88, %89, %90, %91, %92, %93, %94, %95, %96, %97, %98, %99, %100, %101, %102, %103, %104, %105, %106, %107, %108, %109, %110, %111, %112, %113, %114, %115, %116, %117, %118, %119, %120, %121, %122, %123, %124, %125, %126, %127}, %128, %129, p, 1, 1, 0, 0;}\n"
    : "+f"(d[0]), "+f"(d[1]), "+f"(d[2]), "+f"(d[3]), "+f"(d[4]), "+f"(d[5]), "+f"(d[6]), "+f"(d[7]), "+f"(d[8]), "+f"(d[9]), "+f"(d[10]), "+f"(d[11]), "+f"(d[12]), "+f"(d[13]), "+f"(d[14]), "+f"(d[15]), "+f"(d[16]), "+f"(d[17]), "+f"(d[18]), "+f"(d[19]), "+f"(d[20]), "+f"(d[21]), "+f"(d[22]), "+f"(d[23]), "+f"(d[24]), "+f"(d[25]), "+f"(d[26]), "+f"(d[27]), "+f"(d[28]), "+f"(d[29]), "+f"(d[30]), "+f"(d[31]), "+f"(d[32]), "+f"(d[33]), "+f"(d[34]), "+f"(d[35]), "+f"(d[36]), "+f"(d[37]), "+f"(d[38]), "+f"(d[39]), "+f"(d[40]), "+f"(d[41]), "+f"(d[42]), "+f"(d[43]), "+f"(d[44]), "+f"(d[45]), "+f"(d[46]), "+f"(d[47]), "+f"(d[48]), "+f"(d[49]), "+f"(d[50]), "+f"(d[51]), "+f"(d[52]), "+f"(d[53]), "+f"(d[54]), "+f"(d[55]), "+f"(d[56]), "+f"(d[57]), "+f"(d[58]), "+f"(d[59]), "+f"(d[60]), "+f"(d[61]), "+f"(d[62]), "+f"(d[63]), "+f"(d[64]), "+f"(d[65]), "+f"(d[66]), "+f"(d[67]), "+f"(d[68]), "+f"(d[69]), "+f"(d[70]), "+f"(d[71]), "+f"(d[72]), "+f"(d[73]), "+f"(d[74]), "+f"(d[75]), "+f"(d[76]), "+f"(d[77]), "+f"(d[78]), "+f"(d[79]), "+f"(d[80]), "+f"(d[81]), "+f"(d[82]), "+f"(d[83]), "+f"(d[84]), "+f"(d[85]), "+f"(d[86]), "+f"(d[87]), "+f"(d[88]), "+f"(d[89]), "+f"(d[90]), "+f"(d[91]), "+f"(d[92]), "+f"(d[93]), "+f"(d[94]), "+f"(d[95]), "+f"(d[96]), "+f"(d[97]), "+f"(d[98]), "+f"(d[99]), "+f"(d[100]), "+f"(d[101]), "+f"(d[102]), "+f"(d[103]), "+f"(d[104]), "+f"(d[105]), "+f"(d[106]), "+f"(d[107]), "+f"(d[108]), "+f"(d[109]), "+f"(d[110]), "+f"(d[111]), "+f"(d[112]), "+f"(d[113]), "+f"(d[114]), "+f"(d[115]), "+f"(d[116]), "+f"(d[117]), "+f"(d[118]), "+f"(d[119]), "+f"(d[120]), "+f"(d[121]), "+f"(d[122]), "+f"(d[123]), "+f"(d[124]), "+f"(d[125]), "+f"(d[126]), "+f"(d[127])
    : "l"(da), "l"(db), "r"(sc));
}

__device__ __forceinline__ void wg_rs_bf16_n64(float* d, uint32_t a0, uint32_t a1, uint32_t a2, uint32_t a3, uint64_t db, int sc) {
  asm volatile("{.reg .pred p; setp.ne.b32 p, %37, 0;\n"
    "wgmma.mma_async.sync.aligned.m64n64k16.f32.bf16.bf16 {%0, %1, %2, %3, %4, %5, %6, %7, %8, %9, %10, %11, %12, %13, %14, %15, %16, %17, %18, %19, %20, %21, %22, %23, %24, %25, %26, %27, %28, %29, %30, %31}, {%32,%33,%34,%35}, %36, p, 1, 1, 1;}\n"
    : "+f"(d[0]), "+f"(d[1]), "+f"(d[2]), "+f"(d[3]), "+f"(d[4]), "+f"(d[5]), "+f"(d[6]), "+f"(d[7]), "+f"(d[8]), "+f"(d[9]), "+f"(d[10]), "+f"(d[11]), "+f"(d[12]), "+f"(d[13]), "+f"(d[14]), "+f"(d[15]), "+f"(d[16]), "+f"(d[17]), "+f"(d[18]), "+f"(d[19]), "+f"(d[20]), "+f"(d[21]), "+f"(d[22]), "+f"(d[23]), "+f"(d[24]), "+f"(d[25]), "+f"(d[26]), "+f"(d[27]), "+f"(d[28]), "+f"(d[29]), "+f"(d[30]), "+f"(d[31])
    : "r"(a0), "r"(a1), "r"(a2), "r"(a3), "l"(db), "r"(sc));
}

__device__ __forceinline__ void wg_rs_f16_n32k(float* d, uint32_t a0, uint32_t a1, uint32_t a2, uint32_t a3, uint64_t db, int sc) {
  asm volatile("{.reg .pred p; setp.ne.b32 p, %21, 0;\n"
    "wgmma.mma_async.sync.aligned.m64n32k16.f32.f16.f16 {%0, %1, %2, %3, %4, %5, %6, %7, %8, %9, %10, %11, %12, %13, %14, %15}, {%16,%17,%18,%19}, %20, p, 1, 1, 0;}\n"
    : "+f"(d[0]), "+f"(d[1]), "+f"(d[2]), "+f"(d[3]), "+f"(d[4]), "+f"(d[5]), "+f"(d[6]), "+f"(d[7]), "+f"(d[8]), "+f"(d[9]), "+f"(d[10]), "+f"(d[11]), "+f"(d[12]), "+f"(d[13]), "+f"(d[14]), "+f"(d[15])
    : "r"(a0), "r"(a1), "r"(a2), "r"(a3), "l"(db), "r"(sc));
}

__device__ __forceinline__ void wg_rs_f16_n24t(float* d, uint32_t a0, uint32_t a1, uint32_t a2, uint32_t a3, uint64_t db, int sc) {
  asm volatile("{.reg .pred p; setp.ne.b32 p, %17, 0;\n"
    "wgmma.mma_async.sync.aligned.m64n24k16.f32.f16.f16 {%0, %1, %2, %3, %4, %5, %6, %7, %8, %9, %10, %11}, {%12,%13,%14,%15}, %16, p, 1, 1, 1;}\n"
    : "+f"(d[0]), "+f"(d[1]), "+f"(d[2]), "+f"(d[3]), "+f"(d[4]), "+f"(d[5]), "+f"(d[6]), "+f"(d[7]), "+f"(d[8]), "+f"(d[9]), "+f"(d[10]), "+f"(d[11])
    : "r"(a0), "r"(a1), "r"(a2), "r"(a3), "l"(db), "r"(sc));
}

__device__ __forceinline__ void wg_rs_f16_n16t(float* d, uint32_t a0, uint32_t a1, uint32_t a2, uint32_t a3, uint64_t db, int sc) {
  asm volatile("{.reg .pred p; setp.ne.b32 p, %13, 0;\n"
    "wgmma.mma_async.sync.aligned.m64n16k16.f32.f16.f16 {%0, %1, %2, %3, %4, %5, %6, %7}, {%8,%9,%10,%11}, %12, p, 1, 1, 1;}\n"
    : "+f"(d[0]), "+f"(d[1]), "+f"(d[2]), "+f"(d[3]), "+f"(d[4]), "+f"(d[5]), "+f"(d[6]), "+f"(d[7])
    : "r"(a0), "r"(a1), "r"(a2), "r"(a3), "l"(db), "r"(sc));
}

struct cf { float x, y; };
__device__ __forceinline__ cf cmul(cf a, cf b) { cf r; r.x = fmaf(a.x, b.x, -a.y * b.y); r.y = fmaf(a.x, b.y, a.y * b.x); return r; }
__device__ __forceinline__ cf zpow(float rho2, float phi, float e) {
  float m = ex2f(rho2 * e);
  float t = phi * e;
  float f = t - __fadd_rn(__fadd_rn(t, 12582912.f), -12582912.f);
  float ang = f * 6.283185307179586f;
  cf r; r.x = m * __cosf(ang); r.y = m * __sinf(ang); return r;
}
__device__ __forceinline__ uint32_t hprod(uint32_t v, uint32_t vr, uint32_t r) {
  __half2 hv = *reinterpret_cast<__half2*>(&v), hvr = *reinterpret_cast<__half2*>(&vr), hr = *reinterpret_cast<__half2*>(&r);
  __half2 o = __hfma2(__high2half2(hr), hvr, __hmul2(__low2half2(hr), hv));
  return *reinterpret_cast<uint32_t*>(&o);
}
__device__ __forceinline__ uint32_t rot90(uint32_t v) { return __byte_perm(v, 0, 0x1032) ^ 0x00008000u; }

__device__ __forceinline__ void kgen_warp(const Params& p, int d, int wd0, int nw, uint32_t stg, uint32_t sca, int lane) {
  const int off = d * (NST / 2) + lane * 4;
  const uint32_t* P[6] = {(const uint32_t*)p.a_re, (const uint32_t*)p.a_im, (const uint32_t*)p.b_re,
                          (const uint32_t*)p.b_im, (const uint32_t*)p.c_re, (const uint32_t*)p.c_im};
  uint32_t cur[6], nxt[6];
#pragma unroll
  for (int i = 0; i < 6; i++) nxt[i] = __ldg(P[i] + off + wd0);
  float dl, dp, inv_sc;
  {
    const uint4 br = __ldg((const uint4*)(P[2] + off)), bi = __ldg((const uint4*)(P[3] + off));
    const uint4 cr = __ldg((const uint4*)(P[4] + off)), ci = __ldg((const uint4*)(P[5] + off));
    const float ldt = __bfloat162float(p.log_dt[d]), dk = __bfloat162float(p.dskip[d]);
    const uint32_t M = 0x7fff7fffu;
    uint32_t mb = __vmaxu2(__vmaxu2(__vmaxu2(br.x & M, br.y & M), __vmaxu2(br.z & M, br.w & M)),
                           __vmaxu2(__vmaxu2(bi.x & M, bi.y & M), __vmaxu2(bi.z & M, bi.w & M)));
    uint32_t mc = __vmaxu2(__vmaxu2(__vmaxu2(cr.x & M, cr.y & M), __vmaxu2(cr.z & M, cr.w & M)),
                           __vmaxu2(__vmaxu2(ci.x & M, ci.y & M), __vmaxu2(ci.z & M, ci.w & M)));
    mb = __reduce_max_sync(0xffffffffu, max(mb << 16, mb & 0xffff0000u));
    mc = __reduce_max_sync(0xffffffffu, max(mc << 16, mc & 0xffff0000u));
    const float dt = rbf(__expf(ldt));
    const float dsk = dk * rcpf_(dt);
    float sc = fmaxf(2.f * __uint_as_float(mb) * __uint_as_float(mc), fabsf(dsk) * (1.f / 256.f)) * (1.f / 16.f);
    sc = __uint_as_float(__float_as_uint(fminf(fmaxf(sc, 1e-30f), 1e30f)) & 0x7f800000u);
    inv_sc = rcpf_(sc);
    if (lane == 0) sts64f(sca + 8, dt * sc, dsk * inv_sc);
    dl = dt * 1.4426950408889634f; dp = dt * 0.15915494309189535f;
  }
  const int tq = lane & 3;
  const uint32_t st0 = stg + lane * KREC + (((lane >> 2) & 1) << 4), st1 = st0 ^ 16;
  const int mat = lane >> 3, rowi = lane & 7;
  const uint32_t ld_base = stg + (4 * (mat & 1) + (rowi >> 1)) * KREC + ((((mat >> 1) * 2 + (rowi & 1)) << 4) ^ ((mat & 1) << 4));
  const uint32_t cb_lo = stg + tq * KREC + 128;
  float acc[24];
#pragma unroll
  for (int i = 0; i < 24; i++) acc[i] = 0.f;
#pragma unroll 1
  for (int it = 0; it < 2 * nw; it++) {
    if ((it & 1) == 0) {
#pragma unroll
      for (int i = 0; i < 6; i++) cur[i] = nxt[i];
      if (it + 2 < 2 * nw) {
#pragma unroll
        for (int i = 0; i < 6; i++) nxt[i] = __ldg(P[i] + off + wd0 + (it >> 1) + 1);
      }
    } else {
#pragma unroll
      for (int i = 0; i < 6; i++) cur[i] >>= 16;
    }
    const float rho2 = bf_lo(cur[0]) * dl, phi = bf_lo(cur[1]) * dp;
    cf bb = {bf_lo(cur[2]) * inv_sc, bf_lo(cur[3]) * inv_sc}, cc = {bf_lo(cur[4]), bf_lo(cur[5])};
    cf X[8];
    X[0] = cmul(cc, bb);
    const cf z1 = zpow(rho2, phi, 1.f), z8 = zpow(rho2, phi, 8.f), z64 = zpow(rho2, phi, 64.f);
    const cf y1 = zpow(rho2, phi, 256.f), y4 = zpow(rho2, phi, 1024.f);
    const cf z2 = cmul(z1, z1);
    X[1] = cmul(X[0], z1);
#pragma unroll
    for (int j = 2; j < 8; j++) X[j] = cmul(X[j - 2], z2);
    __syncwarp();
    sts128(st0, pack_h2(X[0].x, X[1].x), pack_h2(X[2].x, X[3].x), pack_h2(X[4].x, X[5].x), pack_h2(X[6].x, X[7].x));
    sts128(st1, pack_h2(-X[0].y, -X[1].y), pack_h2(-X[2].y, -X[3].y), pack_h2(-X[4].y, -X[5].y), pack_h2(-X[6].y, -X[7].y));
    {
      const cf a0 = cmul(X[0], y1), a1 = cmul(X[2], y1), a2 = cmul(X[4], y1), a3 = cmul(X[6], y1);
      const cf a4 = cmul(a0, y1), a5 = cmul(a2, y1);
      const cf a6 = cmul(a4, y1), a7 = cmul(a5, y1);
      sts128(st0 + 32, pack_h2(a0.x, a1.x), pack_h2(a2.x, a3.x), pack_h2(a4.x, a5.x), pack_h2(a6.x, a7.x));
      sts128(st1 + 32, pack_h2(-a0.y, -a1.y), pack_h2(-a2.y, -a3.y), pack_h2(-a4.y, -a5.y), pack_h2(-a6.y, -a7.y));
      const cf v0 = cmul(X[0], y4), v1 = cmul(a0, y4), v2 = cmul(a4, y4), v3 = cmul(a6, y4), v4 = cmul(v0, y4);
      sts128(st0 + 64, pack_h2(v0.x, v1.x), pack_h2(v2.x, v3.x), pack_h2(v4.x, 0.f), 0u);
      sts128(st1 + 64, pack_h2(-v0.y, -v1.y), pack_h2(-v2.y, -v3.y), pack_h2(-v4.y, 0.f), 0u);
    }
    {
      const cf f2 = cmul(z8, z8), f3 = cmul(f2, z8), f4 = cmul(f2, f2), f5 = cmul(f3, f2), f6 = cmul(f4, f2), f7 = cmul(f4, f3);
      sts128(st0 + 96, pack_h2(1.f, z8.x), pack_h2(f2.x, f3.x), pack_h2(f4.x, f5.x), pack_h2(f6.x, f7.x));
      sts128(st1 + 96, pack_h2(0.f, z8.y), pack_h2(f2.y, f3.y), pack_h2(f4.y, f5.y), pack_h2(f6.y, f7.y));
      const cf z128 = cmul(z64, z64), z192 = cmul(z128, z64);
      sts128(st0 + 128, pack_h2(z64.x, z64.y), pack_h2(z128.x, z128.y), pack_h2(z192.x, z192.y), 0u);
    }
    __syncwarp();
#pragma unroll 2
    for (int ks = 0; ks < 4; ks++) {
      uint32_t b00, b01, b10, b11, b20, b21, al, ah;
      ldsm4t(ld_base + ks * 8 * KREC, b00, b01, b10, b11);
      ldsm4t(ld_base + ks * 8 * KREC + 64, b20, b21, al, ah);
      const uint4 rl = lds128(cb_lo + ks * 8 * KREC), rh = lds128(cb_lo + ks * 8 * KREC + 4 * KREC + 16);
      const uint32_t alr = rot90(al), ahr = rot90(ah);
      const uint32_t a1 = hprod(al, alr, rl.x), a3 = hprod(ah, ahr, rh.x);
      const uint32_t c0 = hprod(al, alr, rl.y), c2 = hprod(ah, ahr, rh.y);
      const uint32_t c1 = hprod(al, alr, rl.z), c3 = hprod(ah, ahr, rh.z);
      mma_f16(acc + 0, al, a1, ah, a3, b00, b01);
      mma_f16(acc + 4, al, a1, ah, a3, b10, b11);
      mma_f16(acc + 8, al, a1, ah, a3, b20, b21);
      mma_f16(acc + 12, c0, c1, c2, c3, b00, b01);
      mma_f16(acc + 16, c0, c1, c2, c3, b10, b11);
      mma_f16(acc + 20, c0, c1, c2, c3, b20, b21);
    }
  }
  __syncwarp();
#pragma unroll
  for (int q = 0; q < 4; q++) {
    const float* a = acc + 12 * (q >> 1) + 2 * (q & 1);
    sts128(stg + q * 768 + lane * 16, __float_as_uint(a[0]), __float_as_uint(a[1]), __float_as_uint(a[4]), __float_as_uint(a[5]));
    sts64f(stg + q * 768 + 512 + lane * 8, a[8], a[9]);
  }
}

__device__ __forceinline__ void tput(uint32_t tbl, int X, uint32_t h) {
  sts16(tbl + 2 * (1296 - X), (uint16_t)h);
  sts16(tbl + TBL_C1 + 2 * (1297 - X), (uint16_t)h);
}
__device__ __forceinline__ void ktab_build(uint32_t src, int nparts, int q, uint32_t tbl, uint32_t sca, int lane) {
  const int tq = lane & 3, r = 8 * q + (lane >> 2);
  float v[6] = {0.f, 0.f, 0.f, 0.f, 0.f, 0.f};
#pragma unroll 1
  for (int j = 0; j < nparts; j++) {
    const uint4 a = lds128(src + j * KSTG + q * 768 + lane * 16);
    const float2 c = lds64f(src + j * KSTG + q * 768 + 512 + lane * 8);
    v[0] += __uint_as_float(a.x); v[1] += __uint_as_float(a.y); v[2] += __uint_as_float(a.z); v[3] += __uint_as_float(a.w);
    v[4] += c.x; v[5] += c.y;
  }
  const bool first = (r == 0);
  if (first && tq == 0) { v[0] += lds32f(sca + 12); sts32f(sca, v[4]); }
  const uint32_t h0 = pack_h2(v[0], v[1]), h1 = pack_h2(v[2], v[3]), h2 = pack_h2(v[4], v[5]);
  tput(tbl, 64 + 8 * r + 2 * tq, h0);
  tput(tbl, 65 + 8 * r + 2 * tq, h0 >> 16);
  const bool lo = tq < 2;
  const int Xd = 320 + 8 * r + 4 * tq, k2 = 32 * (tq - 2) + r;
  tput(tbl, lo ? Xd + 2 : 720 + k2, h1 >> 16);
  const bool sp = first && tq == 2;
  const int Xa = lo ? Xd : (sp ? 576 : 911 + k2);
  tput(tbl, Xa, h1);
  if (lo || sp) {
    tput(tbl, Xa + 1, h1);
    if (Xa != 320) tput(tbl, Xa - 1, h1);
  }
  if (sp) { tput(tbl, 578, h1); tput(tbl, 1295, h2); }
  if (lo) {
    const int X3 = ((r & 1) ? 1104 : 1231) + 32 * tq + (r >> 1);
    tput(tbl, X3 == 1231 ? 975 : X3, h2);
    tput(tbl, X3 + 16, h2 >> 16);
  }
}

__device__ __forceinline__ void sig_windows(uint32_t sig, int t) {
  float S[41];
  S[0] = 0.f;
#pragma unroll
  for (int c = 0; c < 5; c++) {
    const int kap = 2 * t - 3 + c + 72;
    const uint4 v = lds128(sig + SIG_U + (kap & 7) * U_LBO + (kap >> 3) * 16);
    const uint32_t w[4] = {v.x, v.y, v.z, v.w};
#pragma unroll
    for (int k = 0; k < 4; k++) {
      const float2 f = h2f(w[k]);
      S[8 * c + 2 * k + 1] = S[8 * c + 2 * k] + f.x;
      S[8 * c + 2 * k + 2] = S[8 * c + 2 * k + 1] + f.y;
    }
  }
#define WIN2(j, lo, hi) pack_h2(S[25 + (j) - (lo)] - S[24 + (j) - (hi)], S[26 + (j) - (lo)] - S[25 + (j) - (hi)])
#define WIN8(a, j, lo, hi) sts128(a, WIN2(j, lo, hi), WIN2(j + 2, lo, hi), WIN2(j + 4, lo, hi), WIN2(j + 6, lo, hi))
  WIN8(sig + SIG_V3 + t * 32, 0, 3, 5);
  WIN8(sig + SIG_V3 + t * 32 + 16, 8, 3, 5);
  WIN8(sig + SIG_V5 + t * 32, 0, 6, 10);
  WIN8(sig + SIG_V5 + t * 32 + 16, 8, 6, 10);
  if (t < 64) {
    WIN8(sig + SIG_V7 + t * 16, 0, 5, 11);
    WIN8(sig + SIG_V7 + 1024 + t * 16, 8, 5, 11);
    WIN8(sig + SIG_V9 + t * 16, 0, 12, 20);
    WIN8(sig + SIG_V9 + 1024 + t * 16, 8, 12, 20);
    WIN8(sig + SIG_V2 + t * 16, 0, 3, 4);
    WIN8(sig + SIG_V2 + 1024 + t * 16, 8, 3, 4);
  }
#undef WIN8
#undef WIN2
}

__device__ __forceinline__ void conv_channel(uint32_t tbl, uint32_t sig, uint32_t y2b, uint32_t y3b, float k1024,
                                             int w, int lane, int barid, float* res) {
  const int g = lane >> 2, tq = lane & 3;
  const uint32_t tb = tbl + ((g & 1) ? TBL_C1 + 2 : 0) + 2 * (1296 - (g - 2 * tq)) - 32 * w + 112;
  float a2[12], a3[8];
#pragma unroll
  for (int i = 0; i < 16; i++) res[i] = 0.f;
#pragma unroll
  for (int i = 0; i < 12; i++) a2[i] = 0.f;
#pragma unroll
  for (int q = 0; q < 4; q++) {
    const float2 f = h2f(lds32(sig + SIG_V2 + (q >> 1) * 1024 + (16 * w + 8 * (q & 1) + g) * 16 + tq * 4));
    a3[2 * q] = k1024 * f.x;
    a3[2 * q + 1] = k1024 * f.y;
  }
  const uint64_t dU = mkdesc(sig + SIG_U + 9 * 16, U_LBO, 128, 0);
  const uint64_t dV = mkdesc(sig + SIG_V3 + 768, 128, 1024, 0);
  fence_regs<16>(res); fence_regs<12>(a2); fence_regs<8>(a3);
  constexpr int LB = 2 * U_LBO / 16;
#pragma unroll 1
  for (int it = 0; it < 8; it++) {
    const uint32_t td = tb - 128 - 128 * it;
    const uint32_t t2 = tb - 1440 - 384 * (it >> 2) - 64 * (it & 3);
    const uint32_t t3 = tb - 2208 - 256 * (it >> 2) - 32 * (it & 3);
    const uint64_t dd = dU - it;
    const uint64_t d2 = dV + (uint64_t)(256 * (it >> 2) - 32 * (it & 1) - 64 * ((it >> 1) & 1) + 128) - 128;
    const uint64_t d3 = dV + (uint64_t)((SIG_V7 - SIG_V3) / 16 + 128 * (it >> 2) - 16 * (it & 3));
    uint32_t Rd[9], R2[5], R3[3];
#pragma unroll
    for (int i = 0; i < 5; i++) Rd[i] = lds32(td - 16 * i);
#pragma unroll
    for (int i = 0; i < 3; i++) { R2[i] = lds32(t2 - 16 * i); R3[i] = lds32(t3 - 16 * i); }
    wg_fence();
    wg_rs_f16_n32k(res, Rd[1], Rd[2], Rd[0], Rd[1], dd + 3 * LB, 1);
    wg_rs_f16_n24t(a2, R2[1], R2[2], R2[0], R2[1], d2, 1);
    wg_rs_f16_n32k(res, Rd[3], Rd[4], Rd[2], Rd[3], dd + 2 * LB, 1);
    wg_rs_f16_n16t(a3, R3[1], R3[2], R3[0], R3[1], d3, 1);
    wg_commit();
    wg_wait<1>();
#pragma unroll
    for (int i = 5; i < 9; i++) Rd[i] = lds32(td - 16 * i);
#pragma unroll
    for (int i = 3; i < 5; i++) R2[i] = lds32(t2 - 16 * i);
    wg_fence();
    wg_rs_f16_n32k(res, Rd[5], Rd[6], Rd[4], Rd[5], dd + LB, 1);
    wg_rs_f16_n24t(a2, R2[3], R2[4], R2[2], R2[3], d2 - 16, 1);
    wg_rs_f16_n32k(res, Rd[7], Rd[8], Rd[6], Rd[7], dd, 1);
    wg_commit();
    wg_wait<1>();
  }
  {
    uint32_t Rd[11];
#pragma unroll
    for (int i = 0; i < 11; i++) Rd[i] = lds32(tb - 128 - 1024 - 16 * i);
    wg_fence();
#pragma unroll
    for (int i = 0; i < 4; i++) wg_rs_f16_n32k(res, Rd[2 * i + 1], Rd[2 * i + 2], Rd[2 * i], Rd[2 * i + 1], dU + (3 - i) * LB - 8, 1);
    wg_rs_f16_n32k(res, Rd[9], Rd[10], Rd[8], Rd[9], dU + 3 * LB - 9, 1);
    wg_commit();
  }
  wg_wait<0>();
  fence_regs<16>(res); fence_regs<12>(a2); fence_regs<8>(a3);
  bar_sync(barid, 128);
  {
    const uint32_t o2 = y2b + (136 * w + 8 * g + 2 * tq) * 4, o3 = y3b + (272 * w + 16 * g + 2 * tq) * 4;
#pragma unroll
    for (int q = 0; q < 6; q++) sts64f(o2 + (544 * (q >> 1) + 64 * (q & 1)) * 4, a2[2 * q], a2[2 * q + 1]);
#pragma unroll
    for (int q = 0; q < 4; q++) sts64f(o3 + (8 * (q >> 1) + 136 * (q & 1)) * 4, a3[2 * q], a3[2 * q + 1]);
  }
  bar_sync(barid, 128);
  const uint32_t go = (136 * tq + 16 * w + g) * 4;
#pragma unroll
  for (int nt = 1; nt < 4; nt++)
#pragma unroll
    for (int c = 0; c < 4; c++) {
      const int o = 64 * (c & 1) + 8 * (c >> 1);
      res[4 * nt + c] += lds32f(y2b + go + (544 * (nt - 1) + o) * 4);
      if (nt >= 2) res[4 * nt + c] += lds32f(y3b + go + (544 * (nt - 2) + o) * 4);
    }
}

__device__ __forceinline__ float red16(float v) {
#pragma unroll
  for (int o = 1; o < 16; o <<= 1) v += __shfl_xor_sync(0xffffffffu, v, o);
  return v;
}
__device__ __forceinline__ void ln_rows(const __nv_bfloat16* x, int row, uint32_t stg_row, int lane) {
  const int j = lane & 15;
  const uint2* xr = (const uint2*)(x + (size_t)row * D_) + j;
  uint32_t u[14];
#pragma unroll
  for (int i = 0; i < 7; i++) { const uint2 v = __ldg(xr + 16 * i); u[2 * i] = v.x; u[2 * i + 1] = v.y; }
  const float piv = __shfl_sync(0xffffffffu, bf_lo(u[0]), lane & 16);
  float s = 0.f, q = 0.f;
#pragma unroll
  for (int i = 0; i < 14; i++) {
    const float a = bf_lo(u[i]) - piv, c = bf_hi(u[i]) - piv;
    s += a + c; q = fmaf(a, a, q); q = fmaf(c, c, q);
  }
  s = red16(s) * (1.f / D_); q = red16(q) * (1.f / D_);
  const __nv_bfloat16 m1b = __float2bfloat16_rn(s + piv);
  const __nv_bfloat162 m1v = __halves2bfloat162(m1b, m1b);
  const float den = rbf(sqrtf_(rbf(rbf(fmaxf(fmaf(-s, s, q), 0.f)) + 1e-5f)));
  const float rden = rcpf_(den);
  s = 0.f; q = 0.f;
#pragma unroll
  for (int i = 0; i < 14; i++) {
    const __nv_bfloat162 cv = __hsub2(*reinterpret_cast<__nv_bfloat162*>(&u[i]), m1v);
    const uint32_t c = *reinterpret_cast<const uint32_t*>(&cv);
    const uint32_t n = pack_bf2(bf_lo(c) * rden, bf_hi(c) * rden);
    const float a = bf_lo(n), e = bf_hi(n);
    s += a + e; q = fmaf(a, a, q); q = fmaf(e, e, q);
    u[i] = pack_h2(a, e);
  }
#pragma unroll
  for (int i = 0; i < 7; i++)
    asm volatile("st.shared.v2.b32 [%0], {%1,%2};" ::"r"(stg_row + (j + 16 * i) * 8), "r"(u[2 * i]), "r"(u[2 * i + 1]) : "memory");
  s = red16(s) * (1.f / D_); q = red16(q) * (1.f / D_);
  const float den2 = rbf(sqrtf_(rbf(rbf(fmaxf(fmaf(-s, s, q), 0.f)) + 1e-5f)));
  if (j == 0) {
    const float ir = den * den2, mu = fmaf(rbf(s), den, __bfloat162float(m1b));
    const float ih = rbf(ir), mh = rbf(mu), ml = rbf(mu - mh);
    g_ax[row] = make_uint4(pack_bf2(ih, ir - ih), pack_bf2(mh, mh), pack_bf2(ml, ml), pack_bf2(mh, mu - mh - ml));
    g_r[row] = rcpf_(ir);
  }
}

__device__ __forceinline__ void recv_part(const uint4* src, float* pre) {
  uint4 v[4];
#pragma unroll 1
  for (int it = 0; it < SPIN_MAX; it++) {
#pragma unroll
    for (int q = 0; q < 4; q++) v[q] = ld_relaxed4(src + q * 256);
    uint32_t m = 0;
#pragma unroll
    for (int q = 0; q < 4; q++) m = umax3(umax3(m, v[q].x, v[q].y), v[q].z, v[q].w);
    if (m != 0xffffffffu) break;
  }
#pragma unroll
  for (int q = 0; q < 4; q++) {
    const uint32_t u[4] = {v[q].x, v[q].y, v[q].z, v[q].w};
#pragma unroll
    for (int k = 0; k < 4; k++) { pre[8 * q + 2 * k] += bf_lo(u[k]); pre[8 * q + 2 * k + 1] += bf_hi(u[k]); }
  }
}
__device__ __forceinline__ void send_part(uint4* dst, const float* a) {
#pragma unroll
  for (int q = 0; q < 4; q++)
    st_relaxed4(dst + q * 256, pack_bf2(a[8 * q], a[8 * q + 1]), pack_bf2(a[8 * q + 2], a[8 * q + 3]),
                pack_bf2(a[8 * q + 4], a[8 * q + 5]), pack_bf2(a[8 * q + 6], a[8 * q + 7]));
}
__device__ __forceinline__ bool last_release(uint32_t cnt) {
  unsigned old;
  asm volatile("atom.acq_rel.cta.shared.add.u32 %0, [%1], 1;" : "=r"(old) : "r"(cnt) : "memory");
  return old == 7;
}
__device__ __forceinline__ int mod7(int v) { return v >= 7 ? v - 7 : v; }

__global__ void __launch_bounds__(384, 1)
fused_kernel(const __grid_constant__ CUtensorMap tm_x, const __grid_constant__ CUtensorMap tm_w1,
             const __grid_constant__ CUtensorMap tm_w2, const __grid_constant__ CUtensorMap tm_out, const Params p) {
  extern __shared__ uint8_t smem_raw[];
  const uint32_t sb = (smem_u32(smem_raw) + 1023) & ~1023u;
  const int tid = threadIdx.x, lane = tid & 31, t = tid & 127;
  const int warp = __shfl_sync(0xffffffffu, tid >> 5, 0), wg = warp >> 2, w = warp & 3;
  const int b = blockIdx.x;
  const uint32_t ms = sb + OFF_M;
  const bool is_ssm = b >= NMLP;
  const int sidx = b - NMLP;
  const int npair = sidx < 12 ? 6 : 5;
  const int pair0 = is_ssm ? 112 + (sidx < 12 ? 6 * sidx : 12 + 5 * sidx) + wg : b;
  const uint32_t work = is_ssm ? sb + S_WORK + wg * S_WGB : sb + OFF_A;
  const int G = b / NRK, rk = b - G * NRK;
  const uint32_t bar0 = ms + M_BAR;
  const int kc0 = (G + rk) % 7;

  if (is_ssm ? (wg + 3 * (w >> 1) < npair) : (wg < 2)) {
    const int d = is_ssm ? 2 * (pair0 + 3 * (w >> 1)) + (w & 1) : 2 * b + wg;
    kgen_warp(p, d, is_ssm ? 0 : w, is_ssm ? 4 : 1, work + (is_ssm ? w : warp) * KSTG, ms + M_SC + (is_ssm ? warp : wg) * 16, lane);
  }
  TSTAMP(1);

  if (is_ssm || wg == 2) {
    asm volatile("setmaxnreg.dec.sync.aligned.u32 96;");
    const int barid = 4 + wg;
    unsigned epoch = 0;
    if (t == 0) epoch = *(volatile unsigned*)&g_epoch;
    if (!is_ssm) {
      if (t == 0) {
#pragma unroll 1
        for (int i = 0; i < 16; i++) { mbar_init(bar0 + 8 * i, 1); asm volatile("st.shared.b32 [%0], 0;" ::"r"(ms + M_REL + 4 * i) : "memory"); }
        asm volatile("fence.mbarrier_init.release.cluster;" ::: "memory");
        fence_async();
#pragma unroll 1
        for (int s = 0; s < 3; s++) {
          const int kc = mod7(kc0 + s);
          mbar_expect(bar0 + 8 * s, 49152);
          tma_2d(sb + OFF_X + s * 16384, &tm_x, 64 * kc, 128 * G, bar0 + 8 * s);
          tma_3d(sb + OFF_W + s * 32768, &tm_w1, 0, 64 * kc, 4 * rk, bar0 + 8 * s);
        }
        asm volatile("st.shared.b32 [%0], %1;" ::"r"(ms + M_EP), "r"(epoch) : "memory");
      }
      sts128(sb + OFF_FF + t * 16, ~0u, ~0u, ~0u, ~0u);
      sts128(sb + OFF_FF + 2048 + t * 16, ~0u, ~0u, ~0u, ~0u);
      fence_async();
      bar_arrive(7, 384);
      bar_sync(6, 128);
      if (t < 4) {
        bulk_s2g((uint8_t*)(g_s2 + ((size_t)G * 224 + 32 * rk) * 32) + t * 4096, sb + OFF_FF, 4096);
        bulk_commit();
        if (t == 0)
          asm volatile("cp.async.bulk.prefetch.L2.global [%0], %1;" ::"l"(p.w2 + (size_t)(256 * rk + 16 * G) * D_), "r"(16 * D_ * 2) : "memory");
      }
      {
        const uint4* wr = (const uint4*)(p.w1 + (size_t)(t >> 1) * F_ + 16 * b) + (t & 1);
        float cs[8];
#pragma unroll
        for (int k = 0; k < 8; k++) cs[k] = 0.f;
        uint4 wv[7];
#pragma unroll
        for (int i = 0; i < 7; i++) wv[i] = __ldg(wr + (size_t)i * 64 * (F_ / 8));
#pragma unroll
        for (int i = 0; i < 7; i++) {
          const uint32_t u[4] = {wv[i].x, wv[i].y, wv[i].z, wv[i].w};
#pragma unroll
          for (int k = 0; k < 4; k++) { cs[2 * k] += bf_lo(u[k]); cs[2 * k + 1] += bf_hi(u[k]); }
        }
#pragma unroll
        for (int st = 0; st < 3; st++) {
          const int n = 4 >> st;
          const bool up = (lane >> (3 - st)) & 1;
#pragma unroll
          for (int k = 0; k < n; k++) {
            const float give = up ? cs[k] : cs[k + n], keep = up ? cs[k + n] : cs[k];
            cs[k] = keep + __shfl_xor_sync(0xffffffffu, give, 8 >> st);
          }
        }
        cs[0] += __shfl_xor_sync(0xffffffffu, cs[0], 16);
        if (lane < 16) sts32f(ms + M_CSR + (w * 16 + (lane & 1) * 8 + (lane >> 1)) * 4, cs[0]);
      }
      bar_sync(1, 384);
      TSTAMP(2);
      if (t < 16) {
        const uint32_t a = ms + M_CSR + t * 4;
        const float c = -0.5f * ((lds32f(a) + lds32f(a + 64)) + (lds32f(a + 128) + lds32f(a + 192)));
        const float bb = 0.5f * __bfloat162float(p.b1[16 * b + t]);
        const float ch = rbf(c), cl = rbf(c - ch);
        const uint32_t hl = pack_bf2(ch, cl);
        g_bx[16 * b + t] = make_uint4(pack_bf2(bb, bb), hl, hl, pack_bf2(c - ch - cl, ch));
      }
#pragma unroll 1
      for (int rb = b; rb < 128; rb += NMLP) {
#pragma unroll 1
        for (int i = 0; i < 2; i++) {
          const int rl = 4 * w + 2 * i + (lane >> 4);
          ln_rows(p.x, 16 * rb + rl, sb + OFF_B + rl * 912, lane);
        }
        bar_sync(6, 128);
        const uint32_t la = sb + OFF_B + ((lane & 7) + 8 * ((lane >> 3) & 1)) * 912 + (lane >> 4) * 16 + w * 224;
        uint2* dst = (uint2*)(g_xnT + (size_t)rb * 896) + lane + w * 448;
#pragma unroll 1
        for (int i = 0; i < 7; i++) {
          uint32_t r0, r1, r2, r3;
          ldsm4t(la + i * 32, r0, r1, r2, r3);
          dst[i * 64] = make_uint2(r0, r1);
          dst[i * 64 + 32] = make_uint2(r2, r3);
        }
        if (t < 4) bulk_wait0();
        bar_sync(6, 128);
      }
    } else {
      __syncthreads();
    }
    if (tid == (is_ssm ? 0 : 256)) { __threadfence(); red_release(&g_cntA); }
    if (!is_ssm && t < 24) {
      bulk_s2g((uint8_t*)(g_part + (size_t)(G * 7 + rk) * 6 * 1024) + t * 4096, sb + OFF_FF, 4096);
      bulk_commit();
    }
    TSTAMP(3);
    const uint32_t tbl0 = is_ssm ? sb + 4 * wg * TBL : sb + OFF_B;
    const uint32_t sca0 = ms + M_SC + (is_ssm ? 64 * wg : 0);
#pragma unroll 1
    for (int i = t; i < (is_ssm ? 4 : 2) * TBL / 16; i += 128) sts128(tbl0 + i * 16, 0u, 0u, 0u, 0u);
    bar_sync(barid, 128);
    {
      const int c = is_ssm ? w : w >> 1;
      const int q0 = is_ssm ? 0 : 2 * (w & 1), q1 = is_ssm ? 4 : q0 + 2;
#pragma unroll 1
      for (int q = q0; q < q1; q++) ktab_build(work + (is_ssm ? 1 : 4) * c * KSTG, is_ssm ? 1 : 4, q, tbl0 + c * TBL, sca0 + c * 16, lane);
    }
    TSTAMP(4);
    if (t == 0) {
      wait_count(&g_cntA, (epoch + 1) * NCTA);
      if (!is_ssm) {
        if (b == 0) *(volatile unsigned*)&g_epoch = epoch + 1;
        asm volatile("fence.proxy.async;" ::: "memory");
        mbar_expect(bar0 + 8 * 15, 2048 + 4096 + 512);
        bulk_g2s(ms + M_AX, g_ax + 128 * G, 2048, bar0 + 8 * 15);
        bulk_g2s(ms + M_BX, g_bx + 256 * rk, 4096, bar0 + 8 * 15);
        bulk_g2s(ms + M_R, g_r + 128 * G, 512, bar0 + 8 * 15);
      }
    }
    bar_sync(barid, 128);
    TSTAMP(5);
    const uint32_t y3b = work + 2 * SIG, y2b = is_ssm ? y3b + Y3B : sb + OFF_C;
    const int np = is_ssm ? (wg + 3 < npair ? 2 : 1) : 1;
#pragma unroll 1
    for (int pi = 0; pi < np; pi++) {
      const int pair = pair0 + 3 * pi;
      {
        const uint4* src = g_xnT + ((size_t)t * 448 + 2 * pair) * 2;
        const uint4 l0 = ld_relaxed4(src), h0 = ld_relaxed4(src + 1), l1 = ld_relaxed4(src + 2), h1 = ld_relaxed4(src + 3);
        const uint32_t z = work + SIG_V3 - 1024 + (t >> 6) * 4096 + (t & 63) * 16;
        sts128(z, 0u, 0u, 0u, 0u); sts128(z + SIG, 0u, 0u, 0u, 0u);
        if (t < 72) {
          const uint32_t zu = work + SIG_U + (t & 7) * U_LBO + (t >> 3) * 16;
          sts128(zu, 0u, 0u, 0u, 0u); sts128(zu + SIG, 0u, 0u, 0u, 0u);
        }
        const uint32_t a = work + SIG_U + (2 * (t & 3)) * U_LBO + ((t >> 2) + 9) * 16;
        sts128(a, l0.x, l0.z, h0.x, h0.z);
        sts128(a + U_LBO, l0.y, l0.w, h0.y, h0.w);
        sts128(a + SIG, l1.x, l1.z, h1.x, h1.z);
        sts128(a + SIG + U_LBO, l1.y, l1.w, h1.y, h1.w);
      }
      bar_sync(barid, 128);
#pragma unroll 1
      for (int k = w; k < 6; k += 4) sig_windows(work + (k & 1) * SIG, (k >> 1) * 32 + lane);
      fence_async();
      if (!is_ssm) {
        if (t < 24) bulk_wait0();
        __syncwarp();
        if (t == 0) { __threadfence(); red_release(&g_cntB[G * 32]); }
      }
      TSTAMP(6);
      bar_sync(is_ssm ? barid : 3, is_ssm ? 128 : 384);
      TSTAMP(7);
      uint32_t keep[8];
      float res[16];
#pragma unroll 1
      for (int c = 0; c < 2; c++) {
        const uint4 sc = lds128(sca0 + (2 * pi + c) * 16);
        conv_channel(tbl0 + (2 * pi + c) * TBL, work + c * SIG, y2b, y3b, __uint_as_float(sc.x), w, lane, barid, res);
        const float os = __uint_as_float(sc.z);
        if (c == 0) {
#pragma unroll
          for (int i = 0; i < 8; i++) keep[i] = pack_bf2(res[2 * i] * os, res[2 * i + 1] * os);
        } else {
          uint4* dst = g_s2 + ((size_t)(lane & 3) * 224 + pair) * 32 + w * 8 + (lane >> 2);
#pragma unroll
          for (int nt = 0; nt < 4; nt++) {
            const uint32_t n0 = pack_bf2(res[4 * nt] * os, res[4 * nt + 1] * os), n1 = pack_bf2(res[4 * nt + 2] * os, res[4 * nt + 3] * os);
            st_relaxed4(dst + nt * 4 * 224 * 32, __byte_perm(keep[2 * nt], n0, 0x5410), __byte_perm(keep[2 * nt + 1], n1, 0x5410),
                        __byte_perm(keep[2 * nt], n0, 0x7632), __byte_perm(keep[2 * nt + 1], n1, 0x7632));
          }
        }
      }
      TSTAMP(8 + pi);
    }
  } else {
    bar_arrive(1, 384);
    asm volatile("setmaxnreg.inc.sync.aligned.u32 208;");
    bar_sync(7, 384);
    const int g = lane >> 2, tq = lane & 3;
    uint32_t H[64];
    float r0, r1;
    {
      float acc[128];
      int sl = 0;
#pragma unroll 1
      for (int s = 0; s < 7; s++) {
        mbar_wait(bar0 + 8 * s, 0);
        const uint64_t da = mkdesc(sb + OFF_X + sl * 16384 + wg * 8192, 16, 1024, 1);
        const uint64_t db = mkdesc(sb + OFF_W + sl * 32768, 8192, 1024, 1);
        wg_fence();
#pragma unroll
        for (int k = 0; k < 4; k++) wg_ss_bf16_n256(acc, da + 2 * k, db + 128 * k, (s | k) != 0);
        wg_commit();
        wg_wait<1>();
        const int pl = sl == 0 ? 2 : sl - 1;
        sl = sl == 2 ? 0 : sl + 1;
        if (s > 0 && lane == 0 && last_release(ms + M_REL + 4 * s)) {
          const uint32_t bx = bar0 + 8 * (s < 5 ? s + 2 : 14);
          mbar_expect(bar0 + 8 * (s + 2), s < 5 ? 49152 : 32768);
          if (s < 5) tma_3d(sb + OFF_W + pl * 32768, &tm_w1, 0, 64 * mod7(kc0 + s + 2), 4 * rk, bar0 + 8 * (s + 2));
          else tma_2d(sb + OFF_W + pl * 32768, &tm_w2, 64 * mod7(rk + s - 4), 256 * rk, bar0 + 8 * (s + 2));
          if (s == 6) mbar_expect(bx, 16384);
          if (s != 5) tma_2d(sb + OFF_X + pl * 16384, &tm_x, 64 * (s < 5 ? mod7(kc0 + s + 2) : rk), 128 * G, bx);
        }
      }
      mbar_wait(bar0 + 8 * 15, 0);
      wg_fence();
      wg_ss_bf16_n256k(acc, mkdesc(ms + M_AX + wg * 1024, 0, 128, 0), mkdesc(ms + M_BX, 0, 128, 0), 1);
      wg_commit();
      wg_wait<1>();
      if (lane == 0 && last_release(ms + M_REL + 4 * 7)) {
#pragma unroll 1
        for (int c = 2; c < 4; c++) {
          mbar_expect(bar0 + 8 * (7 + c), 32768);
          tma_2d(sb + (c - 2) * OFF_X, &tm_w2, 64 * mod7(rk + 1 + c), 256 * rk, bar0 + 8 * (7 + c));
        }
      }
      bar_arrive(3, 384);
      r0 = lds32f(ms + M_R + (64 * wg + 16 * w + g) * 4);
      r1 = lds32f(ms + M_R + (64 * wg + 16 * w + g + 8) * 4);
      const float p0 = 0.7978845608028654f * r0, q0 = 0.0356774081363001f * r0 * r0 * r0;
      const float p1 = 0.7978845608028654f * r1, q1 = 0.0356774081363001f * r1 * r1 * r1;
      wg_wait<0>();
      fence_regs<128>(acc);
      TSTAMP(2);
#pragma unroll
      for (int i = 0; i < 64; i++) {
        const float pp = (i & 1) ? p1 : p0, qq = (i & 1) ? q1 : q0;
        const float a = acc[2 * i], c = acc[2 * i + 1];
        H[i] = pack_bf2(fmaf(a, tanhf_(a * fmaf(a * a, qq, pp)), a), fmaf(c, tanhf_(c * fmaf(c * c, qq, pp)), c));
      }
    }
    TSTAMP(3);
    float accA[32], accB[32], pre[32];
#pragma unroll
    for (int i = 0; i < 32; i++) pre[i] = 0.f;
    const uint4* inbox = g_part + (size_t)(G * 7 + rk) * 6 * 1024 + tid;
    auto issue2 = [&](int c, float* acc) {
      const uint32_t base = sb + ((0x0213021u >> (4 * c)) & 3) * 32768;
      mbar_wait(bar0 + 8 * (7 + c), 0);
      const uint64_t db = mkdesc(base, 8192, 1024, 1);
      wg_fence();
#pragma unroll
      for (int k = 0; k < 16; k++) wg_rs_bf16_n64(acc, H[4 * k], H[4 * k + 1], H[4 * k + 2], H[4 * k + 3], db + 128 * k, k != 0);
      wg_commit();
    };
    auto process = [&](int s, float* acc) {
      wg_wait<1>();
      fence_regs<32>(acc);
      if (s < 3 && lane == 0 && last_release(ms + M_REL + 4 * (8 + s))) {
        mbar_expect(bar0 + 8 * (11 + s), 32768);
        tma_2d(sb + ((0x021u >> (4 * s)) & 3) * 32768, &tm_w2, 64 * mod7(mod7(rk + 5 + s)), 256 * rk, bar0 + 8 * (11 + s));
      }
      send_part(g_part + ((size_t)(G * 7 + mod7(rk + 1 + s)) * 6 + s) * 1024 + tid, acc);
      if (s >= 3) recv_part(inbox + (s - 3) * 1024, pre);
    };
    issue2(0, accA);
    if (lane == 0) wait_count(&g_cntB[G * 32], (lds32(ms + M_EP) + 1) * NRK);
    __syncwarp();
#pragma unroll
    for (int s = 0; s < 6; s += 2) {
      issue2(s + 1, accB);
      process(s, accA);
      issue2(s + 2, accA);
      process(s + 1, accB);
    }
    TSTAMP(4);
    uint2 sw[8];
    {
      const uint2* sp = (const uint2*)(g_s2 + ((size_t)G * 224 + 32 * rk + tq) * 32 + w * 8 + g) + wg;
#pragma unroll 1
      for (int it = 0; it < SPIN_MAX; it++) {
        uint32_t m = 0;
#pragma unroll
        for (int i = 0; i < 8; i++) { sw[i] = ld_relaxed2(sp + i * 4 * 64); m = umax3(m, sw[i].x, sw[i].y); }
        if (m != 0xffffffffu) break;
      }
    }
    uint32_t b2w[8];
#pragma unroll
    for (int i = 0; i < 8; i++) b2w[i] = __ldg((const uint32_t*)(p.b2 + 64 * rk) + 4 * i + tq);
    TSTAMP(5);
    mbar_wait(bar0 + 8 * 14, 0);
    const uint32_t xa = sb + OFF_X + 2 * 16384 + (64 * wg + 16 * w + (lane & 15)) * 128;
    uint32_t xw[16];
#pragma unroll
    for (int q = 0; q < 4; q++) ldsm4(xa + (((2 * q + (lane >> 4)) ^ (lane & 7)) << 4), xw[4 * q], xw[4 * q + 1], xw[4 * q + 2], xw[4 * q + 3]);
#pragma unroll 1
    for (int s = 3; s < 6; s++) recv_part(inbox + s * 1024, pre);
    wg_wait<0>();
    fence_regs<32>(accA);
    TSTAMP(7);
    r0 *= 0.5f; r1 *= 0.5f;
#pragma unroll
    for (int k = 0; k < 16; k++) {
      const uint32_t sv = (k & 1) ? sw[k >> 1].y : sw[k >> 1].x;
      const float rr = (k & 1) ? r1 : r0;
      const float o0 = fmaf(pre[2 * k] + accA[2 * k], rr, bf_lo(b2w[k >> 1])), o1 = fmaf(pre[2 * k + 1] + accA[2 * k + 1], rr, bf_hi(b2w[k >> 1]));
      const float g0 = o0 * rcpf_(1.f + ex2f(o0 * -1.4426950408889634f)), g1 = o1 * rcpf_(1.f + ex2f(o1 * -1.4426950408889634f));
      xw[k] = pack_bf2(fmaf(bf_lo(sv), g0, bf_lo(xw[k])), fmaf(bf_hi(sv), g1, bf_hi(xw[k])));
    }
#pragma unroll
    for (int q = 0; q < 4; q++) stsm4(xa + (((2 * q + (lane >> 4)) ^ (lane & 7)) << 4), xw[4 * q], xw[4 * q + 1], xw[4 * q + 2], xw[4 * q + 3]);
    fence_async();
    __syncwarp();
    if (lane == 0) {
      tma_store_2d(&tm_out, sb + OFF_X + 2 * 16384 + (64 * wg + 16 * w) * 128, 64 * rk, 128 * G + 64 * wg + 16 * w);
      bulk_commit();
      bulk_wait0_read();
    }
    TSTAMP(8);
  }
}

typedef CUresult (*EncodeFn)(CUtensorMap*, CUtensorMapDataType, cuuint32_t, void*, const cuuint64_t*, const cuuint64_t*,
                             const cuuint32_t*, const cuuint32_t*, CUtensorMapInterleave, CUtensorMapSwizzle,
                             CUtensorMapL2promotion, CUtensorMapFloatOOBfill);

void make_map(EncodeFn fn, CUtensorMap* m, const void* ptr, int rank, const cuuint64_t* dims, const cuuint64_t* strides, const cuuint32_t* box) {
  const cuuint32_t es[3] = {1, 1, 1};
  fn(m, CU_TENSOR_MAP_DATA_TYPE_BFLOAT16, rank, const_cast<void*>(ptr), dims, strides, box, es, CU_TENSOR_MAP_INTERLEAVE_NONE,
     CU_TENSOR_MAP_SWIZZLE_128B, CU_TENSOR_MAP_L2_PROMOTION_L2_128B, CU_TENSOR_MAP_FLOAT_OOB_FILL_NONE);
}

}

extern "C" void kernel_launch(void* const* d_in, const int* in_sizes, int n_in, void* d_out, int out_size) {
  (void)in_sizes; (void)n_in; (void)out_size;
  void* fnp = nullptr;
  cudaDriverEntryPointQueryResult qr;
  cudaGetDriverEntryPoint("cuTensorMapEncodeTiled", &fnp, cudaEnableDefault, &qr);
  EncodeFn fn = (EncodeFn)fnp;
  Params p;
  p.x = (const __nv_bfloat16*)d_in[0];
  p.a_re = (const __nv_bfloat16*)d_in[1]; p.a_im = (const __nv_bfloat16*)d_in[2];
  p.b_re = (const __nv_bfloat16*)d_in[3]; p.b_im = (const __nv_bfloat16*)d_in[4];
  p.c_re = (const __nv_bfloat16*)d_in[5]; p.c_im = (const __nv_bfloat16*)d_in[6];
  p.log_dt = (const __nv_bfloat16*)d_in[7]; p.dskip = (const __nv_bfloat16*)d_in[8];
  p.w1 = (const __nv_bfloat16*)d_in[10]; p.b1 = (const __nv_bfloat16*)d_in[11];
  p.w2 = (const __nv_bfloat16*)d_in[12]; p.b2 = (const __nv_bfloat16*)d_in[13];
  CUtensorMap mx, mw1, mw2, mo;
  {
    const cuuint64_t dims[2] = {448, 2048}, str[1] = {896};
    const cuuint32_t box[2] = {64, 128}, boxo[2] = {64, 16};
    make_map(fn, &mx, p.x, 2, dims, str, box);
    make_map(fn, &mo, d_out, 2, dims, str, boxo);
  }
  {
    const cuuint64_t dims[3] = {64, 448, 28}, str[2] = {3584, 128};
    const cuuint32_t box[3] = {64, 64, 4};
    make_map(fn, &mw1, p.w1, 3, dims, str, box);
  }
  {
    const cuuint64_t dims[2] = {448, 1792}, str[1] = {896};
    const cuuint32_t box[2] = {64, 256};
    make_map(fn, &mw2, p.w2, 2, dims, str, box);
  }
  cudaFuncSetAttribute(fused_kernel, cudaFuncAttributeMaxDynamicSharedMemorySize, SMEM_BYTES);
  fused_kernel<<<NCTA, 384, SMEM_BYTES>>>(mx, mw1, mw2, mo, p);
}
```

```cpp
#include <cuda_runtime.h>
#include <cuda_bf16.h>
#include <cuda_fp16.h>
#include <cuda.h>
#include <stdint.h>

namespace {

constexpr int D_ = 448, NST = 256, F_ = 1792;
constexpr int NRK = 7, NMLP = 112, NCTA = 132;
constexpr int SPIN_MAX = 1 << 21;

__device__ uint4 g_xnT[128 * 448 * 2];
__device__ uint4 g_ax[2048];
__device__ float g_r[2048];
__device__ uint4 g_bx[F_];
__device__ uint4 g_part[16 * 7 * 6 * 1024];
__device__ uint4 g_s2[16 * 224 * 32];
__device__ uint4 g_tbl[104 * 329];
__device__ unsigned g_cntA;
__device__ unsigned g_cntB[16 * 32];
__device__ unsigned g_epoch;
#define TSTAMP(i)

constexpr int TBL_SC = 5248, TBL = 5264;
constexpr int TBL_C1 = 2624;
constexpr int SIG = 19584;
constexpr int SIG_U = 0, U_LBO = 656, SIG_V3 = 6272, SIG_V5 = 10368, SIG_V7 = 13440, SIG_V9 = 15488, SIG_V2 = 17536;
constexpr int Y2B = 6528, Y3B = 4352;
constexpr int KREC = 160, KSTG = 32 * KREC;
constexpr int OFF_W = 0, OFF_X = 98304, OFF_A = 147456, OFF_B = OFF_A + 8 * KSTG + 2560, OFF_T = OFF_B + 4 * KSTG;
constexpr int OFF_FF = OFF_T + 15872, OFF_M = OFF_FF + 2048;
constexpr int B_AX = Y2B, B_BX = B_AX + 2048, B_R = B_BX + 4096;
constexpr int M_BAR = 0, M_REL = 128, M_EP = 192, M_CSR = 256, M_END = 512;
constexpr int SMEM_BYTES = OFF_M + M_END;
constexpr int S_WORK = 63232, S_WGB = 2 * SIG + Y2B + Y3B;
static_assert(S_WORK + 3 * S_WGB <= OFF_M && SMEM_BYTES <= 232448, "smem");

struct Params {
  const __nv_bfloat16 *x, *a_re, *a_im, *b_re, *b_im, *c_re, *c_im, *log_dt, *dskip, *w1, *b1, *w2, *b2;
};

__device__ __forceinline__ int rd_tid() { int v; asm volatile("mov.u32 %0, %%tid.x;" : "=r"(v)); return v; }
__device__ __forceinline__ int rd_bid() { int v; asm volatile("mov.u32 %0, %%ctaid.x;" : "=r"(v)); return v; }
__device__ __forceinline__ uint32_t smem_u32(const void* p) { return (uint32_t)__cvta_generic_to_shared(p); }
__device__ __forceinline__ void mbar_init(uint32_t bar, int cnt) { asm volatile("mbarrier.init.shared::cta.b64 [%0], %1;" ::"r"(bar), "r"(cnt)); }
__device__ __forceinline__ void mbar_expect(uint32_t bar, uint32_t bytes) {
  asm volatile("mbarrier.arrive.expect_tx.shared::cta.b64 _, [%0], %1;" ::"r"(bar), "r"(bytes) : "memory");
}
__device__ __forceinline__ void mbar_wait(uint32_t bar, uint32_t parity) {
  uint32_t done = 0;
#pragma unroll 1
  for (int it = 0; it < SPIN_MAX; it++) {
    asm volatile("{.reg .pred p; mbarrier.try_wait.parity.shared::cta.b64 p, [%1], %2; selp.u32 %0,1,0,p;}"
                 : "=r"(done) : "r"(bar), "r"(parity) : "memory");
    if (done) break;
  }
}
__device__ __forceinline__ void tma_2d(uint32_t dst, const CUtensorMap* m, int c0, int c1, uint32_t bar) {
  asm volatile("cp.async.bulk.tensor.2d.shared::cluster.global.mbarrier::complete_tx::bytes [%0], [%1, {%3, %4}], [%2];"
               ::"r"(dst), "l"(m), "r"(bar), "r"(c0), "r"(c1) : "memory");
}
__device__ __forceinline__ void tma_3d(uint32_t dst, const CUtensorMap* m, int c0, int c1, int c2, uint32_t bar) {
  asm volatile("cp.async.bulk.tensor.3d.shared::cluster.global.mbarrier::complete_tx::bytes [%0], [%1, {%3, %4, %5}], [%2];"
               ::"r"(dst), "l"(m), "r"(bar), "r"(c0), "r"(c1), "r"(c2) : "memory");
}
__device__ __forceinline__ void tma_store_2d(const CUtensorMap* m, uint32_t src, int c0, int c1) {
  asm volatile("cp.async.bulk.tensor.2d.global.shared::cta.bulk_group [%0, {%2, %3}], [%1];"
               ::"l"(m), "r"(src), "r"(c0), "r"(c1) : "memory");
}
__device__ __forceinline__ void bulk_s2g(void* dst, uint32_t src, uint32_t bytes) {
  asm volatile("cp.async.bulk.global.shared::cta.bulk_group [%0], [%1], %2;" ::"l"(dst), "r"(src), "r"(bytes) : "memory");
}
__device__ __forceinline__ void bulk_g2s(uint32_t dst, const void* src, uint32_t bytes, uint32_t bar) {
  asm volatile("cp.async.bulk.shared::cluster.global.mbarrier::complete_tx::bytes [%0], [%1], %2, [%3];"
               ::"r"(dst), "l"(src), "r"(bytes), "r"(bar) : "memory");
}
__device__ __forceinline__ void bulk_commit() { asm volatile("cp.async.bulk.commit_group;" ::: "memory"); }
__device__ __forceinline__ void bulk_wait0() { asm volatile("cp.async.bulk.wait_group 0;" ::: "memory"); }
__device__ __forceinline__ void bulk_wait0_read() { asm volatile("cp.async.bulk.wait_group.read 0;" ::: "memory"); }
__device__ __forceinline__ void fence_async() { asm volatile("fence.proxy.async.shared::cta;" ::: "memory"); }
__device__ __forceinline__ void bar_sync(int id, int n) { asm volatile("bar.sync %0, %1;" ::"r"(id), "r"(n) : "memory"); }
__device__ __forceinline__ void bar_arrive(int id, int n) { asm volatile("bar.arrive %0, %1;" ::"r"(id), "r"(n) : "memory"); }
__device__ __forceinline__ void wg_fence() { asm volatile("wgmma.fence.sync.aligned;" ::: "memory"); }
__device__ __forceinline__ void wg_commit() { asm volatile("wgmma.commit_group.sync.aligned;" ::: "memory"); }
template <int N> __device__ __forceinline__ void wg_wait() { asm volatile("wgmma.wait_group.sync.aligned %0;" ::"n"(N) : "memory"); }
template <int N> __device__ __forceinline__ void fence_regs(float* d) {
#pragma unroll
  for (int i = 0; i < N; i++) asm volatile("" : "+f"(d[i])::"memory");
}
__device__ __forceinline__ uint64_t mkdesc(uint32_t addr, uint32_t lbo, uint32_t sbo, uint32_t sw) {
  return (uint64_t)((addr & 0x3FFFF) >> 4) | ((uint64_t)(lbo >> 4) << 16) | ((uint64_t)(sbo >> 4) << 32) | ((uint64_t)sw << 62);
}
__device__ __forceinline__ uint32_t lds32(uint32_t a) { uint32_t v; asm volatile("ld.shared.b32 %0, [%1];" : "=r"(v) : "r"(a) : "memory"); return v; }
__device__ __forceinline__ float lds32f(uint32_t a) { float v; asm volatile("ld.shared.f32 %0, [%1];" : "=f"(v) : "r"(a) : "memory"); return v; }
__device__ __forceinline__ float2 lds64f(uint32_t a) { float2 v; asm volatile("ld.shared.v2.f32 {%0,%1}, [%2];" : "=f"(v.x), "=f"(v.y) : "r"(a) : "memory"); return v; }
__device__ __forceinline__ uint4 lds128(uint32_t a) {
  uint4 v; asm volatile("ld.shared.v4.b32 {%0,%1,%2,%3}, [%4];" : "=r"(v.x), "=r"(v.y), "=r"(v.z), "=r"(v.w) : "r"(a) : "memory"); return v;
}
__device__ __forceinline__ void sts16(uint32_t a, uint16_t v) { asm volatile("st.shared.b16 [%0], %1;" ::"r"(a), "h"(v) : "memory"); }
__device__ __forceinline__ void sts32f(uint32_t a, float v) { asm volatile("st.shared.f32 [%0], %1;" ::"r"(a), "f"(v) : "memory"); }
__device__ __forceinline__ void sts64f(uint32_t a, float x, float y) { asm volatile("st.shared.v2.f32 [%0], {%1,%2};" ::"r"(a), "f"(x), "f"(y) : "memory"); }
__device__ __forceinline__ void sts128(uint32_t a, uint32_t x, uint32_t y, uint32_t z, uint32_t w) {
  asm volatile("st.shared.v4.b32 [%0], {%1,%2,%3,%4};" ::"r"(a), "r"(x), "r"(y), "r"(z), "r"(w) : "memory");
}
__device__ __forceinline__ void ldsm4(uint32_t a, uint32_t& r0, uint32_t& r1, uint32_t& r2, uint32_t& r3) {
  asm volatile("ldmatrix.sync.aligned.m8n8.x4.shared.b16 {%0,%1,%2,%3}, [%4];" : "=r"(r0), "=r"(r1), "=r"(r2), "=r"(r3) : "r"(a) : "memory");
}
__device__ __forceinline__ void ldsm4t(uint32_t a, uint32_t& r0, uint32_t& r1, uint32_t& r2, uint32_t& r3) {
  asm volatile("ldmatrix.sync.aligned.m8n8.x4.trans.shared.b16 {%0,%1,%2,%3}, [%4];" : "=r"(r0), "=r"(r1), "=r"(r2), "=r"(r3) : "r"(a) : "memory");
}
__device__ __forceinline__ void stsm4(uint32_t a, uint32_t r0, uint32_t r1, uint32_t r2, uint32_t r3) {
  asm volatile("stmatrix.sync.aligned.m8n8.x4.shared.b16 [%0], {%1,%2,%3,%4};" ::"r"(a), "r"(r0), "r"(r1), "r"(r2), "r"(r3) : "memory");
}
__device__ __forceinline__ void mma_f16(float* c, uint32_t a0, uint32_t a1, uint32_t a2, uint32_t a3, uint32_t b0, uint32_t b1) {
  asm volatile("mma.sync.aligned.m16n8k16.row.col.f32.f16.f16.f32 {%0,%1,%2,%3},{%4,%5,%6,%7},{%8,%9},{%0,%1,%2,%3};"
               : "+f"(c[0]), "+f"(c[1]), "+f"(c[2]), "+f"(c[3]) : "r"(a0), "r"(a1), "r"(a2), "r"(a3), "r"(b0), "r"(b1));
}
__device__ __forceinline__ uint4 ld_relaxed4(const void* p) {
  uint4 v; asm volatile("ld.relaxed.gpu.global.v4.b32 {%0,%1,%2,%3}, [%4];" : "=r"(v.x), "=r"(v.y), "=r"(v.z), "=r"(v.w) : "l"(p) : "memory"); return v;
}
__device__ __forceinline__ uint2 ld_relaxed2(const void* p) {
  uint2 v; asm volatile("ld.relaxed.gpu.global.v2.b32 {%0,%1}, [%2];" : "=r"(v.x), "=r"(v.y) : "l"(p) : "memory"); return v;
}
__device__ __forceinline__ void st_relaxed4(void* p, uint32_t x, uint32_t y, uint32_t z, uint32_t w) {
  asm volatile("st.relaxed.gpu.global.v4.b32 [%0], {%1,%2,%3,%4};" ::"l"(p), "r"(x), "r"(y), "r"(z), "r"(w) : "memory");
}
__device__ __forceinline__ unsigned ld_relaxed1(const unsigned* p) {
  unsigned v; asm volatile("ld.relaxed.gpu.global.u32 %0, [%1];" : "=r"(v) : "l"(p) : "memory"); return v;
}
__device__ __forceinline__ void red_release(unsigned* p) {
  asm volatile("red.release.gpu.global.add.u32 [%0], 1;" ::"l"(p) : "memory");
}
__device__ __forceinline__ void wait_count(const unsigned* p, unsigned target) {
#pragma unroll 1
  for (int it = 0; it < SPIN_MAX; it++) {
    if ((int)(ld_relaxed1(p) - target) >= 0) break;
    __nanosleep(40);
  }
  asm volatile("fence.acq_rel.gpu;" ::: "memory");
}
__device__ __forceinline__ uint32_t pack_h2(float lo, float hi) { uint32_t r; asm("cvt.rn.f16x2.f32 %0, %1, %2;" : "=r"(r) : "f"(hi), "f"(lo)); return r; }
__device__ __forceinline__ uint32_t pack_bf2(float lo, float hi) { uint32_t r; asm("cvt.rn.bf16x2.f32 %0, %1, %2;" : "=r"(r) : "f"(hi), "f"(lo)); return r; }
__device__ __forceinline__ uint32_t pack_bf2v(float lo, float hi) { uint32_t r; asm volatile("cvt.rn.bf16x2.f32 %0, %1, %2;" : "=r"(r) : "f"(hi), "f"(lo)); return r; }
__device__ __forceinline__ float bf_lo(uint32_t w) { return __uint_as_float(w << 16); }
__device__ __forceinline__ float bf_hi(uint32_t w) { return __uint_as_float(w & 0xffff0000u); }
__device__ __forceinline__ float rbf(float v) { return __bfloat162float(__float2bfloat16_rn(v)); }
__device__ __forceinline__ float2 h2f(uint32_t w) { return __half22float2(*reinterpret_cast<__half2*>(&w)); }
__device__ __forceinline__ float ex2f(float v) { float r; asm("ex2.approx.ftz.f32 %0, %1;" : "=f"(r) : "f"(v)); return r; }
__device__ __forceinline__ float rcpf_(float v) { float r; asm("rcp.approx.f32 %0, %1;" : "=f"(r) : "f"(v)); return r; }
__device__ __forceinline__ float sqrtf_(float v) { float r; asm("sqrt.approx.f32 %0, %1;" : "=f"(r) : "f"(v)); return r; }
__device__ __forceinline__ float tanhf_(float v) { float r; asm volatile("tanh.approx.f32 %0, %1;" : "=f"(r) : "f"(v)); return r; }
__device__ __forceinline__ uint32_t umax3(uint32_t a, uint32_t b, uint32_t c) { return max(max(a, b), c); }

__device__ __forceinline__ void wg_ss_bf16_n256(float* d, uint64_t da, uint64_t db, int sc) {
  asm volatile("{.reg .pred p; setp.ne.b32 p, %130, 0;\n"
    "wgmma.mma_async.sync.aligned.m64n256k16.f32.bf16.bf16 {%0, %1, %2, %3, %4, %5, %6, %7, %8, %9, %10, %11, %12, %13, %14, %15, %16, %17, %18, %19, %20, %21, %22, %23, %24, %25, %26, %27, %28, %29, %30, %31, %32, %33, %34, %35, %36, %37, %38, %39, %40, %41, %42, %43, %44, %45, %46, %47, %48, %49, %50, %51, %52, %53, %54, %55, %56, %57, %58, %59, %60, %61, %62, %63, %64, %65, %66, %67, %68, %69, %70, %71, %72, %73, %74, %75, %76, %77, %78, %79, %80, %81, %82, %83, %84, %85, %86, %87, %88, %89, %90, %91, %92, %93, %94, %95, %96, %97, %98, %99, %100, %101, %102, %103, %104, %105, %106, %107, %108, %109, %110, %111, %112, %113, %114, %115, %116, %117, %118, %119, %120, %121, %122, %123, %124, %125, %126, %127}, %128, %129, p, 1, 1, 0, 1;}\n"
    : "+f"(d[0]), "+f"(d[1]), "+f"(d[2]), "+f"(d[3]), "+f"(d[4]), "+f"(d[5]), "+f"(d[6]), "+f"(d[7]), "+f"(d[8]), "+f"(d[9]), "+f"(d[10]), "+f"(d[11]), "+f"(d[12]), "+f"(d[13]), "+f"(d[14]), "+f"(d[15]), "+f"(d[16]), "+f"(d[17]), "+f"(d[18]), "+f"(d[19]), "+f"(d[20]), "+f"(d[21]), "+f"(d[22]), "+f"(d[23]), "+f"(d[24]), "+f"(d[25]), "+f"(d[26]), "+f"(d[27]), "+f"(d[28]), "+f"(d[29]), "+f"(d[30]), "+f"(d[31]), "+f"(d[32]), "+f"(d[33]), "+f"(d[34]), "+f"(d[35]), "+f"(d[36]), "+f"(d[37]), "+f"(d[38]), "+f"(d[39]), "+f"(d[40]), "+f"(d[41]), "+f"(d[42]), "+f"(d[43]), "+f"(d[44]), "+f"(d[45]), "+f"(d[46]), "+f"(d[47]), "+f"(d[48]), "+f"(d[49]), "+f"(d[50]), "+f"(d[51]), "+f"(d[52]), "+f"(d[53]), "+f"(d[54]), "+f"(d[55]), "+f"(d[56]), "+f"(d[57]), "+f"(d[58]), "+f"(d[59]), "+f"(d[60]), "+f"(d[61]), "+f"(d[62]), "+f"(d[63]), "+f"(d[64]), "+f"(d[65]), "+f"(d[66]), "+f"(d[67]), "+f"(d[68]), "+f"(d[69]), "+f"(d[70]), "+f"(d[71]), "+f"(d[72]), "+f"(d[73]), "+f"(d[74]), "+f"(d[75]), "+f"(d[76]), "+f"(d[77]), "+f"(d[78]), "+f"(d[79]), "+f"(d[80]), "+f"(d[81]), "+f"(d[82]), "+f"(d[83]), "+f"(d[84]), "+f"(d[85]), "+f"(d[86]), "+f"(d[87]), "+f"(d[88]), "+f"(d[89]), "+f"(d[90]), "+f"(d[91]), "+f"(d[92]), "+f"(d[93]), "+f"(d[94]), "+f"(d[95]), "+f"(d[96]), "+f"(d[97]), "+f"(d[98]), "+f"(d[99]), "+f"(d[100]), "+f"(d[101]), "+f"(d[102]), "+f"(d[103]), "+f"(d[104]), "+f"(d[105]), "+f"(d[106]), "+f"(d[107]), "+f"(d[108]), "+f"(d[109]), "+f"(d[110]), "+f"(d[111]), "+f"(d[112]), "+f"(d[113]), "+f"(d[114]), "+f"(d[115]), "+f"(d[116]), "+f"(d[117]), "+f"(d[118]), "+f"(d[119]), "+f"(d[120]), "+f"(d[121]), "+f"(d[122]), "+f"(d[123]), "+f"(d[124]), "+f"(d[125]), "+f"(d[126]), "+f"(d[127])
    : "l"(da), "l"(db), "r"(sc));
}

__device__ __forceinline__ void wg_ss_bf16_n256k(float* d, uint64_t da, uint64_t db, int sc) {
  asm volatile("{.reg .pred p; setp.ne.b32 p, %130, 0;\n"
    "wgmma.mma_async.sync.aligned.m64n256k16.f32.bf16.bf16 {%0, %1, %2, %3, %4, %5, %6, %7, %8, %9, %10, %11, %12, %13, %14, %15, %16, %17, %18, %19, %20, %21, %22, %23, %24, %25, %26, %27, %28, %29, %30, %31, %32, %33, %34, %35, %36, %37, %38, %39, %40, %41, %42, %43, %44, %45, %46, %47, %48, %49, %50, %51, %52, %53, %54, %55, %56, %57, %58, %59, %60, %61, %62, %63, %64, %65, %66, %67, %68, %69, %70, %71, %72, %73, %74, %75, %76, %77, %78, %79, %80, %81, %82, %83, %84, %85, %86, %87, %88, %89, %90, %91, %92, %93, %94, %95, %96, %97, %98, %99, %100, %101, %102, %103, %104, %105, %106, %107, %108, %109, %110, %111, %112, %113, %114, %115, %116, %117, %118, %119, %120, %121, %122, %123, %124, %125, %126, %127}, %128, %129, p, 1, 1, 0, 0;}\n"
    : "+f"(d[0]), "+f"(d[1]), "+f"(d[2]), "+f"(d[3]), "+f"(d[4]), "+f"(d[5]), "+f"(d[6]), "+f"(d[7]), "+f"(d[8]), "+f"(d[9]), "+f"(d[10]), "+f"(d[11]), "+f"(d[12]), "+f"(d[13]), "+f"(d[14]), "+f"(d[15]), "+f"(d[16]), "+f"(d[17]), "+f"(d[18]), "+f"(d[19]), "+f"(d[20]), "+f"(d[21]), "+f"(d[22]), "+f"(d[23]), "+f"(d[24]), "+f"(d[25]), "+f"(d[26]), "+f"(d[27]), "+f"(d[28]), "+f"(d[29]), "+f"(d[30]), "+f"(d[31]), "+f"(d[32]), "+f"(d[33]), "+f"(d[34]), "+f"(d[35]), "+f"(d[36]), "+f"(d[37]), "+f"(d[38]), "+f"(d[39]), "+f"(d[40]), "+f"(d[41]), "+f"(d[42]), "+f"(d[43]), "+f"(d[44]), "+f"(d[45]), "+f"(d[46]), "+f"(d[47]), "+f"(d[48]), "+f"(d[49]), "+f"(d[50]), "+f"(d[51]), "+f"(d[52]), "+f"(d[53]), "+f"(d[54]), "+f"(d[55]), "+f"(d[56]), "+f"(d[57]), "+f"(d[58]), "+f"(d[59]), "+f"(d[60]), "+f"(d[61]), "+f"(d[62]), "+f"(d[63]), "+f"(d[64]), "+f"(d[65]), "+f"(d[66]), "+f"(d[67]), "+f"(d[68]), "+f"(d[69]), "+f"(d[70]), "+f"(d[71]), "+f"(d[72]), "+f"(d[73]), "+f"(d[74]), "+f"(d[75]), "+f"(d[76]), "+f"(d[77]), "+f"(d[78]), "+f"(d[79]), "+f"(d[80]), "+f"(d[81]), "+f"(d[82]), "+f"(d[83]), "+f"(d[84]), "+f"(d[85]), "+f"(d[86]), "+f"(d[87]), "+f"(d[88]), "+f"(d[89]), "+f"(d[90]), "+f"(d[91]), "+f"(d[92]), "+f"(d[93]), "+f"(d[94]), "+f"(d[95]), "+f"(d[96]), "+f"(d[97]), "+f"(d[98]), "+f"(d[99]), "+f"(d[100]), "+f"(d[101]), "+f"(d[102]), "+f"(d[103]), "+f"(d[104]), "+f"(d[105]), "+f"(d[106]), "+f"(d[107]), "+f"(d[108]), "+f"(d[109]), "+f"(d[110]), "+f"(d[111]), "+f"(d[112]), "+f"(d[113]), "+f"(d[114]), "+f"(d[115]), "+f"(d[116]), "+f"(d[117]), "+f"(d[118]), "+f"(d[119]), "+f"(d[120]), "+f"(d[121]), "+f"(d[122]), "+f"(d[123]), "+f"(d[124]), "+f"(d[125]), "+f"(d[126]), "+f"(d[127])
    : "l"(da), "l"(db), "r"(sc));
}

__device__ __forceinline__ void wg_rs_bf16_n64(float* d, uint32_t a0, uint32_t a1, uint32_t a2, uint32_t a3, uint64_t db, int sc) {
  asm volatile("{.reg .pred p; setp.ne.b32 p, %37, 0;\n"
    "wgmma.mma_async.sync.aligned.m64n64k16.f32.bf16.bf16 {%0, %1, %2, %3, %4, %5, %6, %7, %8, %9, %10, %11, %12, %13, %14, %15, %16, %17, %18, %19, %20, %21, %22, %23, %24, %25, %26, %27, %28, %29, %30, %31}, {%32,%33,%34,%35}, %36, p, 1, 1, 1;}\n"
    : "+f"(d[0]), "+f"(d[1]), "+f"(d[2]), "+f"(d[3]), "+f"(d[4]), "+f"(d[5]), "+f"(d[6]), "+f"(d[7]), "+f"(d[8]), "+f"(d[9]), "+f"(d[10]), "+f"(d[11]), "+f"(d[12]), "+f"(d[13]), "+f"(d[14]), "+f"(d[15]), "+f"(d[16]), "+f"(d[17]), "+f"(d[18]), "+f"(d[19]), "+f"(d[20]), "+f"(d[21]), "+f"(d[22]), "+f"(d[23]), "+f"(d[24]), "+f"(d[25]), "+f"(d[26]), "+f"(d[27]), "+f"(d[28]), "+f"(d[29]), "+f"(d[30]), "+f"(d[31])
    : "r"(a0), "r"(a1), "r"(a2), "r"(a3), "l"(db), "r"(sc));
}

__device__ __forceinline__ void wg_rs_f16_n32k(float* d, uint32_t a0, uint32_t a1, uint32_t a2, uint32_t a3, uint64_t db, int sc) {
  asm volatile("{.reg .pred p; setp.ne.b32 p, %21, 0;\n"
    "wgmma.mma_async.sync.aligned.m64n32k16.f32.f16.f16 {%0, %1, %2, %3, %4, %5, %6, %7, %8, %9, %10, %11, %12, %13, %14, %15}, {%16,%17,%18,%19}, %20, p, 1, 1, 0;}\n"
    : "+f"(d[0]), "+f"(d[1]), "+f"(d[2]), "+f"(d[3]), "+f"(d[4]), "+f"(d[5]), "+f"(d[6]), "+f"(d[7]), "+f"(d[8]), "+f"(d[9]), "+f"(d[10]), "+f"(d[11]), "+f"(d[12]), "+f"(d[13]), "+f"(d[14]), "+f"(d[15])
    : "r"(a0), "r"(a1), "r"(a2), "r"(a3), "l"(db), "r"(sc));
}

__device__ __forceinline__ void wg_rs_f16_n24t(float* d, uint32_t a0, uint32_t a1, uint32_t a2, uint32_t a3, uint64_t db, int sc) {
  asm volatile("{.reg .pred p; setp.ne.b32 p, %17, 0;\n"
    "wgmma.mma_async.sync.aligned.m64n24k16.f32.f16.f16 {%0, %1, %2, %3, %4, %5, %6, %7, %8, %9, %10, %11}, {%12,%13,%14,%15}, %16, p, 1, 1, 1;}\n"
    : "+f"(d[0]), "+f"(d[1]), "+f"(d[2]), "+f"(d[3]), "+f"(d[4]), "+f"(d[5]), "+f"(d[6]), "+f"(d[7]), "+f"(d[8]), "+f"(d[9]), "+f"(d[10]), "+f"(d[11])
    : "r"(a0), "r"(a1), "r"(a2), "r"(a3), "l"(db), "r"(sc));
}

__device__ __forceinline__ void wg_rs_f16_n16t(float* d, uint32_t a0, uint32_t a1, uint32_t a2, uint32_t a3, uint64_t db, int sc) {
  asm volatile("{.reg .pred p; setp.ne.b32 p, %13, 0;\n"
    "wgmma.mma_async.sync.aligned.m64n16k16.f32.f16.f16 {%0, %1, %2, %3, %4, %5, %6, %7}, {%8,%9,%10,%11}, %12, p, 1, 1, 1;}\n"
    : "+f"(d[0]), "+f"(d[1]), "+f"(d[2]), "+f"(d[3]), "+f"(d[4]), "+f"(d[5]), "+f"(d[6]), "+f"(d[7])
    : "r"(a0), "r"(a1), "r"(a2), "r"(a3), "l"(db), "r"(sc));
}

struct cf { float x, y; };
__device__ __forceinline__ cf cmul(cf a, cf b) { cf r; r.x = fmaf(a.x, b.x, -a.y * b.y); r.y = fmaf(a.x, b.y, a.y * b.x); return r; }
__device__ __forceinline__ cf zpow(float rho2, float phi, float e) {
  const float m = ex2f(rho2 * e), ang = phi * e;
  cf r; r.x = m * __cosf(ang); r.y = m * __sinf(ang); return r;
}
__device__ __forceinline__ uint32_t hprod(uint32_t v, uint32_t vr, uint32_t r) {
  __half2 hv = *reinterpret_cast<__half2*>(&v), hvr = *reinterpret_cast<__half2*>(&vr), hr = *reinterpret_cast<__half2*>(&r);
  __half2 o = __hfma2(__high2half2(hr), hvr, __hmul2(__low2half2(hr), hv));
  return *reinterpret_cast<uint32_t*>(&o);
}
__device__ __forceinline__ uint32_t rot90(uint32_t v) { return __byte_perm(v, 0, 0x1032) ^ 0x00008000u; }
__device__ __forceinline__ uint32_t hadd2u(uint32_t a, uint32_t b) {
  __half2 o = __hadd2(*reinterpret_cast<__half2*>(&a), *reinterpret_cast<__half2*>(&b));
  return *reinterpret_cast<uint32_t*>(&o);
}

__device__ __forceinline__ void kgen_warp(const Params& p, int d, int wd0, int nw, uint32_t stg, uint32_t tbl, int zt, int zn, int lane) {
  const int off = d * (NST / 2) + lane * 4;
  const uint32_t* P[6] = {(const uint32_t*)p.a_re, (const uint32_t*)p.a_im, (const uint32_t*)p.b_re,
                          (const uint32_t*)p.b_im, (const uint32_t*)p.c_re, (const uint32_t*)p.c_im};
  uint32_t cur[6], nxt[6];
#pragma unroll
  for (int i = 0; i < 6; i++) { cur[i] = __ldg(P[i] + off + wd0); nxt[i] = __ldg(P[i] + off + wd0 + nw - 1); }
  float dl, dt, inv_sc;
  {
    const uint4 br = __ldg((const uint4*)(P[2] + off)), bi = __ldg((const uint4*)(P[3] + off));
    const uint4 cr = __ldg((const uint4*)(P[4] + off)), ci = __ldg((const uint4*)(P[5] + off));
    const float ldt = __bfloat162float(p.log_dt[d]), dk = __bfloat162float(p.dskip[d]);
#pragma unroll 1
    for (int i = zt; i < TBL_SC / 16; i += zn) sts128(tbl + i * 16, 0u, 0u, 0u, 0u);
    const uint32_t M = 0x7fff7fffu;
    uint32_t mb = __vmaxu2(__vmaxu2(__vmaxu2(br.x & M, br.y & M), __vmaxu2(br.z & M, br.w & M)),
                           __vmaxu2(__vmaxu2(bi.x & M, bi.y & M), __vmaxu2(bi.z & M, bi.w & M)));
    uint32_t mc = __vmaxu2(__vmaxu2(__vmaxu2(cr.x & M, cr.y & M), __vmaxu2(cr.z & M, cr.w & M)),
                           __vmaxu2(__vmaxu2(ci.x & M, ci.y & M), __vmaxu2(ci.z & M, ci.w & M)));
    mb = __reduce_max_sync(0xffffffffu, max(mb << 16, mb & 0xffff0000u));
    mc = __reduce_max_sync(0xffffffffu, max(mc << 16, mc & 0xffff0000u));
    dt = rbf(ex2f(ldt * 1.4426950408889634f));
    const float dsk = dk * rcpf_(dt);
    float sc = fmaxf(0.125f * __uint_as_float(mb) * __uint_as_float(mc), fabsf(dsk) * (1.f / 4096.f));
    sc = __uint_as_float(__float_as_uint(fminf(fmaxf(sc, 1e-30f), 1e30f)) & 0x7f800000u);
    inv_sc = rcpf_(sc);
    if (lane == 0) sts64f(tbl + TBL_SC + 8, dt * sc, dsk * inv_sc);
    dl = dt * 1.4426950408889634f;
  }
  const int tq = lane & 3;
  const uint32_t st0 = stg + lane * KREC + (((lane >> 2) & 1) << 4), st1 = st0 ^ 16;
  const int mat = lane >> 3, rowi = lane & 7;
  const uint32_t ld_base = stg + (4 * (mat & 1) + (rowi >> 1)) * KREC + ((((mat >> 1) * 2 + (rowi & 1)) << 4) ^ ((mat & 1) << 4));
  float acc[24];
#pragma unroll
  for (int i = 0; i < 24; i++) acc[i] = 0.f;
#pragma unroll 1
  for (int it = 0; it < 2 * nw; it++) {
    const uint32_t sel = (it & 1) ? 0x3244u : 0x1044u;
    float v[6];
#pragma unroll
    for (int i = 0; i < 6; i++) { v[i] = __uint_as_float(__byte_perm(cur[i], 0, sel)); if (it == 1) cur[i] = nxt[i]; }
    const float rho2 = v[0] * dl, phi = v[1] * dt;
    const cf bb = {v[2] * inv_sc, v[3] * -inv_sc}, cc = {v[4], -v[5]};
    cf X[8];
    X[0] = cmul(cc, bb);
    const cf z1 = zpow(rho2, -phi, 1.f), z8 = zpow(rho2, phi, 8.f), z64 = zpow(rho2, phi, 64.f);
    const cf y1 = zpow(rho2, -phi, 256.f), y4 = zpow(rho2, -phi, 1024.f);
    const cf z2 = cmul(z1, z1);
    X[1] = cmul(X[0], z1);
#pragma unroll
    for (int j = 2; j < 8; j++) X[j] = cmul(X[j - 2], z2);
    const cf a0 = cmul(X[0], y1), a1 = cmul(X[2], y1), a2 = cmul(X[4], y1), a3 = cmul(X[6], y1);
    const cf a4 = cmul(a0, y1), a5 = cmul(a2, y1);
    const cf a6 = cmul(a4, y1), a7 = cmul(a5, y1);
    const cf v0 = cmul(X[0], y4), v1 = cmul(a0, y4), v2 = cmul(a4, y4), v3 = cmul(a6, y4), v4 = cmul(v0, y4);
    const cf f2 = cmul(z8, z8), f3 = cmul(f2, z8), f4 = cmul(f2, f2), f5 = cmul(f3, f2), f6 = cmul(f4, f2), f7 = cmul(f4, f3);
    const cf z128 = cmul(z64, z64), z192 = cmul(z128, z64);
    __syncwarp();
    sts128(st0, pack_h2(X[0].x, X[1].x), pack_h2(X[2].x, X[3].x), pack_h2(X[4].x, X[5].x), pack_h2(X[6].x, X[7].x));
    sts128(st1, pack_h2(X[0].y, X[1].y), pack_h2(X[2].y, X[3].y), pack_h2(X[4].y, X[5].y), pack_h2(X[6].y, X[7].y));
    sts128(st0 + 32, pack_h2(a0.x, a1.x), pack_h2(a2.x, a3.x), pack_h2(a4.x, a5.x), pack_h2(a6.x, a7.x));
    sts128(st1 + 32, pack_h2(a0.y, a1.y), pack_h2(a2.y, a3.y), pack_h2(a4.y, a5.y), pack_h2(a6.y, a7.y));
    sts128(st0 + 64, pack_h2(v0.x, v1.x), pack_h2(v2.x, v3.x), pack_h2(v4.x, z64.x), pack_h2(z128.x, z192.x));
    sts128(st1 + 64, pack_h2(v0.y, v1.y), pack_h2(v2.y, v3.y), pack_h2(v4.y, z64.y), pack_h2(z128.y, z192.y));
    sts128(st0 + 96, pack_h2(1.f, z8.x), pack_h2(f2.x, f3.x), pack_h2(f4.x, f5.x), pack_h2(f6.x, f7.x));
    sts128(st1 + 96, pack_h2(0.f, z8.y), pack_h2(f2.y, f3.y), pack_h2(f4.y, f5.y), pack_h2(f6.y, f7.y));
    __syncwarp();
    uint32_t B[4][8];
#pragma unroll
    for (int ks = 0; ks < 4; ks++) {
      ldsm4t(ld_base + ks * 8 * KREC + 64, B[ks][4], B[ks][5], B[ks][6], B[ks][7]);
      ldsm4t(ld_base + ks * 8 * KREC, B[ks][0], B[ks][1], B[ks][2], B[ks][3]);
    }
#pragma unroll
    for (int ks = 0; ks < 4; ks++) {
      const uint32_t al = B[ks][6], ah = B[ks][7];
      uint32_t rl[3], rh[3];
#pragma unroll
      for (int j = 0; j < 3; j++) {
        rl[j] = __shfl_sync(0xffffffffu, B[ks][4], 20 + 4 * j + tq);
        rh[j] = __shfl_sync(0xffffffffu, B[ks][5], 20 + 4 * j + tq);
      }
      const uint32_t alr = rot90(al), ahr = rot90(ah);
      const uint32_t e1 = hprod(al, alr, rl[0]), e3 = hprod(ah, ahr, rh[0]);
      const uint32_t c0 = hprod(al, alr, rl[1]), c2 = hprod(ah, ahr, rh[1]);
      const uint32_t c1 = hprod(al, alr, rl[2]), c3 = hprod(ah, ahr, rh[2]);
      mma_f16(acc + 0, al, e1, ah, e3, B[ks][0], B[ks][1]);
      mma_f16(acc + 4, al, e1, ah, e3, B[ks][2], B[ks][3]);
      mma_f16(acc + 8, al, e1, ah, e3, B[ks][4], B[ks][5]);
      mma_f16(acc + 12, c0, c1, c2, c3, B[ks][0], B[ks][1]);
      mma_f16(acc + 16, c0, c1, c2, c3, B[ks][2], B[ks][3]);
      mma_f16(acc + 20, c0, c1, c2, c3, B[ks][4], B[ks][5]);
    }
  }
  __syncwarp();
#pragma unroll
  for (int q = 0; q < 4; q++)
#pragma unroll
    for (int nt = 0; nt < 3; nt++) {
      const float* a = acc + 12 * (q >> 1) + 4 * nt + 2 * (q & 1);
      sts64f(stg + (q * 3 + nt) * 256 + lane * 8, a[0], a[1]);
    }
}

__device__ __forceinline__ void tput(uint32_t tbl, int X, uint32_t h) {
  sts16(tbl + 2 * (1296 - X), (uint16_t)h);
  sts16(tbl + TBL_C1 + 2 * (1297 - X), (uint16_t)h);
}
__device__ __forceinline__ void ktab_build(uint32_t src, bool four, int q, uint32_t tbl, int lane) {
  const int tq = lane & 3, r = 8 * q + (lane >> 2);
  float v[6];
  src += q * 768 + lane * 8;
#pragma unroll
  for (int nt = 0; nt < 3; nt++) {
    const float2 a = lds64f(src + nt * 256), c = lds64f(src + nt * 256 + KSTG);
    v[2 * nt] = a.x + c.x; v[2 * nt + 1] = a.y + c.y;
  }
  if (four) {
#pragma unroll
    for (int nt = 0; nt < 3; nt++) {
      const float2 a = lds64f(src + nt * 256 + 2 * KSTG), c = lds64f(src + nt * 256 + 3 * KSTG);
      v[2 * nt] += a.x + c.x; v[2 * nt + 1] += a.y + c.y;
    }
  }
  const bool first = (r == 0);
  if (first && tq == 0) { v[0] += lds32f(tbl + TBL_SC + 12); sts32f(tbl + TBL_SC, v[4]); }
  const uint32_t h0 = pack_h2(v[0], v[1]), h1 = pack_h2(v[2], v[3]), h2 = pack_h2(v[4], v[5]);
  tput(tbl, 64 + 8 * r + 2 * tq, h0);
  tput(tbl, 65 + 8 * r + 2 * tq, h0 >> 16);
  const bool lo = tq < 2;
  const int Xd = 320 + 8 * r + 4 * tq, k2 = 32 * (tq - 2) + r;
  tput(tbl, lo ? Xd + 2 : 720 + k2, h1 >> 16);
  const bool sp = first && tq == 2;
  const int Xa = lo ? Xd : (sp ? 576 : 911 + k2);
  tput(tbl, Xa, h1);
  if (lo || sp) {
    tput(tbl, Xa + 1, h1);
    if (Xa != 320) tput(tbl, Xa - 1, h1);
  }
  if (sp) { tput(tbl, 578, h1); tput(tbl, 1295, h2); }
  if (lo) {
    const int X3 = ((r & 1) ? 1104 : 1231) + 32 * tq + (r >> 1);
    tput(tbl, X3 == 1231 ? 975 : X3, h2);
    tput(tbl, X3 + 16, h2 >> 16);
  }
}

__device__ __forceinline__ void sig_windows(uint32_t sig, int t) {
  uint32_t U[20];
#pragma unroll
  for (int c = 0; c < 5; c++) {
    const int kap = 2 * t - 3 + c + 72;
    const uint4 v = lds128(sig + SIG_U + (kap & 7) * U_LBO + (kap >> 3) * 16);
    U[4 * c] = v.x; U[4 * c + 1] = v.y; U[4 * c + 2] = v.z; U[4 * c + 3] = v.w;
  }
  uint32_t O[19], A2[17], A4[17], V2[8], V5[8];
#pragma unroll
  for (int i = 3; i < 19; i++) O[i] = __byte_perm(U[i - 1], U[i], 0x5432);
#pragma unroll
  for (int i = 3; i < 17; i++) A2[i] = hadd2u(U[i], O[i]);
#pragma unroll
  for (int i = 4; i < 17; i++) A4[i] = hadd2u(A2[i], A2[i - 1]);
#pragma unroll
  for (int k = 0; k < 8; k++) { V2[k] = hadd2u(O[11 + k], U[10 + k]); V5[k] = hadd2u(A4[9 + k], U[7 + k]); }
#pragma unroll
  for (int h = 0; h < 2; h++) {
    sts128(sig + SIG_V3 + t * 32 + h * 16, hadd2u(V2[4 * h], O[10 + 4 * h]), hadd2u(V2[4 * h + 1], O[11 + 4 * h]),
           hadd2u(V2[4 * h + 2], O[12 + 4 * h]), hadd2u(V2[4 * h + 3], O[13 + 4 * h]));
    sts128(sig + SIG_V5 + t * 32 + h * 16, V5[4 * h], V5[4 * h + 1], V5[4 * h + 2], V5[4 * h + 3]);
  }
  if (t < 64) {
    uint32_t V7[8], V9[8];
#pragma unroll
    for (int k = 0; k < 8; k++) {
      V7[k] = hadd2u(V5[k], hadd2u(O[10 + k], O[7 + k]));
      V9[k] = hadd2u(hadd2u(A4[6 + k], A4[4 + k]), U[2 + k]);
    }
#pragma unroll
    for (int h = 0; h < 2; h++) {
      sts128(sig + SIG_V7 + h * 1024 + t * 16, V7[4 * h], V7[4 * h + 1], V7[4 * h + 2], V7[4 * h + 3]);
      sts128(sig + SIG_V9 + h * 1024 + t * 16, V9[4 * h], V9[4 * h + 1], V9[4 * h + 2], V9[4 * h + 3]);
      sts128(sig + SIG_V2 + h * 1024 + t * 16, V2[4 * h], V2[4 * h + 1], V2[4 * h + 2], V2[4 * h + 3]);
    }
  }
}

__device__ __forceinline__ void conv_channel(uint32_t tbl, uint32_t sig, uint32_t y2b, uint32_t y3b, float k1024,
                                             int w, int lane, int barid, float* res) {
  const int g = lane >> 2, tq = lane & 3;
  const uint32_t tb = tbl + ((g & 1) ? TBL_C1 + 2 : 0) + 2 * (1296 - (g - 2 * tq)) - 32 * w + 112;
  float a2[12], a3[8];
#pragma unroll
  for (int i = 0; i < 16; i++) res[i] = 0.f;
#pragma unroll
  for (int i = 0; i < 12; i++) a2[i] = 0.f;
#pragma unroll
  for (int q = 0; q < 4; q++) {
    const float2 f = h2f(lds32(sig + SIG_V2 + (q >> 1) * 1024 + (16 * w + 8 * (q & 1) + g) * 16 + tq * 4));
    a3[2 * q] = k1024 * f.x;
    a3[2 * q + 1] = k1024 * f.y;
  }
  const uint64_t dU = mkdesc(sig + SIG_U, U_LBO, 128, 0);
  const uint64_t dV = mkdesc(sig, 128, 1024, 0);
  fence_regs<16>(res); fence_regs<12>(a2); fence_regs<8>(a3);
  constexpr int LB = 2 * U_LBO / 16;
  uint32_t cd = lds32(tb - 128), c2 = 0, c3 = 0;
#pragma unroll
  for (int it = 0; it < 8; it++) {
    const uint32_t td = tb - 128 - 128 * it;
    const uint32_t t2 = tb - 1440 - 384 * (it >> 2) - 64 * (it & 3);
    const uint32_t t3 = tb - 2208 - 256 * (it >> 2) - 32 * (it & 3);
    const uint64_t dd = dU + (9 - it);
    const uint64_t d2 = dV + ((SIG_V3 + 768) / 16 + 256 * (it >> 2) - 32 * (it & 1) - 64 * ((it >> 1) & 1));
    const uint64_t d3 = dV + ((SIG_V7 + 768) / 16 + 128 * (it >> 2) - 16 * (it & 3));
    uint32_t Rd[9], R2[5], R3[3];
    Rd[0] = cd;
    R2[0] = (it & 3) ? c2 : lds32(t2);
    R3[0] = (it & 3) ? c3 : lds32(t3);
#pragma unroll
    for (int i = 1; i < 5; i++) Rd[i] = lds32(td - 16 * i);
#pragma unroll
    for (int i = 1; i < 3; i++) { R2[i] = lds32(t2 - 16 * i); R3[i] = lds32(t3 - 16 * i); }
    wg_fence();
    wg_rs_f16_n32k(res, Rd[1], Rd[2], Rd[0], Rd[1], dd + 3 * LB, 1);
    wg_rs_f16_n24t(a2, R2[1], R2[2], R2[0], R2[1], d2, 1);
    wg_rs_f16_n32k(res, Rd[3], Rd[4], Rd[2], Rd[3], dd + 2 * LB, 1);
    wg_rs_f16_n16t(a3, R3[1], R3[2], R3[0], R3[1], d3, 1);
    wg_commit();
    wg_wait<1>();
#pragma unroll
    for (int i = 5; i < 9; i++) Rd[i] = lds32(td - 16 * i);
#pragma unroll
    for (int i = 3; i < 5; i++) R2[i] = lds32(t2 - 16 * i);
    wg_fence();
    wg_rs_f16_n32k(res, Rd[5], Rd[6], Rd[4], Rd[5], dd + LB, 1);
    wg_rs_f16_n24t(a2, R2[3], R2[4], R2[2], R2[3], d2 - 16, 1);
    wg_rs_f16_n32k(res, Rd[7], Rd[8], Rd[6], Rd[7], dd, 1);
    wg_commit();
    wg_wait<1>();
    cd = Rd[8]; c2 = R2[4]; c3 = R3[2];
  }
  {
    uint32_t Rd[11];
    Rd[0] = cd;
#pragma unroll
    for (int i = 1; i < 11; i++) Rd[i] = lds32(tb - 128 - 1024 - 16 * i);
    wg_fence();
#pragma unroll
    for (int i = 0; i < 4; i++) wg_rs_f16_n32k(res, Rd[2 * i + 1], Rd[2 * i + 2], Rd[2 * i], Rd[2 * i + 1], dU + ((3 - i) * LB + 1), 1);
    wg_rs_f16_n32k(res, Rd[9], Rd[10], Rd[8], Rd[9], dU + 3 * LB, 1);
    wg_commit();
  }
  wg_wait<1>();
  fence_regs<12>(a2); fence_regs<8>(a3);
  bar_sync(barid, 128);
  {
    const uint32_t o2 = y2b + (136 * w + 8 * g + 2 * tq) * 4, o3 = y3b + (272 * w + 16 * g + 2 * tq) * 4;
#pragma unroll
    for (int q = 0; q < 6; q++) sts64f(o2 + (544 * (q >> 1) + 64 * (q & 1)) * 4, a2[2 * q], a2[2 * q + 1]);
#pragma unroll
    for (int q = 0; q < 4; q++) sts64f(o3 + (8 * (q >> 1) + 136 * (q & 1)) * 4, a3[2 * q], a3[2 * q + 1]);
  }
  bar_sync(barid, 128);
  const uint32_t go = (136 * tq + 16 * w + g) * 4;
  float ex[12];
#pragma unroll
  for (int i = 0; i < 12; i++) {
    const int o = 544 * (i >> 2) + 64 * (i & 1) + 8 * ((i >> 1) & 1);
    ex[i] = lds32f(y2b + go + o * 4);
    if (i >= 4) ex[i] += lds32f(y3b + go + (o - 544) * 4);
  }
  wg_wait<0>();
  fence_regs<16>(res);
#pragma unroll
  for (int i = 0; i < 12; i++) res[4 + i] += ex[i];
}

__device__ __forceinline__ void red16x2(float& a, float& c) {
#pragma unroll
  for (int o = 1; o < 16; o <<= 1) { a += __shfl_xor_sync(0xffffffffu, a, o); c += __shfl_xor_sync(0xffffffffu, c, o); }
}
__device__ __forceinline__ void ln_rows(uint32_t* u, int row, uint32_t stg_row, int lane) {
  const int j = lane & 15;
  const float piv = __shfl_sync(0xffffffffu, bf_lo(u[0]), lane & 16);
  float s0 = 0.f, s1 = 0.f, q0 = 0.f, q1 = 0.f;
#pragma unroll
  for (int i = 0; i < 14; i++) {
    const float a = bf_lo(u[i]) - piv, c = bf_hi(u[i]) - piv;
    s0 += a; s1 += c; q0 = fmaf(a, a, q0); q1 = fmaf(c, c, q1);
  }
  float s = s0 + s1, q = q0 + q1;
  red16x2(s, q);
  s *= (1.f / D_); q *= (1.f / D_);
  const __nv_bfloat16 m1b = __float2bfloat16_rn(s + piv);
  const __nv_bfloat162 m1v = __halves2bfloat162(m1b, m1b);
  const float den = rbf(sqrtf_(rbf(rbf(fmaxf(fmaf(-s, s, q), 0.f)) + 1e-5f)));
  const float rden = rcpf_(den);
  s0 = s1 = q0 = q1 = 0.f;
#pragma unroll
  for (int i = 0; i < 14; i++) {
    const __nv_bfloat162 cv = __hsub2(*reinterpret_cast<__nv_bfloat162*>(&u[i]), m1v);
    const uint32_t c = *reinterpret_cast<const uint32_t*>(&cv);
    const uint32_t n = pack_bf2(bf_lo(c) * rden, bf_hi(c) * rden);
    const float a = bf_lo(n), e = bf_hi(n);
    s0 += a; s1 += e; q0 = fmaf(a, a, q0); q1 = fmaf(e, e, q1);
    u[i] = pack_h2(a, e);
  }
#pragma unroll
  for (int i = 0; i < 7; i++)
    asm volatile("st.shared.v2.b32 [%0], {%1,%2};" ::"r"(stg_row + (j + 16 * i) * 8), "r"(u[2 * i]), "r"(u[2 * i + 1]) : "memory");
  s = s0 + s1; q = q0 + q1;
  red16x2(s, q);
  s *= (1.f / D_); q *= (1.f / D_);
  const float den2 = rbf(sqrtf_(rbf(rbf(fmaxf(fmaf(-s, s, q), 0.f)) + 1e-5f)));
  if (j == 0) {
    const float ir = den * den2, mu = fmaf(rbf(s), den, __bfloat162float(m1b));
    const float ih = rbf(ir), mh = rbf(mu), ml = rbf(mu - mh);
    g_ax[row] = make_uint4(pack_bf2(ih, ir - ih), pack_bf2(mh, mh), pack_bf2(ml, ml), pack_bf2(mh, mu - mh - ml));
    g_r[row] = rcpf_(ir);
  }
}

__device__ __forceinline__ void recv_part(const uint4* src, float* pre) {
  uint4 v[4];
#pragma unroll 1
  for (int it = 0; it < SPIN_MAX; it++) {
#pragma unroll
    for (int q = 0; q < 4; q++) v[q] = ld_relaxed4(src + q * 256);
    uint32_t m = 0;
#pragma unroll
    for (int q = 0; q < 4; q++) m = umax3(umax3(m, v[q].x, v[q].y), v[q].z, v[q].w);
    if (m != 0xffffffffu) break;
    __nanosleep(40);
  }
#pragma unroll
  for (int q = 0; q < 4; q++) {
    const uint32_t u[4] = {v[q].x, v[q].y, v[q].z, v[q].w};
#pragma unroll
    for (int k = 0; k < 4; k++) { pre[8 * q + 2 * k] += bf_lo(u[k]); pre[8 * q + 2 * k + 1] += bf_hi(u[k]); }
  }
  fence_regs<32>(pre);
}
__device__ __forceinline__ void send_part(uint4* dst, const float* a) {
#pragma unroll
  for (int q = 0; q < 4; q++)
    st_relaxed4(dst + q * 256, pack_bf2(a[8 * q], a[8 * q + 1]), pack_bf2(a[8 * q + 2], a[8 * q + 3]),
                pack_bf2(a[8 * q + 4], a[8 * q + 5]), pack_bf2(a[8 * q + 6], a[8 * q + 7]));
}
__device__ __forceinline__ bool last_release(uint32_t cnt) {
  unsigned old;
  asm volatile("atom.acq_rel.cta.shared.add.u32 %0, [%1], 1;" : "=r"(old) : "r"(cnt) : "memory");
  return old == 7;
}
__device__ __forceinline__ int mod7(int v) { return v >= 7 ? v - 7 : v; }

#define IDS const int tid = rd_tid(), lane = tid & 31, t = tid & 127, wg = tid >> 7, w = (tid >> 5) & 3; \
            (void)lane; (void)t; (void)wg; (void)w;

__global__ void __launch_bounds__(384, 1)
fused_kernel(const __grid_constant__ CUtensorMap tm_x, const __grid_constant__ CUtensorMap tm_w1,
             const __grid_constant__ CUtensorMap tm_w2, const __grid_constant__ CUtensorMap tm_out, const Params p) {
  extern __shared__ __align__(1024) uint8_t smem_raw[];
  const uint32_t sb = smem_u32(smem_raw);
  const uint32_t ms = sb + OFF_M;
  const uint32_t bar0 = ms + M_BAR;
  const int b = blockIdx.x;
  const bool is_ssm = b >= NMLP;
  const int G = b / NRK, rk = b - G * NRK;
  const int kc0 = (G + rk) % 7;
  TSTAMP(0);
  {
    IDS
    if (tid == 256) {
#pragma unroll 1
      for (int i = 0; i < 16; i++) { mbar_init(bar0 + 8 * i, 1); asm volatile("st.shared.b32 [%0], 0;" ::"r"(ms + M_REL + 4 * i) : "memory"); }
      asm volatile("fence.mbarrier_init.release.cluster;" ::: "memory");
      fence_async();
      if (!is_ssm) {
#pragma unroll 1
        for (int s = 0; s < 3; s++) {
          const int kc = mod7(kc0 + s);
          mbar_expect(bar0 + 8 * s, 49152);
          tma_2d(sb + OFF_X + s * 16384, &tm_x, 64 * kc, 128 * G, bar0 + 8 * s);
          tma_3d(sb + OFF_W + s * 32768, &tm_w1, 0, 64 * kc, 4 * rk, bar0 + 8 * s);
        }
      }
      asm volatile("st.shared.b32 [%0], %1;" ::"r"(ms + M_EP), "r"(*(volatile unsigned*)&g_epoch) : "memory");
    }
    if (is_ssm || wg < 2 || b < 104) {
      const int d = is_ssm ? 2 * (112 + 3 * (b - NMLP) + wg) + (w >> 1) : (wg < 2 ? 2 * b + wg : 344 + b);
      const uint32_t stg = is_ssm ? sb + S_WORK + wg * S_WGB + w * KSTG : sb + (wg < 2 ? OFF_A + 4 * wg * KSTG : OFF_B) + w * KSTG;
      const uint32_t tbl = is_ssm ? sb + (4 * wg + (w >> 1)) * TBL : sb + OFF_T + wg * TBL;
      kgen_warp(p, d, is_ssm ? 2 * (w & 1) : w, is_ssm ? 2 : 1, stg, tbl, is_ssm ? t & 63 : t, is_ssm ? 64 : 128, lane);
    }
  }
  TSTAMP(1);
  __syncthreads();

  if (is_ssm || __shfl_sync(0xffffffffu, rd_tid() >> 7, 0) == 2) {
    asm volatile("setmaxnreg.dec.sync.aligned.u32 104;");
    {
      IDS
      if (!is_ssm) { sts128(sb + OFF_FF + t * 16, ~0u, ~0u, ~0u, ~0u); }
      const int nc = is_ssm ? 2 : (b < 104 ? 3 : 2);
#pragma unroll 1
      for (int c = nc - 1; c >= 0; c--) {
        const uint32_t src = is_ssm ? sb + S_WORK + wg * S_WGB + 2 * c * KSTG : sb + (c < 2 ? OFF_A + 4 * c * KSTG : OFF_B);
        ktab_build(src, !is_ssm, w, (is_ssm ? sb + 4 * wg * TBL : sb + OFF_T) + c * TBL, lane);
      }
      fence_async();
      bar_sync(4 + wg, 128);
    }
    TSTAMP(2);
    if (!is_ssm) {
      IDS
      uint32_t u[14], un[14];
      const int rl0 = 4 * w + (lane >> 4);
      {
        const uint2* xr = (const uint2*)(p.x + (size_t)(16 * b + rl0) * D_) + (lane & 15);
#pragma unroll
        for (int i = 0; i < 7; i++) { const uint2 v = __ldg(xr + 16 * i); un[2 * i] = v.x; un[2 * i + 1] = v.y; }
      }
      if (t < 9) {
        if (t < 8) bulk_s2g((uint8_t*)(g_s2 + ((size_t)G * 224 + 32 * rk) * 32) + t * 2048, sb + OFF_FF, 2048);
        else if (b < 104) bulk_s2g(g_tbl + b * (TBL / 16), sb + OFF_T + 2 * TBL, TBL);
        bulk_commit();
        if (t == 0)
          asm volatile("cp.async.bulk.prefetch.L2.global [%0], %1;" ::"l"(p.w2 + (size_t)(256 * rk + 16 * G) * D_), "r"(16 * D_ * 2) : "memory");
      }
      {
        const uint4* wr = (const uint4*)(p.w1 + (size_t)(t >> 1) * F_ + 16 * b) + (t & 1);
        float cs[8];
#pragma unroll
        for (int k = 0; k < 8; k++) cs[k] = 0.f;
        uint4 wv[7];
#pragma unroll
        for (int i = 0; i < 7; i++) wv[i] = __ldg(wr + (size_t)i * 64 * (F_ / 8));
#pragma unroll
        for (int i = 0; i < 7; i++) {
          const uint32_t uu[4] = {wv[i].x, wv[i].y, wv[i].z, wv[i].w};
#pragma unroll
          for (int k = 0; k < 4; k++) { cs[2 * k] += bf_lo(uu[k]); cs[2 * k + 1] += bf_hi(uu[k]); }
        }
#pragma unroll
        for (int st = 0; st < 3; st++) {
          const int n = 4 >> st;
          const bool up = (lane >> (3 - st)) & 1;
#pragma unroll
          for (int k = 0; k < n; k++) {
            const float give = up ? cs[k] : cs[k + n], keep = up ? cs[k + n] : cs[k];
            cs[k] = keep + __shfl_xor_sync(0xffffffffu, give, 8 >> st);
          }
        }
        cs[0] += __shfl_xor_sync(0xffffffffu, cs[0], 16);
        if (lane < 16) sts32f(ms + M_CSR + (w * 16 + (lane & 1) * 8 + (lane >> 1)) * 4, cs[0]);
      }
      const float b1v = t < 16 ? __bfloat162float(p.b1[16 * b + t]) : 0.f;
      TSTAMP(10);
      const int nit = b < 16 ? 4 : 2;
#pragma unroll 1
      for (int i = 0; i < nit; i++) {
        const int rb = b + NMLP * (i >> 1), rl = rl0 + 2 * (i & 1);
#pragma unroll
        for (int k = 0; k < 14; k++) u[k] = un[k];
        if (i + 1 < nit) {
          const uint2* xr = (const uint2*)(p.x + (size_t)(16 * (b + NMLP * ((i + 1) >> 1)) + rl0 + 2 * ((i + 1) & 1)) * D_) + (lane & 15);
#pragma unroll
          for (int k = 0; k < 7; k++) { const uint2 v = __ldg(xr + 16 * k); un[2 * k] = v.x; un[2 * k + 1] = v.y; }
        }
        ln_rows(u, 16 * rb + rl, sb + OFF_B + rl * 912, lane);
        if (i & 1) {
          bar_sync(6, 128);
          const uint32_t la = sb + OFF_B + (lane & 15) * 912 + (lane >> 4) * 16 + w * 224;
          uint2* dst = (uint2*)(g_xnT + (size_t)rb * 896) + lane + w * 448;
#pragma unroll
          for (int k = 0; k < 7; k++) {
            uint32_t r0, r1, r2, r3;
            ldsm4t(la + k * 32, r0, r1, r2, r3);
            dst[k * 64] = make_uint2(r0, r1);
            dst[k * 64 + 32] = make_uint2(r2, r3);
          }
          if (i == 1 && t < 16) {
            const uint32_t a = ms + M_CSR + t * 4;
            const float c = -0.5f * ((lds32f(a) + lds32f(a + 64)) + (lds32f(a + 128) + lds32f(a + 192)));
            const float ch = rbf(c), cl = rbf(c - ch);
            const uint32_t hl = pack_bf2(ch, cl);
            g_bx[16 * b + t] = make_uint4(pack_bf2(0.5f * b1v, 0.5f * b1v), hl, hl, pack_bf2(c - ch - cl, ch));
            bulk_wait0();
          }
          bar_sync(6, 128);
        }
      }
      TSTAMP(11);
    }
    {
      IDS
      if (tid == 256) red_release(&g_cntA);
      if (!is_ssm && t >= 32 && t < 80) {
        bulk_s2g((uint8_t*)(g_part + (size_t)(G * 7 + rk) * 6 * 1024) + (t - 32) * 2048, sb + OFF_FF, 2048);
        bulk_commit();
      }
      TSTAMP(3);
      if (t == 0) {
        const unsigned epoch = lds32(ms + M_EP);
        wait_count(&g_cntA, (epoch + 1) * NCTA);
        if (b == 0) *(volatile unsigned*)&g_epoch = epoch + 1;
        asm volatile("fence.proxy.async;" ::: "memory");
        if (!is_ssm) {
          mbar_expect(bar0 + 8 * 15, 2048 + 4096 + 512);
          bulk_g2s(sb + OFF_B + B_AX, g_ax + 128 * G, 2048, bar0 + 8 * 15);
          bulk_g2s(sb + OFF_B + B_BX, g_bx + 256 * rk, 4096, bar0 + 8 * 15);
          bulk_g2s(sb + OFF_B + B_R, g_r + 128 * G, 512, bar0 + 8 * 15);
        } else if (b < NMLP + 12 || wg < 2) {
          const int j = (b < NMLP + 12 ? 3 * (b - NMLP) : 2 * (b - NMLP) + 12) + wg;
          mbar_expect(bar0 + 8 * wg, 2 * TBL);
          bulk_g2s(sb + (4 * wg + 2) * TBL, g_tbl + 2 * j * (TBL / 16), 2 * TBL, bar0 + 8 * wg);
        }
      }
      bar_sync(4 + wg, 128);
    }
    TSTAMP(5);
#pragma unroll 1
    for (int pi = 0; pi < 2; pi++) {
      {
        IDS
        if (pi == 1 && (!is_ssm || (b >= NMLP + 12 && wg == 2))) break;
        const int pair = !is_ssm ? b : (pi == 0 ? 112 + 3 * (b - NMLP) : (b < NMLP + 12 ? 172 + 3 * (b - NMLP) : 184 + 2 * (b - NMLP))) + wg;
        const uint32_t work = is_ssm ? sb + S_WORK + wg * S_WGB : sb + OFF_A;
        const uint4* src = g_xnT + ((size_t)t * 448 + 2 * pair) * 2;
        const uint4 l0 = ld_relaxed4(src), h0 = ld_relaxed4(src + 1), l1 = ld_relaxed4(src + 2), h1 = ld_relaxed4(src + 3);
        const uint32_t z = work + SIG_V3 - 1024 + (t >> 6) * 4096 + (t & 63) * 16;
        sts128(z, 0u, 0u, 0u, 0u); sts128(z + SIG, 0u, 0u, 0u, 0u);
        if (t < 72) {
          const uint32_t zu = work + SIG_U + (t & 7) * U_LBO + (t >> 3) * 16;
          sts128(zu, 0u, 0u, 0u, 0u); sts128(zu + SIG, 0u, 0u, 0u, 0u);
        }
        const uint32_t a = work + SIG_U + (2 * (t & 3)) * U_LBO + ((t >> 2) + 9) * 16;
        sts128(a, l0.x, l0.z, h0.x, h0.z);
        sts128(a + U_LBO, l0.y, l0.w, h0.y, h0.w);
        sts128(a + SIG, l1.x, l1.z, h1.x, h1.z);
        sts128(a + SIG + U_LBO, l1.y, l1.w, h1.y, h1.w);
        bar_sync(4 + wg, 128);
#pragma unroll 1
        for (int k = w; k < 6; k += 4) sig_windows(work + (k & 1) * SIG, (k >> 1) * 32 + lane);
        fence_async();
        if (!is_ssm) {
          if (t >= 32 && t < 80) bulk_wait0();
          bar_sync(6, 128);
          if (t == 0) red_release(&g_cntB[G * 32]);
        } else if (pi == 1) {
          mbar_wait(bar0 + 8 * wg, 0);
        }
        TSTAMP(6);
        bar_sync(is_ssm ? 4 + wg : 3, is_ssm ? 128 : 384);
        TSTAMP(7);
      }
      uint32_t keep[8];
      float res[16];
#pragma unroll 1
      for (int c = 0; c < 2; c++) {
        IDS
        const int wgu = __shfl_sync(0xffffffffu, wg, 0);
        const uint32_t work = is_ssm ? sb + S_WORK + wgu * S_WGB : sb + OFF_A;
        const uint32_t tbl = (is_ssm ? sb + (4 * wgu + 2 * pi) * TBL : sb + OFF_T) + c * TBL;
        const uint4 sc = lds128(tbl + TBL_SC);
        conv_channel(tbl, work + c * SIG, is_ssm ? work + 2 * SIG + Y3B : sb + OFF_B, work + 2 * SIG, __uint_as_float(sc.x), w, lane, 4 + wgu, res);
        const float os = __uint_as_float(sc.z);
        if (c == 0) {
#pragma unroll
          for (int i = 0; i < 8; i++) keep[i] = pack_bf2(res[2 * i] * os, res[2 * i + 1] * os);
        } else {
          const int pair = !is_ssm ? b : (pi == 0 ? 112 + 3 * (b - NMLP) : (b < NMLP + 12 ? 172 + 3 * (b - NMLP) : 184 + 2 * (b - NMLP))) + wg;
          uint4* dst = g_s2 + ((size_t)(lane & 3) * 224 + pair) * 32 + w * 8 + (lane >> 2);
#pragma unroll
          for (int nt = 0; nt < 4; nt++) {
            const uint32_t n0 = pack_bf2(res[4 * nt] * os, res[4 * nt + 1] * os), n1 = pack_bf2(res[4 * nt + 2] * os, res[4 * nt + 3] * os);
            st_relaxed4(dst + nt * 4 * 224 * 32, __byte_perm(keep[2 * nt], n0, 0x5410), __byte_perm(keep[2 * nt + 1], n1, 0x5410),
                        __byte_perm(keep[2 * nt], n0, 0x7632), __byte_perm(keep[2 * nt + 1], n1, 0x7632));
          }
        }
      }
      TSTAMP(8 + pi);
    }
  } else {
    asm volatile("setmaxnreg.inc.sync.aligned.u32 200;");
    uint32_t H[64];
    {
      float acc[128];
      float p0, q0, p1, q1;
      {
        IDS
        const int wgu = __shfl_sync(0xffffffffu, wg, 0);
        int sl = 0;
#pragma unroll 1
        for (int s = 0; s < 7; s++) {
          mbar_wait(bar0 + 8 * s, 0);
          const uint64_t da = mkdesc(sb + OFF_X + sl * 16384 + wgu * 8192, 16, 1024, 1);
          const uint64_t db = mkdesc(sb + OFF_W + sl * 32768, 8192, 1024, 1);
          wg_fence();
#pragma unroll
          for (int k = 0; k < 4; k++) wg_ss_bf16_n256(acc, da + 2 * k, db + 128 * k, (s | k) != 0);
          wg_commit();
          wg_wait<1>();
          const int pl = sl == 0 ? 2 : sl - 1;
          sl = sl == 2 ? 0 : sl + 1;
          if (s > 0 && lane == 0 && last_release(ms + M_REL + 4 * s)) {
            const uint32_t bx = bar0 + 8 * (s < 5 ? s + 2 : 14);
            mbar_expect(bar0 + 8 * (s + 2), s < 5 ? 49152 : 32768);
            if (s < 5) tma_3d(sb + OFF_W + pl * 32768, &tm_w1, 0, 64 * mod7(kc0 + s + 2), 4 * rk, bar0 + 8 * (s + 2));
            else tma_2d(sb + OFF_W + pl * 32768, &tm_w2, 64 * mod7(rk + s - 4), 256 * rk, bar0 + 8 * (s + 2));
            if (s == 6) mbar_expect(bx, 16384);
            if (s != 5) tma_2d(sb + OFF_X + pl * 16384, &tm_x, 64 * (s < 5 ? mod7(kc0 + s + 2) : rk), 128 * G, bx);
          }
        }
        TSTAMP(9);
        mbar_wait(bar0 + 8 * 15, 0);
        wg_fence();
        wg_ss_bf16_n256k(acc, mkdesc(sb + OFF_B + B_AX + wgu * 1024, 0, 128, 0), mkdesc(sb + OFF_B + B_BX, 0, 128, 0), 1);
        wg_commit();
        wg_wait<1>();
        if (lane == 0 && last_release(ms + M_REL + 4 * 7)) {
#pragma unroll 1
          for (int c = 2; c < 4; c++) {
            mbar_expect(bar0 + 8 * (7 + c), 32768);
            tma_2d(sb + (c - 2) * OFF_X, &tm_w2, 64 * mod7(rk + 1 + c), 256 * rk, bar0 + 8 * (7 + c));
          }
        }
        bar_arrive(3, 384);
        const float r0 = lds32f(sb + OFF_B + B_R + (16 * (tid >> 5) + (lane >> 2)) * 4);
        const float r1 = lds32f(sb + OFF_B + B_R + (16 * (tid >> 5) + (lane >> 2) + 8) * 4);
        p0 = 0.7978845608028654f * r0; q0 = 0.0356774081363001f * r0 * r0 * r0;
        p1 = 0.7978845608028654f * r1; q1 = 0.0356774081363001f * r1 * r1 * r1;
      }
      wg_wait<0>();
      fence_regs<128>(acc);
      TSTAMP(2);
      float hq[4];
#pragma unroll
      for (int i = 0; i < 64; i++) {
        const float pp = (i & 1) ? p1 : p0, qq = (i & 1) ? q1 : q0;
        const float a = acc[2 * i], c = acc[2 * i + 1];
        const float ta = tanhf_(a * fmaf(a * a, qq, pp)), tc = tanhf_(c * fmaf(c * c, qq, pp));
        if (i >= 2) H[i - 2] = pack_bf2v(hq[(i & 1) * 2], hq[(i & 1) * 2 + 1]);
        hq[(i & 1) * 2] = fmaf(a, ta, a); hq[(i & 1) * 2 + 1] = fmaf(c, tc, c);
      }
      H[62] = pack_bf2v(hq[0], hq[1]); H[63] = pack_bf2v(hq[2], hq[3]);
    }
    TSTAMP(3);
    float accA[32], accB[32], pre[32];
#pragma unroll
    for (int i = 0; i < 32; i++) pre[i] = 0.f;
    auto issue2 = [&](int c, float* acc) {
      const uint32_t base = sb + ((0x0213021u >> (4 * c)) & 3) * 32768;
      mbar_wait(bar0 + 8 * (7 + c), 0);
      const uint64_t db = mkdesc(base, 8192, 1024, 1);
      wg_fence();
#pragma unroll
      for (int k = 0; k < 16; k++) wg_rs_bf16_n64(acc, H[4 * k], H[4 * k + 1], H[4 * k + 2], H[4 * k + 3], db + 128 * k, k != 0);
      wg_commit();
    };
    auto process = [&](int s, float* acc) {
      wg_wait<1>();
      fence_regs<32>(acc);
      const int tid = rd_tid();
      if (s < 3 && (tid & 31) == 0 && last_release(ms + M_REL + 4 * (8 + s))) {
        mbar_expect(bar0 + 8 * (11 + s), 32768);
        tma_2d(sb + ((0x021u >> (4 * s)) & 3) * 32768, &tm_w2, 64 * mod7(mod7(rk + 5 + s)), 256 * rk, bar0 + 8 * (11 + s));
      }
      send_part(g_part + ((size_t)(G * 7 + mod7(rk + 1 + s)) * 6 + s) * 1024 + tid, acc);
      if (s >= 3) recv_part(g_part + ((size_t)b * 6 + s - 3) * 1024 + tid, pre);
      TSTAMP(10 + s);
    };
    issue2(0, accA);
    if ((rd_tid() & 31) == 0) wait_count(&g_cntB[G * 32], (lds32(ms + M_EP) + 1) * NRK);
    __syncwarp();
    TSTAMP(6);
#pragma unroll
    for (int s = 0; s < 6; s += 2) {
      issue2(s + 1, accB);
      process(s, accA);
      issue2(s + 2, accA);
      process(s + 1, accB);
    }
    TSTAMP(4);
    IDS
    const int g = lane >> 2, tq = lane & 3;
    uint2 sw[8];
    {
      const uint2* sp = (const uint2*)(g_s2 + ((size_t)G * 224 + 32 * rk + tq) * 32 + w * 8 + g) + wg;
#pragma unroll 1
      for (int it = 0; it < SPIN_MAX; it++) {
        uint32_t m = 0;
#pragma unroll
        for (int i = 0; i < 8; i++) { sw[i] = ld_relaxed2(sp + i * 4 * 64); m = umax3(m, sw[i].x, sw[i].y); }
        if (m != 0xffffffffu) break;
        __nanosleep(40);
      }
    }
    TSTAMP(5);
#pragma unroll 1
    for (int s = 3; s < 6; s++) {
      recv_part(g_part + ((size_t)b * 6 + s) * 1024 + tid, pre);
    }
    wg_wait<0>();
    fence_regs<32>(accA);
    TSTAMP(7);
    uint32_t b2w[8];
#pragma unroll
    for (int i = 0; i < 8; i++) b2w[i] = __ldg((const uint32_t*)(p.b2 + 64 * rk) + 4 * i + tq);
    mbar_wait(bar0 + 8 * 14, 0);
    const uint32_t xa = sb + OFF_X + 2 * 16384 + (16 * (tid >> 5) + (lane & 15)) * 128;
    uint32_t xw[16];
#pragma unroll
    for (int q = 0; q < 4; q++) ldsm4(xa + (((2 * q + (lane >> 4)) ^ (lane & 7)) << 4), xw[4 * q], xw[4 * q + 1], xw[4 * q + 2], xw[4 * q + 3]);
    const float r0 = 0.5f * lds32f(sb + OFF_B + B_R + (16 * (tid >> 5) + g) * 4);
    const float r1 = 0.5f * lds32f(sb + OFF_B + B_R + (16 * (tid >> 5) + g + 8) * 4);
#pragma unroll
    for (int k = 0; k < 16; k++) {
      const uint32_t sv = (k & 1) ? sw[k >> 1].y : sw[k >> 1].x;
      const float rr = (k & 1) ? r1 : r0;
      const float o0 = fmaf(pre[2 * k] + accA[2 * k], rr, bf_lo(b2w[k >> 1])), o1 = fmaf(pre[2 * k + 1] + accA[2 * k + 1], rr, bf_hi(b2w[k >> 1]));
      const float g0 = o0 * rcpf_(1.f + ex2f(o0 * -1.4426950408889634f)), g1 = o1 * rcpf_(1.f + ex2f(o1 * -1.4426950408889634f));
      xw[k] = pack_bf2(fmaf(bf_lo(sv), g0, bf_lo(xw[k])), fmaf(bf_hi(sv), g1, bf_hi(xw[k])));
    }
#pragma unroll
    for (int q = 0; q < 4; q++) stsm4(xa + (((2 * q + (lane >> 4)) ^ (lane & 7)) << 4), xw[4 * q], xw[4 * q + 1], xw[4 * q + 2], xw[4 * q + 3]);
    fence_async();
    __syncwarp();
    if (lane == 0) {
      tma_store_2d(&tm_out, sb + OFF_X + 2 * 16384 + (tid >> 5) * 2048, 64 * rk, 128 * G + 16 * (tid >> 5));
      bulk_commit();
      bulk_wait0_read();
    }
    TSTAMP(8);
  }
}

typedef CUresult (*EncodeFn)(CUtensorMap*, CUtensorMapDataType, cuuint32_t, void*, const cuuint64_t*, const cuuint64_t*,
                             const cuuint32_t*, const cuuint32_t*, CUtensorMapInterleave, CUtensorMapSwizzle,
                             CUtensorMapL2promotion, CUtensorMapFloatOOBfill);

void make_map(EncodeFn fn, CUtensorMap* m, const void* ptr, int rank, const cuuint64_t* dims, const cuuint64_t* strides, const cuuint32_t* box) {
  const cuuint32_t es[3] = {1, 1, 1};
  fn(m, CU_TENSOR_MAP_DATA_TYPE_BFLOAT16, rank, const_cast<void*>(ptr), dims, strides, box, es, CU_TENSOR_MAP_INTERLEAVE_NONE,
     CU_TENSOR_MAP_SWIZZLE_128B, CU_TENSOR_MAP_L2_PROMOTION_L2_128B, CU_TENSOR_MAP_FLOAT_OOB_FILL_NONE);
}

}

extern "C" void kernel_launch(void* const* d_in, const int* in_sizes, int n_in, void* d_out, int out_size) {
  (void)in_sizes; (void)n_in; (void)out_size;
  void* fnp = nullptr;
  cudaDriverEntryPointQueryResult qr;
  cudaGetDriverEntryPoint("cuTensorMapEncodeTiled", &fnp, cudaEnableDefault, &qr);
  EncodeFn fn = (EncodeFn)fnp;
  Params p;
  p.x = (const __nv_bfloat16*)d_in[0];
  p.a_re = (const __nv_bfloat16*)d_in[1]; p.a_im = (const __nv_bfloat16*)d_in[2];
  p.b_re = (const __nv_bfloat16*)d_in[3]; p.b_im = (const __nv_bfloat16*)d_in[4];
  p.c_re = (const __nv_bfloat16*)d_in[5]; p.c_im = (const __nv_bfloat16*)d_in[6];
  p.log_dt = (const __nv_bfloat16*)d_in[7]; p.dskip = (const __nv_bfloat16*)d_in[8];
  p.w1 = (const __nv_bfloat16*)d_in[10]; p.b1 = (const __nv_bfloat16*)d_in[11];
  p.w2 = (const __nv_bfloat16*)d_in[12]; p.b2 = (const __nv_bfloat16*)d_in[13];
  CUtensorMap mx, mw1, mw2, mo;
  {
    const cuuint64_t dims[2] = {448, 2048}, str[1] = {896};
    const cuuint32_t box[2] = {64, 128}, boxo[2] = {64, 16};
    make_map(fn, &mx, p.x, 2, dims, str, box);
    make_map(fn, &mo, d_out, 2, dims, str, boxo);
  }
  {
    const cuuint64_t dims[3] = {64, 448, 28}, str[2] = {3584, 128};
    const cuuint32_t box[3] = {64, 64, 4};
    make_map(fn, &mw1, p.w1, 3, dims, str, box);
  }
  {
    const cuuint64_t dims[2] = {448, 1792}, str[1] = {896};
    const cuuint32_t box[2] = {64, 256};
    make_map(fn, &mw2, p.w2, 2, dims, str, box);
  }
  cudaFuncSetAttribute(fused_kernel, cudaFuncAttributeMaxDynamicSharedMemorySize, SMEM_BYTES);
  fused_kernel<<<NCTA, 384, SMEM_BYTES>>>(mx, mw1, mw2, mo, p);
}
```

```cpp
#include <cuda_runtime.h>
#include <cuda_bf16.h>
#include <cuda_fp16.h>
#include <cuda.h>
#include <stdint.h>

namespace {

constexpr int D_ = 448, NST = 256, F_ = 1792;
constexpr int NRK = 7, NMLP = 112, NCTA = 132;
constexpr int SPIN_MAX = 1 << 21;

__device__ uint4 g_xnT[128 * 448 * 2];
__device__ uint4 g_ax[2048];
__device__ float g_r[2048];
__device__ uint4 g_bx[F_];
__device__ uint4 g_part[16 * 7 * 6 * 1024];
__device__ uint4 g_s2[16 * 224 * 32];
__device__ uint4 g_tbl[104 * 329];
__device__ unsigned g_cntA;
__device__ unsigned g_epoch;
#define TSTAMP(i)

constexpr int TBL_SC = 5248, TBL = 5264;
constexpr int TBL_C1 = 2624;
constexpr int SIG = 19584;
constexpr int SIG_U = 0, U_LBO = 656, SIG_V3 = 6272, SIG_V5 = 10368, SIG_V7 = 13440, SIG_V9 = 15488, SIG_V2 = 17536;
constexpr int Y2B = 6528, Y3B = 4352;
constexpr int KREC = 160, KSTG = 32 * KREC;
constexpr int OFF_W = 0, OFF_X = 98304, OFF_A = 147456, OFF_B = OFF_A + 8 * KSTG + 2560, OFF_T = OFF_B + 4 * KSTG;
constexpr int OFF_M = OFF_T + 15872;
constexpr int B_AX = Y2B, B_BX = B_AX + 2048, B_R = B_BX + 4096;
constexpr int M_BAR = 0, M_REL = 128, M_EP = 192, M_CSR = 256, M_END = 512;
constexpr int SMEM_BYTES = OFF_M + M_END;
constexpr int S_WORK = 63232, S_WGB = 2 * SIG + Y2B + Y3B;
static_assert(S_WORK + 3 * S_WGB <= OFF_M && SMEM_BYTES <= 232448, "smem");

struct Params {
  const __nv_bfloat16 *x, *a_re, *a_im, *b_re, *b_im, *c_re, *c_im, *log_dt, *dskip, *w1, *b1, *w2, *b2;
};

__device__ __forceinline__ int opaque(int x) { int v; asm volatile("mov.u32 %0, %1;" : "=r"(v) : "r"(x)); return v; }
__device__ __forceinline__ int rd_bid() { int v; asm volatile("mov.u32 %0, %%ctaid.x;" : "=r"(v)); return v; }
__device__ __forceinline__ uint32_t smem_u32(const void* p) { return (uint32_t)__cvta_generic_to_shared(p); }
__device__ __forceinline__ void mbar_init(uint32_t bar, int cnt) { asm volatile("mbarrier.init.shared::cta.b64 [%0], %1;" ::"r"(bar), "r"(cnt)); }
__device__ __forceinline__ void mbar_expect(uint32_t bar, uint32_t bytes) {
  asm volatile("mbarrier.arrive.expect_tx.shared::cta.b64 _, [%0], %1;" ::"r"(bar), "r"(bytes) : "memory");
}
__device__ __forceinline__ void mbar_wait(uint32_t bar, uint32_t parity) {
  uint32_t done = 0;
#pragma unroll 1
  for (int it = 0; it < SPIN_MAX; it++) {
    asm volatile("{.reg .pred p; mbarrier.try_wait.parity.shared::cta.b64 p, [%1], %2; selp.u32 %0,1,0,p;}"
                 : "=r"(done) : "r"(bar), "r"(parity) : "memory");
    if (done) break;
  }
}
__device__ __forceinline__ void tma_2d(uint32_t dst, const CUtensorMap* m, int c0, int c1, uint32_t bar) {
  asm volatile("cp.async.bulk.tensor.2d.shared::cluster.global.mbarrier::complete_tx::bytes [%0], [%1, {%3, %4}], [%2];"
               ::"r"(dst), "l"(m), "r"(bar), "r"(c0), "r"(c1) : "memory");
}
__device__ __forceinline__ void tma_3d(uint32_t dst, const CUtensorMap* m, int c0, int c1, int c2, uint32_t bar) {
  asm volatile("cp.async.bulk.tensor.3d.shared::cluster.global.mbarrier::complete_tx::bytes [%0], [%1, {%3, %4, %5}], [%2];"
               ::"r"(dst), "l"(m), "r"(bar), "r"(c0), "r"(c1), "r"(c2) : "memory");
}
__device__ __forceinline__ void tma_store_2d(const CUtensorMap* m, uint32_t src, int c0, int c1) {
  asm volatile("cp.async.bulk.tensor.2d.global.shared::cta.bulk_group [%0, {%2, %3}], [%1];"
               ::"l"(m), "r"(src), "r"(c0), "r"(c1) : "memory");
}
__device__ __forceinline__ void bulk_s2g(void* dst, uint32_t src, uint32_t bytes) {
  asm volatile("cp.async.bulk.global.shared::cta.bulk_group [%0], [%1], %2;" ::"l"(dst), "r"(src), "r"(bytes) : "memory");
}
__device__ __forceinline__ void bulk_g2s(uint32_t dst, const void* src, uint32_t bytes, uint32_t bar) {
  asm volatile("cp.async.bulk.shared::cluster.global.mbarrier::complete_tx::bytes [%0], [%1], %2, [%3];"
               ::"r"(dst), "l"(src), "r"(bytes), "r"(bar) : "memory");
}
__device__ __forceinline__ void bulk_commit() { asm volatile("cp.async.bulk.commit_group;" ::: "memory"); }
__device__ __forceinline__ void bulk_wait0() { asm volatile("cp.async.bulk.wait_group 0;" ::: "memory"); }
__device__ __forceinline__ void bulk_wait0_read() { asm volatile("cp.async.bulk.wait_group.read 0;" ::: "memory"); }
__device__ __forceinline__ void fence_async() { asm volatile("fence.proxy.async.shared::cta;" ::: "memory"); }
__device__ __forceinline__ void bar_sync(int id, int n) { asm volatile("bar.sync %0, %1;" ::"r"(id), "r"(n) : "memory"); }
__device__ __forceinline__ void bar_arrive(int id, int n) { asm volatile("bar.arrive %0, %1;" ::"r"(id), "r"(n) : "memory"); }
__device__ __forceinline__ void wg_fence() { asm volatile("wgmma.fence.sync.aligned;" ::: "memory"); }
__device__ __forceinline__ void wg_commit() { asm volatile("wgmma.commit_group.sync.aligned;" ::: "memory"); }
template <int N> __device__ __forceinline__ void wg_wait() { asm volatile("wgmma.wait_group.sync.aligned %0;" ::"n"(N) : "memory"); }
template <int N> __device__ __forceinline__ void fence_regs(float* d) {
#pragma unroll
  for (int i = 0; i < N; i++) asm volatile("" : "+f"(d[i])::"memory");
}
__device__ __forceinline__ uint64_t mkdesc(uint32_t addr, uint32_t lbo, uint32_t sbo, uint32_t sw) {
  return (uint64_t)((addr & 0x3FFFF) >> 4) | ((uint64_t)(lbo >> 4) << 16) | ((uint64_t)(sbo >> 4) << 32) | ((uint64_t)sw << 62);
}
__device__ __forceinline__ uint32_t lds32(uint32_t a) { uint32_t v; asm volatile("ld.shared.b32 %0, [%1];" : "=r"(v) : "r"(a) : "memory"); return v; }
__device__ __forceinline__ float lds32f(uint32_t a) { float v; asm volatile("ld.shared.f32 %0, [%1];" : "=f"(v) : "r"(a) : "memory"); return v; }
__device__ __forceinline__ float2 lds64f(uint32_t a) { float2 v; asm volatile("ld.shared.v2.f32 {%0,%1}, [%2];" : "=f"(v.x), "=f"(v.y) : "r"(a) : "memory"); return v; }
__device__ __forceinline__ uint4 lds128(uint32_t a) {
  uint4 v; asm volatile("ld.shared.v4.b32 {%0,%1,%2,%3}, [%4];" : "=r"(v.x), "=r"(v.y), "=r"(v.z), "=r"(v.w) : "r"(a) : "memory"); return v;
}
__device__ __forceinline__ void sts16(uint32_t a, uint16_t v) { asm volatile("st.shared.b16 [%0], %1;" ::"r"(a), "h"(v) : "memory"); }
__device__ __forceinline__ void sts32f(uint32_t a, float v) { asm volatile("st.shared.f32 [%0], %1;" ::"r"(a), "f"(v) : "memory"); }
__device__ __forceinline__ void sts64f(uint32_t a, float x, float y) { asm volatile("st.shared.v2.f32 [%0], {%1,%2};" ::"r"(a), "f"(x), "f"(y) : "memory"); }
__device__ __forceinline__ void sts128(uint32_t a, uint32_t x, uint32_t y, uint32_t z, uint32_t w) {
  asm volatile("st.shared.v4.b32 [%0], {%1,%2,%3,%4};" ::"r"(a), "r"(x), "r"(y), "r"(z), "r"(w) : "memory");
}
__device__ __forceinline__ void ldsm4(uint32_t a, uint32_t& r0, uint32_t& r1, uint32_t& r2, uint32_t& r3) {
  asm volatile("ldmatrix.sync.aligned.m8n8.x4.shared.b16 {%0,%1,%2,%3}, [%4];" : "=r"(r0), "=r"(r1), "=r"(r2), "=r"(r3) : "r"(a) : "memory");
}
__device__ __forceinline__ void ldsm4t(uint32_t a, uint32_t& r0, uint32_t& r1, uint32_t& r2, uint32_t& r3) {
  asm volatile("ldmatrix.sync.aligned.m8n8.x4.trans.shared.b16 {%0,%1,%2,%3}, [%4];" : "=r"(r0), "=r"(r1), "=r"(r2), "=r"(r3) : "r"(a) : "memory");
}
__device__ __forceinline__ void ldsm2t(uint32_t a, uint32_t& r0, uint32_t& r1) {
  asm volatile("ldmatrix.sync.aligned.m8n8.x2.trans.shared.b16 {%0,%1}, [%2];" : "=r"(r0), "=r"(r1) : "r"(a) : "memory");
}
__device__ __forceinline__ void stsm4(uint32_t a, uint32_t r0, uint32_t r1, uint32_t r2, uint32_t r3) {
  asm volatile("stmatrix.sync.aligned.m8n8.x4.shared.b16 [%0], {%1,%2,%3,%4};" ::"r"(a), "r"(r0), "r"(r1), "r"(r2), "r"(r3) : "memory");
}
__device__ __forceinline__ void mma_f16(float* c, uint32_t a0, uint32_t a1, uint32_t a2, uint32_t a3, uint32_t b0, uint32_t b1) {
  asm volatile("mma.sync.aligned.m16n8k16.row.col.f32.f16.f16.f32 {%0,%1,%2,%3},{%4,%5,%6,%7},{%8,%9},{%0,%1,%2,%3};"
               : "+f"(c[0]), "+f"(c[1]), "+f"(c[2]), "+f"(c[3]) : "r"(a0), "r"(a1), "r"(a2), "r"(a3), "r"(b0), "r"(b1));
}
__device__ __forceinline__ uint4 ld_relaxed4(const void* p) {
  uint4 v; asm volatile("ld.relaxed.gpu.global.v4.b32 {%0,%1,%2,%3}, [%4];" : "=r"(v.x), "=r"(v.y), "=r"(v.z), "=r"(v.w) : "l"(p) : "memory"); return v;
}
__device__ __forceinline__ void st_relaxed2(void* p, uint32_t x, uint32_t y) {
  asm volatile("st.relaxed.gpu.global.v2.b32 [%0], {%1,%2};" ::"l"(p), "r"(x), "r"(y) : "memory");
}
__device__ __forceinline__ uint4 ld_b128(const void* p) {
  uint4 v;
  asm volatile("{.reg .b128 t; .reg .b64 a, c; ld.relaxed.gpu.global.b128 t, [%4]; mov.b128 {a, c}, t; mov.b64 {%0,%1}, a; mov.b64 {%2,%3}, c;}"
               : "=r"(v.x), "=r"(v.y), "=r"(v.z), "=r"(v.w) : "l"(p) : "memory");
  return v;
}
__device__ __forceinline__ void st_b128(void* p, uint32_t tag, uint32_t x, uint32_t y, uint32_t z, uint32_t w) {
  asm volatile("{.reg .b128 t; .reg .b64 a, c; mov.b64 a, {%1,%2}; mov.b64 c, {%3,%4}; mov.b128 t, {a, c}; st.relaxed.gpu.global.b128 [%0], t;}"
               ::"l"(p), "r"((x & ~1u) | tag), "r"(y), "r"(z), "r"(w) : "memory");
}
__device__ __forceinline__ unsigned ld_relaxed1(const unsigned* p) {
  unsigned v; asm volatile("ld.relaxed.gpu.global.u32 %0, [%1];" : "=r"(v) : "l"(p) : "memory"); return v;
}
__device__ __forceinline__ void red_release(unsigned* p) {
  asm volatile("red.release.gpu.global.add.u32 [%0], 1;" ::"l"(p) : "memory");
}
__device__ __forceinline__ void wait_count(const unsigned* p, unsigned target) {
#pragma unroll 1
  for (int it = 0; it < SPIN_MAX; it++) {
    if ((int)(ld_relaxed1(p) - target) >= 0) break;
    __nanosleep(40);
  }
  asm volatile("fence.acq_rel.gpu;" ::: "memory");
}
__device__ __forceinline__ uint32_t pack_h2(float lo, float hi) { uint32_t r; asm("cvt.rn.f16x2.f32 %0, %1, %2;" : "=r"(r) : "f"(hi), "f"(lo)); return r; }
__device__ __forceinline__ uint32_t pack_bf2(float lo, float hi) { uint32_t r; asm("cvt.rn.bf16x2.f32 %0, %1, %2;" : "=r"(r) : "f"(hi), "f"(lo)); return r; }
__device__ __forceinline__ uint32_t pack_bf2v(float lo, float hi) { uint32_t r; asm volatile("cvt.rn.bf16x2.f32 %0, %1, %2;" : "=r"(r) : "f"(hi), "f"(lo)); return r; }
__device__ __forceinline__ float bf_lo(uint32_t w) { return __uint_as_float(w << 16); }
__device__ __forceinline__ float bf_hi(uint32_t w) { return __uint_as_float(w & 0xffff0000u); }
__device__ __forceinline__ float rbf(float v) { return __bfloat162float(__float2bfloat16_rn(v)); }
__device__ __forceinline__ float2 h2f(uint32_t w) { return __half22float2(*reinterpret_cast<__half2*>(&w)); }
__device__ __forceinline__ float ex2f(float v) { float r; asm("ex2.approx.ftz.f32 %0, %1;" : "=f"(r) : "f"(v)); return r; }
__device__ __forceinline__ float rcpf_(float v) { float r; asm("rcp.approx.f32 %0, %1;" : "=f"(r) : "f"(v)); return r; }
__device__ __forceinline__ float sqrtf_(float v) { float r; asm("sqrt.approx.f32 %0, %1;" : "=f"(r) : "f"(v)); return r; }
__device__ __forceinline__ float tanhf_(float v) { float r; asm volatile("tanh.approx.f32 %0, %1;" : "=f"(r) : "f"(v)); return r; }

__device__ __forceinline__ void wg_ss_bf16_n256(float* d, uint64_t da, uint64_t db, int sc) {
  asm volatile("{.reg .pred p; setp.ne.b32 p, %130, 0;\n"
    "wgmma.mma_async.sync.aligned.m64n256k16.f32.bf16.bf16 {%0, %1, %2, %3, %4, %5, %6, %7, %8, %9, %10, %11, %12, %13, %14, %15, %16, %17, %18, %19, %20, %21, %22, %23, %24, %25, %26, %27, %28, %29, %30, %31, %32, %33, %34, %35, %36, %37, %38, %39, %40, %41, %42, %43, %44, %45, %46, %47, %48, %49, %50, %51, %52, %53, %54, %55, %56, %57, %58, %59, %60, %61, %62, %63, %64, %65, %66, %67, %68, %69, %70, %71, %72, %73, %74, %75, %76, %77, %78, %79, %80, %81, %82, %83, %84, %85, %86, %87, %88, %89, %90, %91, %92, %93, %94, %95, %96, %97, %98, %99, %100, %101, %102, %103, %104, %105, %106, %107, %108, %109, %110, %111, %112, %113, %114, %115, %116, %117, %118, %119, %120, %121, %122, %123, %124, %125, %126, %127}, %128, %129, p, 1, 1, 0, 1;}\n"
    : "+f"(d[0]), "+f"(d[1]), "+f"(d[2]), "+f"(d[3]), "+f"(d[4]), "+f"(d[5]), "+f"(d[6]), "+f"(d[7]), "+f"(d[8]), "+f"(d[9]), "+f"(d[10]), "+f"(d[11]), "+f"(d[12]), "+f"(d[13]), "+f"(d[14]), "+f"(d[15]), "+f"(d[16]), "+f"(d[17]), "+f"(d[18]), "+f"(d[19]), "+f"(d[20]), "+f"(d[21]), "+f"(d[22]), "+f"(d[23]), "+f"(d[24]), "+f"(d[25]), "+f"(d[26]), "+f"(d[27]), "+f"(d[28]), "+f"(d[29]), "+f"(d[30]), "+f"(d[31]), "+f"(d[32]), "+f"(d[33]), "+f"(d[34]), "+f"(d[35]), "+f"(d[36]), "+f"(d[37]), "+f"(d[38]), "+f"(d[39]), "+f"(d[40]), "+f"(d[41]), "+f"(d[42]), "+f"(d[43]), "+f"(d[44]), "+f"(d[45]), "+f"(d[46]), "+f"(d[47]), "+f"(d[48]), "+f"(d[49]), "+f"(d[50]), "+f"(d[51]), "+f"(d[52]), "+f"(d[53]), "+f"(d[54]), "+f"(d[55]), "+f"(d[56]), "+f"(d[57]), "+f"(d[58]), "+f"(d[59]), "+f"(d[60]), "+f"(d[61]), "+f"(d[62]), "+f"(d[63]), "+f"(d[64]), "+f"(d[65]), "+f"(d[66]), "+f"(d[67]), "+f"(d[68]), "+f"(d[69]), "+f"(d[70]), "+f"(d[71]), "+f"(d[72]), "+f"(d[73]), "+f"(d[74]), "+f"(d[75]), "+f"(d[76]), "+f"(d[77]), "+f"(d[78]), "+f"(d[79]), "+f"(d[80]), "+f"(d[81]), "+f"(d[82]), "+f"(d[83]), "+f"(d[84]), "+f"(d[85]), "+f"(d[86]), "+f"(d[87]), "+f"(d[88]), "+f"(d[89]), "+f"(d[90]), "+f"(d[91]), "+f"(d[92]), "+f"(d[93]), "+f"(d[94]), "+f"(d[95]), "+f"(d[96]), "+f"(d[97]), "+f"(d[98]), "+f"(d[99]), "+f"(d[100]), "+f"(d[101]), "+f"(d[102]), "+f"(d[103]), "+f"(d[104]), "+f"(d[105]), "+f"(d[106]), "+f"(d[107]), "+f"(d[108]), "+f"(d[109]), "+f"(d[110]), "+f"(d[111]), "+f"(d[112]), "+f"(d[113]), "+f"(d[114]), "+f"(d[115]), "+f"(d[116]), "+f"(d[117]), "+f"(d[118]), "+f"(d[119]), "+f"(d[120]), "+f"(d[121]), "+f"(d[122]), "+f"(d[123]), "+f"(d[124]), "+f"(d[125]), "+f"(d[126]), "+f"(d[127])
    : "l"(da), "l"(db), "r"(sc));
}

__device__ __forceinline__ void wg_ss_bf16_n256k(float* d, uint64_t da, uint64_t db, int sc) {
  asm volatile("{.reg .pred p; setp.ne.b32 p, %130, 0;\n"
    "wgmma.mma_async.sync.aligned.m64n256k16.f32.bf16.bf16 {%0, %1, %2, %3, %4, %5, %6, %7, %8, %9, %10, %11, %12, %13, %14, %15, %16, %17, %18, %19, %20, %21, %22, %23, %24, %25, %26, %27, %28, %29, %30, %31, %32, %33, %34, %35, %36, %37, %38, %39, %40, %41, %42, %43, %44, %45, %46, %47, %48, %49, %50, %51, %52, %53, %54, %55, %56, %57, %58, %59, %60, %61, %62, %63, %64, %65, %66, %67, %68, %69, %70, %71, %72, %73, %74, %75, %76, %77, %78, %79, %80, %81, %82, %83, %84, %85, %86, %87, %88, %89, %90, %91, %92, %93, %94, %95, %96, %97, %98, %99, %100, %101, %102, %103, %104, %105, %106, %107, %108, %109, %110, %111, %112, %113, %114, %115, %116, %117, %118, %119, %120, %121, %122, %123, %124, %125, %126, %127}, %128, %129, p, 1, 1, 0, 0;}\n"
    : "+f"(d[0]), "+f"(d[1]), "+f"(d[2]), "+f"(d[3]), "+f"(d[4]), "+f"(d[5]), "+f"(d[6]), "+f"(d[7]), "+f"(d[8]), "+f"(d[9]), "+f"(d[10]), "+f"(d[11]), "+f"(d[12]), "+f"(d[13]), "+f"(d[14]), "+f"(d[15]), "+f"(d[16]), "+f"(d[17]), "+f"(d[18]), "+f"(d[19]), "+f"(d[20]), "+f"(d[21]), "+f"(d[22]), "+f"(d[23]), "+f"(d[24]), "+f"(d[25]), "+f"(d[26]), "+f"(d[27]), "+f"(d[28]), "+f"(d[29]), "+f"(d[30]), "+f"(d[31]), "+f"(d[32]), "+f"(d[33]), "+f"(d[34]), "+f"(d[35]), "+f"(d[36]), "+f"(d[37]), "+f"(d[38]), "+f"(d[39]), "+f"(d[40]), "+f"(d[41]), "+f"(d[42]), "+f"(d[43]), "+f"(d[44]), "+f"(d[45]), "+f"(d[46]), "+f"(d[47]), "+f"(d[48]), "+f"(d[49]), "+f"(d[50]), "+f"(d[51]), "+f"(d[52]), "+f"(d[53]), "+f"(d[54]), "+f"(d[55]), "+f"(d[56]), "+f"(d[57]), "+f"(d[58]), "+f"(d[59]), "+f"(d[60]), "+f"(d[61]), "+f"(d[62]), "+f"(d[63]), "+f"(d[64]), "+f"(d[65]), "+f"(d[66]), "+f"(d[67]), "+f"(d[68]), "+f"(d[69]), "+f"(d[70]), "+f"(d[71]), "+f"(d[72]), "+f"(d[73]), "+f"(d[74]), "+f"(d[75]), "+f"(d[76]), "+f"(d[77]), "+f"(d[78]), "+f"(d[79]), "+f"(d[80]), "+f"(d[81]), "+f"(d[82]), "+f"(d[83]), "+f"(d[84]), "+f"(d[85]), "+f"(d[86]), "+f"(d[87]), "+f"(d[88]), "+f"(d[89]), "+f"(d[90]), "+f"(d[91]), "+f"(d[92]), "+f"(d[93]), "+f"(d[94]), "+f"(d[95]), "+f"(d[96]), "+f"(d[97]), "+f"(d[98]), "+f"(d[99]), "+f"(d[100]), "+f"(d[101]), "+f"(d[102]), "+f"(d[103]), "+f"(d[104]), "+f"(d[105]), "+f"(d[106]), "+f"(d[107]), "+f"(d[108]), "+f"(d[109]), "+f"(d[110]), "+f"(d[111]), "+f"(d[112]), "+f"(d[113]), "+f"(d[114]), "+f"(d[115]), "+f"(d[116]), "+f"(d[117]), "+f"(d[118]), "+f"(d[119]), "+f"(d[120]), "+f"(d[121]), "+f"(d[122]), "+f"(d[123]), "+f"(d[124]), "+f"(d[125]), "+f"(d[126]), "+f"(d[127])
    : "l"(da), "l"(db), "r"(sc));
}

__device__ __forceinline__ void wg_rs_bf16_n64(float* d, uint32_t a0, uint32_t a1, uint32_t a2, uint32_t a3, uint64_t db, int sc) {
  asm volatile("{.reg .pred p; setp.ne.b32 p, %37, 0;\n"
    "wgmma.mma_async.sync.aligned.m64n64k16.f32.bf16.bf16 {%0, %1, %2, %3, %4, %5, %6, %7, %8, %9, %10, %11, %12, %13, %14, %15, %16, %17, %18, %19, %20, %21, %22, %23, %24, %25, %26, %27, %28, %29, %30, %31}, {%32,%33,%34,%35}, %36, p, 1, 1, 1;}\n"
    : "+f"(d[0]), "+f"(d[1]), "+f"(d[2]), "+f"(d[3]), "+f"(d[4]), "+f"(d[5]), "+f"(d[6]), "+f"(d[7]), "+f"(d[8]), "+f"(d[9]), "+f"(d[10]), "+f"(d[11]), "+f"(d[12]), "+f"(d[13]), "+f"(d[14]), "+f"(d[15]), "+f"(d[16]), "+f"(d[17]), "+f"(d[18]), "+f"(d[19]), "+f"(d[20]), "+f"(d[21]), "+f"(d[22]), "+f"(d[23]), "+f"(d[24]), "+f"(d[25]), "+f"(d[26]), "+f"(d[27]), "+f"(d[28]), "+f"(d[29]), "+f"(d[30]), "+f"(d[31])
    : "r"(a0), "r"(a1), "r"(a2), "r"(a3), "l"(db), "r"(sc));
}

__device__ __forceinline__ void wg_rs_f16_n32k(float* d, uint32_t a0, uint32_t a1, uint32_t a2, uint32_t a3, uint64_t db, int sc) {
  asm volatile("{.reg .pred p; setp.ne.b32 p, %21, 0;\n"
    "wgmma.mma_async.sync.aligned.m64n32k16.f32.f16.f16 {%0, %1, %2, %3, %4, %5, %6, %7, %8, %9, %10, %11, %12, %13, %14, %15}, {%16,%17,%18,%19}, %20, p, 1, 1, 0;}\n"
    : "+f"(d[0]), "+f"(d[1]), "+f"(d[2]), "+f"(d[3]), "+f"(d[4]), "+f"(d[5]), "+f"(d[6]), "+f"(d[7]), "+f"(d[8]), "+f"(d[9]), "+f"(d[10]), "+f"(d[11]), "+f"(d[12]), "+f"(d[13]), "+f"(d[14]), "+f"(d[15])
    : "r"(a0), "r"(a1), "r"(a2), "r"(a3), "l"(db), "r"(sc));
}

__device__ __forceinline__ void wg_rs_f16_n24t(float* d, uint32_t a0, uint32_t a1, uint32_t a2, uint32_t a3, uint64_t db, int sc) {
  asm volatile("{.reg .pred p; setp.ne.b32 p, %17, 0;\n"
    "wgmma.mma_async.sync.aligned.m64n24k16.f32.f16.f16 {%0, %1, %2, %3, %4, %5, %6, %7, %8, %9, %10, %11}, {%12,%13,%14,%15}, %16, p, 1, 1, 1;}\n"
    : "+f"(d[0]), "+f"(d[1]), "+f"(d[2]), "+f"(d[3]), "+f"(d[4]), "+f"(d[5]), "+f"(d[6]), "+f"(d[7]), "+f"(d[8]), "+f"(d[9]), "+f"(d[10]), "+f"(d[11])
    : "r"(a0), "r"(a1), "r"(a2), "r"(a3), "l"(db), "r"(sc));
}

__device__ __forceinline__ void wg_rs_f16_n16t(float* d, uint32_t a0, uint32_t a1, uint32_t a2, uint32_t a3, uint64_t db, int sc) {
  asm volatile("{.reg .pred p; setp.ne.b32 p, %13, 0;\n"
    "wgmma.mma_async.sync.aligned.m64n16k16.f32.f16.f16 {%0, %1, %2, %3, %4, %5, %6, %7}, {%8,%9,%10,%11}, %12, p, 1, 1, 1;}\n"
    : "+f"(d[0]), "+f"(d[1]), "+f"(d[2]), "+f"(d[3]), "+f"(d[4]), "+f"(d[5]), "+f"(d[6]), "+f"(d[7])
    : "r"(a0), "r"(a1), "r"(a2), "r"(a3), "l"(db), "r"(sc));
}

struct cf { float x, y; };
__device__ __forceinline__ cf cmul(cf a, cf b) { cf r; r.x = fmaf(a.x, b.x, -a.y * b.y); r.y = fmaf(a.x, b.y, a.y * b.x); return r; }
__device__ __forceinline__ cf zpow(float rho2, float phi, float e) {
  const float m = ex2f(rho2 * e), ang = phi * e;
  cf r; r.x = m * __cosf(ang); r.y = m * __sinf(ang); return r;
}
__device__ __forceinline__ __half2 H2(uint32_t v) { return *reinterpret_cast<__half2*>(&v); }
__device__ __forceinline__ uint32_t U32(__half2 v) { return *reinterpret_cast<uint32_t*>(&v); }
__device__ __forceinline__ uint32_t hprod(uint32_t v, uint32_t r, uint32_t rr) {
  return U32(__hfma2(__high2half2(H2(v)), H2(rr), __hmul2(__low2half2(H2(v)), H2(r))));
}
__device__ __forceinline__ void hprod2(uint32_t re, uint32_t im, uint32_t r, uint32_t& ore, uint32_t& oim) {
  const __half2 rx = __low2half2(H2(r)), ry = __high2half2(H2(r));
  ore = U32(__hfma2(H2(re), rx, __hneg2(__hmul2(H2(im), ry))));
  oim = U32(__hfma2(H2(re), ry, __hmul2(H2(im), rx)));
}
__device__ __forceinline__ uint32_t rot90(uint32_t v) { return __byte_perm(v, 0, 0x1032) ^ 0x00008000u; }
__device__ __forceinline__ uint32_t hadd2u(uint32_t a, uint32_t b) { return U32(__hadd2(H2(a), H2(b))); }

struct KgIn { uint32_t cur[6], nxt[6]; uint4 m[4]; uint16_t ldt, dk; };
__device__ __forceinline__ void kgen_load(const Params& p, int d, int wd0, int nw, int lane, KgIn& k) {
  const int off = d * (NST / 2) + lane * 4;
  const uint32_t* P[6] = {(const uint32_t*)p.a_re, (const uint32_t*)p.a_im, (const uint32_t*)p.b_re,
                          (const uint32_t*)p.b_im, (const uint32_t*)p.c_re, (const uint32_t*)p.c_im};
  k.ldt = __ldg((const uint16_t*)p.log_dt + d); k.dk = __ldg((const uint16_t*)p.dskip + d);
#pragma unroll
  for (int i = 0; i < 4; i++) k.m[i] = __ldg((const uint4*)(P[2 + i] + off));
#pragma unroll
  for (int i = 0; i < 6; i++) { k.cur[i] = __ldg(P[i] + off + wd0); k.nxt[i] = __ldg(P[i] + off + wd0 + nw - 1); }
}
__device__ __forceinline__ void kgen_warp(KgIn& k, int nw, uint32_t stg, uint32_t tbl, int lane) {
  float dl, dt, inv_sc;
  {
    const uint32_t M = 0x7fff7fffu;
    uint32_t mx[2];
#pragma unroll
    for (int i = 0; i < 2; i++) {
      const uint4 a = k.m[2 * i], c = k.m[2 * i + 1];
      const uint32_t m = __vmaxu2(__vmaxu2(__vmaxu2(a.x & M, a.y & M), __vmaxu2(a.z & M, a.w & M)),
                                  __vmaxu2(__vmaxu2(c.x & M, c.y & M), __vmaxu2(c.z & M, c.w & M)));
      mx[i] = __reduce_max_sync(0xffffffffu, max(m << 16, m & 0xffff0000u));
    }
    dt = rbf(ex2f(bf_lo(k.ldt) * 1.4426950408889634f));
    const float dsk = bf_lo(k.dk) * rcpf_(dt);
    float sc = fmaxf(0.125f * __uint_as_float(mx[0]) * __uint_as_float(mx[1]), fabsf(dsk) * (1.f / 4096.f));
    sc = __uint_as_float(__float_as_uint(fminf(fmaxf(sc, 1e-30f), 1e30f)) & 0x7f800000u);
    inv_sc = rcpf_(sc);
    if (lane == 0) sts64f(tbl + TBL_SC + 8, dt * sc, dsk * inv_sc);
    dl = dt * 1.4426950408889634f;
  }
  const uint32_t st0 = stg + lane * KREC + (((lane >> 2) & 1) << 4), st1 = st0 ^ 16;
  const int mat = lane >> 3, rowi = lane & 7;
  const uint32_t ldB = stg + (4 * (mat & 1) + (rowi >> 1)) * KREC + ((((mat >> 1) * 2 + (rowi & 1)) << 4) ^ ((mat & 1) << 4));
  const uint32_t ldA = stg + (4 * (mat >> 1) + (rowi >> 1)) * KREC + ((((mat & 1) * 2 + (rowi & 1)) << 4) ^ ((mat >> 1) << 4)) + 96;
  const int csrc = 20 + (lane & 3);
  float acc[24];
#pragma unroll
  for (int i = 0; i < 24; i++) acc[i] = 0.f;
#pragma unroll 1
  for (int it = 0; it < 2 * nw; it++) {
    const uint32_t sel = (it & 1) ? 0x3244u : 0x1044u;
    float v[6];
#pragma unroll
    for (int i = 0; i < 6; i++) { v[i] = __uint_as_float(__byte_perm(k.cur[i], 0, sel)); if (it == 1) k.cur[i] = k.nxt[i]; }
    const float rho2 = v[0] * dl, phi = v[1] * dt;
    const cf bb = {v[2] * inv_sc, v[3] * -inv_sc}, cc = {v[4], -v[5]};
    cf X[8];
    X[0] = cmul(cc, bb);
    const cf z1 = zpow(rho2, -phi, 1.f), z8 = zpow(rho2, phi, 8.f), z64 = zpow(rho2, phi, 64.f);
    const cf y1 = zpow(rho2, -phi, 256.f), y4 = zpow(rho2, -phi, 1024.f);
    const cf z2 = cmul(z1, z1);
    X[1] = cmul(X[0], z1);
#pragma unroll
    for (int j = 2; j < 8; j++) X[j] = cmul(X[j - 2], z2);
    const cf a0 = cmul(X[0], y1), a1 = cmul(X[2], y1), a2 = cmul(X[4], y1), a3 = cmul(X[6], y1);
    const cf a4 = cmul(a0, y1), a5 = cmul(a2, y1);
    const cf a6 = cmul(a4, y1), a7 = cmul(a5, y1);
    const cf v0 = cmul(X[0], y4), v1 = cmul(a0, y4), v2 = cmul(a4, y4), v3 = cmul(a6, y4), v4 = cmul(v0, y4);
    const cf f2 = cmul(z8, z8), f3 = cmul(f2, z8), f4 = cmul(f2, f2), f5 = cmul(f3, f2), f6 = cmul(f4, f2), f7 = cmul(f4, f3);
    const cf z128 = cmul(z64, z64);
    const uint32_t fr[4] = {pack_h2(1.f, z8.x), pack_h2(f2.x, f3.x), pack_h2(f4.x, f5.x), pack_h2(f6.x, f7.x)};
    const uint32_t fi[4] = {pack_h2(0.f, z8.y), pack_h2(f2.y, f3.y), pack_h2(f4.y, f5.y), pack_h2(f6.y, f7.y)};
    const uint32_t h64 = pack_h2(z64.x, z64.y);
    uint32_t gr[4], gi[4];
#pragma unroll
    for (int j = 0; j < 4; j++) hprod2(fr[j], fi[j], h64, gr[j], gi[j]);
    __syncwarp();
    sts128(st0, pack_h2(X[0].x, X[1].x), pack_h2(X[2].x, X[3].x), pack_h2(X[4].x, X[5].x), pack_h2(X[6].x, X[7].x));
    sts128(st1, pack_h2(X[0].y, X[1].y), pack_h2(X[2].y, X[3].y), pack_h2(X[4].y, X[5].y), pack_h2(X[6].y, X[7].y));
    sts128(st0 + 32, pack_h2(a0.x, a1.x), pack_h2(a2.x, a3.x), pack_h2(a4.x, a5.x), pack_h2(a6.x, a7.x));
    sts128(st1 + 32, pack_h2(a0.y, a1.y), pack_h2(a2.y, a3.y), pack_h2(a4.y, a5.y), pack_h2(a6.y, a7.y));
    asm volatile("st.shared.v2.b32 [%0], {%1,%2};" ::"r"(st0 + 64), "r"(pack_h2(v0.x, v1.x)), "r"(pack_h2(v2.x, v3.x)) : "memory");
    asm volatile("st.shared.v2.b32 [%0], {%1,%2};" ::"r"(st1 + 64), "r"(pack_h2(v0.y, v1.y)), "r"(pack_h2(v2.y, v3.y)) : "memory");
    asm volatile("st.shared.v2.b32 [%0], {%1,%1};" ::"r"(st0 + 72), "r"(pack_h2(v4.x, z128.x)) : "memory");
    asm volatile("st.shared.v2.b32 [%0], {%1,%1};" ::"r"(st1 + 72), "r"(pack_h2(v4.y, z128.y)) : "memory");
    sts128(st0 + 96, fr[0], fr[1], fr[2], fr[3]);
    sts128(st1 + 96, fi[0], fi[1], fi[2], fi[3]);
    sts128(st0 + 128, gr[0], gr[1], gr[2], gr[3]);
    sts128(st1 + 128, gi[0], gi[1], gi[2], gi[3]);
    __syncwarp();
    uint32_t B[4][6], A[4][4];
#pragma unroll
    for (int ks = 0; ks < 4; ks++) {
      ldsm2t(ldB + ks * 8 * KREC + 64, B[ks][4], B[ks][5]);
      ldsm4t(ldA + ks * 8 * KREC, A[ks][0], A[ks][1], A[ks][2], A[ks][3]);
      ldsm4t(ldB + ks * 8 * KREC, B[ks][0], B[ks][1], B[ks][2], B[ks][3]);
    }
#pragma unroll
    for (int ks = 0; ks < 4; ks++) {
      const uint32_t rl = __shfl_sync(0xffffffffu, B[ks][4], csrc), rh = __shfl_sync(0xffffffffu, B[ks][5], csrc);
      const uint32_t rlr = rot90(rl), rhr = rot90(rh);
      mma_f16(acc + 0, A[ks][0], A[ks][1], A[ks][2], A[ks][3], B[ks][0], B[ks][1]);
      mma_f16(acc + 4, A[ks][0], A[ks][1], A[ks][2], A[ks][3], B[ks][2], B[ks][3]);
      mma_f16(acc + 8, A[ks][0], A[ks][1], A[ks][2], A[ks][3], B[ks][4], B[ks][5]);
      const uint32_t c0 = hprod(A[ks][0], rl, rlr), c1 = hprod(A[ks][1], rl, rlr);
      const uint32_t c2 = hprod(A[ks][2], rh, rhr), c3 = hprod(A[ks][3], rh, rhr);
      mma_f16(acc + 12, c0, c1, c2, c3, B[ks][0], B[ks][1]);
      mma_f16(acc + 16, c0, c1, c2, c3, B[ks][2], B[ks][3]);
      mma_f16(acc + 20, c0, c1, c2, c3, B[ks][4], B[ks][5]);
    }
  }
  __syncwarp();
#pragma unroll
  for (int q = 0; q < 4; q++)
#pragma unroll
    for (int nt = 0; nt < 3; nt++) {
      const float* a = acc + 12 * (q >> 1) + 4 * nt + 2 * (q & 1);
      sts64f(stg + (q * 3 + nt) * 256 + lane * 8, a[0], a[1]);
    }
}

__device__ __forceinline__ void tput(uint32_t tbl, int X, uint32_t h) {
  sts16(tbl + 2 * (1296 - X), (uint16_t)h);
  sts16(tbl + TBL_C1 + 2 * (1297 - X), (uint16_t)h);
}
__device__ __forceinline__ void ktab_build(uint32_t src, bool four, int q, uint32_t tbl, int lane) {
  const int tq = lane & 3, r = 8 * q + (lane >> 2);
  float v[6];
  src += q * 768 + lane * 8;
#pragma unroll
  for (int nt = 0; nt < 3; nt++) {
    const float2 a = lds64f(src + nt * 256), c = lds64f(src + nt * 256 + KSTG);
    v[2 * nt] = a.x + c.x; v[2 * nt + 1] = a.y + c.y;
  }
  if (four) {
#pragma unroll
    for (int nt = 0; nt < 3; nt++) {
      const float2 a = lds64f(src + nt * 256 + 2 * KSTG), c = lds64f(src + nt * 256 + 3 * KSTG);
      v[2 * nt] += a.x + c.x; v[2 * nt + 1] += a.y + c.y;
    }
  }
  const bool first = (r == 0);
  if (first && tq == 0) { v[0] += lds32f(tbl + TBL_SC + 12); sts32f(tbl + TBL_SC, v[4]); }
  const uint32_t h0 = pack_h2(v[0], v[1]), h1 = pack_h2(v[2], v[3]), h2 = pack_h2(v[4], v[5]);
  tput(tbl, 64 + 8 * r + 2 * tq, h0);
  tput(tbl, 65 + 8 * r + 2 * tq, h0 >> 16);
  const bool lo = tq < 2;
  const int Xd = 320 + 8 * r + 4 * tq, k2 = 32 * (tq - 2) + r;
  tput(tbl, lo ? Xd + 2 : 720 + k2, h1 >> 16);
  const bool sp = first && tq == 2;
  const int Xa = lo ? Xd : (sp ? 576 : 911 + k2);
  tput(tbl, Xa, h1);
  if (lo || sp) {
    tput(tbl, Xa + 1, h1);
    if (Xa != 320) tput(tbl, Xa - 1, h1);
  }
  if (sp) { tput(tbl, 578, h1); tput(tbl, 1295, h2); }
  if (lo) {
    const int X3 = ((r & 1) ? 1104 : 1231) + 32 * tq + (r >> 1);
    tput(tbl, X3 == 1231 ? 975 : X3, h2);
    tput(tbl, X3 + 16, h2 >> 16);
  }
}

__device__ __forceinline__ void sig_windows(uint32_t sig, int t) {
  uint32_t U[20];
#pragma unroll
  for (int c = 0; c < 5; c++) {
    const int kap = 2 * t - 3 + c + 72;
    const uint4 v = lds128(sig + SIG_U + (kap & 7) * U_LBO + (kap >> 3) * 16);
    U[4 * c] = v.x; U[4 * c + 1] = v.y; U[4 * c + 2] = v.z; U[4 * c + 3] = v.w;
  }
  uint32_t O[19], A2[17], A4[17], V2[8], V5[8];
#pragma unroll
  for (int i = 3; i < 19; i++) O[i] = __byte_perm(U[i - 1], U[i], 0x5432);
#pragma unroll
  for (int i = 3; i < 17; i++) A2[i] = hadd2u(U[i], O[i]);
#pragma unroll
  for (int i = 4; i < 17; i++) A4[i] = hadd2u(A2[i], A2[i - 1]);
#pragma unroll
  for (int k = 0; k < 8; k++) { V2[k] = hadd2u(O[11 + k], U[10 + k]); V5[k] = hadd2u(A4[9 + k], U[7 + k]); }
#pragma unroll
  for (int h = 0; h < 2; h++) {
    sts128(sig + SIG_V3 + t * 32 + h * 16, hadd2u(V2[4 * h], O[10 + 4 * h]), hadd2u(V2[4 * h + 1], O[11 + 4 * h]),
           hadd2u(V2[4 * h + 2], O[12 + 4 * h]), hadd2u(V2[4 * h + 3], O[13 + 4 * h]));
    sts128(sig + SIG_V5 + t * 32 + h * 16, V5[4 * h], V5[4 * h + 1], V5[4 * h + 2], V5[4 * h + 3]);
  }
  if (t < 64) {
    uint32_t V7[8], V9[8];
#pragma unroll
    for (int k = 0; k < 8; k++) {
      V7[k] = hadd2u(V5[k], hadd2u(O[10 + k], O[7 + k]));
      V9[k] = hadd2u(hadd2u(A4[6 + k], A4[4 + k]), U[2 + k]);
    }
#pragma unroll
    for (int h = 0; h < 2; h++) {
      sts128(sig + SIG_V7 + h * 1024 + t * 16, V7[4 * h], V7[4 * h + 1], V7[4 * h + 2], V7[4 * h + 3]);
      sts128(sig + SIG_V9 + h * 1024 + t * 16, V9[4 * h], V9[4 * h + 1], V9[4 * h + 2], V9[4 * h + 3]);
      sts128(sig + SIG_V2 + h * 1024 + t * 16, V2[4 * h], V2[4 * h + 1], V2[4 * h + 2], V2[4 * h + 3]);
    }
  }
}

__device__ __forceinline__ void conv_channel(uint32_t tbl, uint32_t sig, uint32_t y2b, uint32_t y3b, float k1024,
                                             int w, int lane, int barid, float* res) {
  const int g = lane >> 2, tq = lane & 3;
  const uint32_t tb = tbl + ((g & 1) ? TBL_C1 + 2 : 0) + 2 * (1296 - (g - 2 * tq)) - 32 * w + 112;
  float a2[12], a3[8];
#pragma unroll
  for (int i = 0; i < 16; i++) res[i] = 0.f;
#pragma unroll
  for (int i = 0; i < 12; i++) a2[i] = 0.f;
#pragma unroll
  for (int q = 0; q < 4; q++) {
    const float2 f = h2f(lds32(sig + SIG_V2 + (q >> 1) * 1024 + (16 * w + 8 * (q & 1) + g) * 16 + tq * 4));
    a3[2 * q] = k1024 * f.x;
    a3[2 * q + 1] = k1024 * f.y;
  }
  const uint64_t dU = mkdesc(sig + SIG_U, U_LBO, 128, 0);
  const uint64_t dV = mkdesc(sig, 128, 1024, 0);
  fence_regs<16>(res); fence_regs<12>(a2); fence_regs<8>(a3);
  constexpr int LB = 2 * U_LBO / 16;
  uint32_t Rd[75], R2[2][17], R3[2][9];
  auto load_group = [&](int gi) {
    const int it = gi >> 1, hb = gi & 1;
    if (gi == 0) Rd[0] = lds32(tb - 128);
#pragma unroll
    for (int i = 1; i < (gi == 17 ? 7 : 5); i++) Rd[4 * gi + i] = lds32(tb - 128 - 16 * (4 * gi + i));
    if (gi < 16) {
      const int sg = it >> 2, n2 = gi & 7;
      if (n2 == 0) R2[sg][0] = lds32(tb - 1440 - 384 * sg);
      R2[sg][2 * n2 + 1] = lds32(tb - 1440 - 384 * sg - 16 * (2 * n2 + 1));
      R2[sg][2 * n2 + 2] = lds32(tb - 1440 - 384 * sg - 16 * (2 * n2 + 2));
      if (!hb) {
        const int n3 = it & 3;
        if (n3 == 0) R3[sg][0] = lds32(tb - 2208 - 256 * sg);
        R3[sg][2 * n3 + 1] = lds32(tb - 2208 - 256 * sg - 16 * (2 * n3 + 1));
        R3[sg][2 * n3 + 2] = lds32(tb - 2208 - 256 * sg - 16 * (2 * n3 + 2));
      }
    }
  };
  auto dense = [&](int n) {
    wg_rs_f16_n32k(res, Rd[2 * n + 1], Rd[2 * n + 2], Rd[2 * n], Rd[2 * n + 1], dU + ((3 - (n & 3)) * LB + 9 - (n >> 2)), 1);
  };
  load_group(0);
  load_group(1);
#pragma unroll
  for (int gi = 0; gi < 18; gi++) {
    const int it = gi >> 1, sg = it >> 2, n2 = gi & 7, n3 = it & 3;
    wg_fence();
    dense(2 * gi);
    if (gi < 16)
      wg_rs_f16_n24t(a2, R2[sg][2 * n2 + 1], R2[sg][2 * n2 + 2], R2[sg][2 * n2], R2[sg][2 * n2 + 1],
                     dV + ((SIG_V3 + 768) / 16 + 256 * sg - 16 * (n2 & 3) - 64 * (n2 >> 2)), 1);
    dense(2 * gi + 1);
    if (gi < 16 && !(gi & 1))
      wg_rs_f16_n16t(a3, R3[sg][2 * n3 + 1], R3[sg][2 * n3 + 2], R3[sg][2 * n3], R3[sg][2 * n3 + 1],
                     dV + ((SIG_V7 + 768) / 16 + 128 * sg - 16 * n3), 1);
    if (gi == 17) dense(36);
    wg_commit();
    if (gi < 16) { wg_wait<1>(); load_group(gi + 2); }
  }
  wg_wait<2>();
  fence_regs<12>(a2); fence_regs<8>(a3);
  bar_sync(barid, 128);
  {
    const uint32_t o2 = y2b + (136 * w + 8 * g + 2 * tq) * 4, o3 = y3b + (272 * w + 16 * g + 2 * tq) * 4;
#pragma unroll
    for (int q = 0; q < 6; q++) sts64f(o2 + (544 * (q >> 1) + 64 * (q & 1)) * 4, a2[2 * q], a2[2 * q + 1]);
#pragma unroll
    for (int q = 0; q < 4; q++) sts64f(o3 + (8 * (q >> 1) + 136 * (q & 1)) * 4, a3[2 * q], a3[2 * q + 1]);
  }
  bar_sync(barid, 128);
  const uint32_t go = (136 * tq + 16 * w + g) * 4;
  float ex[12];
#pragma unroll
  for (int i = 0; i < 12; i++) {
    const int o = 544 * (i >> 2) + 64 * (i & 1) + 8 * ((i >> 1) & 1);
    ex[i] = lds32f(y2b + go + o * 4);
    if (i >= 4) ex[i] += lds32f(y3b + go + (o - 544) * 4);
  }
  wg_wait<0>();
  fence_regs<16>(res);
#pragma unroll
  for (int i = 0; i < 12; i++) res[4 + i] += ex[i];
}

__device__ __forceinline__ void red16x2(float& a, float& c) {
#pragma unroll
  for (int o = 1; o < 16; o <<= 1) { a += __shfl_xor_sync(0xffffffffu, a, o); c += __shfl_xor_sync(0xffffffffu, c, o); }
}
__device__ __forceinline__ void ln_rows(uint32_t* u, int row, uint32_t stg_row, uint32_t tag2, int lane) {
  const int j = lane & 15;
  const float piv = __shfl_sync(0xffffffffu, bf_lo(u[0]), lane & 16);
  float s0 = 0.f, s1 = 0.f, q0 = 0.f, q1 = 0.f;
#pragma unroll
  for (int i = 0; i < 14; i++) {
    const float a = bf_lo(u[i]) - piv, c = bf_hi(u[i]) - piv;
    s0 += a; s1 += c; q0 = fmaf(a, a, q0); q1 = fmaf(c, c, q1);
  }
  float s = s0 + s1, q = q0 + q1;
  red16x2(s, q);
  s *= (1.f / D_); q *= (1.f / D_);
  const __nv_bfloat16 m1b = __float2bfloat16_rn(s + piv);
  const __nv_bfloat162 m1v = __halves2bfloat162(m1b, m1b);
  const float den = rbf(sqrtf_(rbf(rbf(fmaxf(fmaf(-s, s, q), 0.f)) + 1e-5f)));
  const float rden = rcpf_(den);
  s0 = s1 = q0 = q1 = 0.f;
#pragma unroll
  for (int i = 0; i < 14; i++) {
    const __nv_bfloat162 cv = __hsub2(*reinterpret_cast<__nv_bfloat162*>(&u[i]), m1v);
    const uint32_t c = *reinterpret_cast<const uint32_t*>(&cv);
    const uint32_t n = pack_bf2(bf_lo(c) * rden, bf_hi(c) * rden);
    const float a = bf_lo(n), e = bf_hi(n);
    s0 += a; s1 += e; q0 = fmaf(a, a, q0); q1 = fmaf(e, e, q1);
    u[i] = (pack_h2(a, e) & 0xfffefffeu) | tag2;
  }
#pragma unroll
  for (int i = 0; i < 7; i++)
    asm volatile("st.shared.v2.b32 [%0], {%1,%2};" ::"r"(stg_row + (j + 16 * i) * 8), "r"(u[2 * i]), "r"(u[2 * i + 1]) : "memory");
  s = s0 + s1; q = q0 + q1;
  red16x2(s, q);
  s *= (1.f / D_); q *= (1.f / D_);
  const float den2 = rbf(sqrtf_(rbf(rbf(fmaxf(fmaf(-s, s, q), 0.f)) + 1e-5f)));
  if (j == 0) {
    const float ir = den * den2, mu = fmaf(rbf(s), den, __bfloat162float(m1b));
    const float ih = rbf(ir), mh = rbf(mu), ml = rbf(mu - mh);
    g_ax[row] = make_uint4(pack_bf2(ih, ir - ih), pack_bf2(mh, mh), pack_bf2(ml, ml), pack_bf2(mh, mu - mh - ml));
    g_r[row] = rcpf_(ir);
  }
}

template <int NV, int STRIDE>
__device__ __forceinline__ void recv_part(const uint4* src, uint32_t tag, float* pre) {
  uint4 v[NV];
#pragma unroll 1
  for (int it = 0; it < SPIN_MAX; it++) {
    uint32_t bad = 0;
#pragma unroll
    for (int q = 0; q < NV; q++) v[q] = ld_b128(src + q * STRIDE);
#pragma unroll
    for (int q = 0; q < NV; q++) bad |= v[q].x ^ tag;
    if (!(bad & 1)) break;
    __nanosleep(20);
  }
#pragma unroll
  for (int q = 0; q < NV; q++) {
    const uint32_t u[4] = {v[q].x, v[q].y, v[q].z, v[q].w};
#pragma unroll
    for (int k = 0; k < 4; k++) { pre[8 * q + 2 * k] += bf_lo(u[k]); pre[8 * q + 2 * k + 1] += bf_hi(u[k]); }
  }
}
__device__ __forceinline__ void send_part(uint4* dst, uint32_t tag, const float* a) {
#pragma unroll
  for (int q = 0; q < 4; q++)
    st_b128(dst + q * 256, tag, pack_bf2(a[8 * q], a[8 * q + 1]), pack_bf2(a[8 * q + 2], a[8 * q + 3]),
            pack_bf2(a[8 * q + 4], a[8 * q + 5]), pack_bf2(a[8 * q + 6], a[8 * q + 7]));
}
__device__ __forceinline__ bool last_release(uint32_t cnt) {
  unsigned old;
  asm volatile("atom.relaxed.cta.shared.inc.u32 %0, [%1], 7;" : "=r"(old) : "r"(cnt) : "memory");
  return old == 7;
}
__device__ __forceinline__ int mod7(int v) { return v >= 7 ? v - 7 : v; }

#define IDS const int tid = opaque(tid0), lane = tid & 31, t = tid & 127, wg = tid >> 7, w = (tid >> 5) & 3; \
            (void)lane; (void)t; (void)wg; (void)w;

__global__ void __launch_bounds__(384, 1)
fused_kernel(const __grid_constant__ CUtensorMap tm_x, const __grid_constant__ CUtensorMap tm_w1,
             const __grid_constant__ CUtensorMap tm_w2, const __grid_constant__ CUtensorMap tm_out, const Params p) {
  extern __shared__ __align__(1024) uint8_t smem_raw[];
  const uint32_t sb = smem_u32(smem_raw);
  const uint32_t ms = sb + OFF_M;
  const uint32_t bar0 = ms + M_BAR;
  const int tid0 = threadIdx.x;
  const int b = blockIdx.x;
  const bool is_ssm = b >= NMLP;
  const int G = b / NRK, rk = b - G * NRK;
  const int kc0 = (G + rk) % 7;
  TSTAMP(0);
  {
    IDS
    const bool kg = is_ssm || wg < 2 || b < 104;
    KgIn kin;
    if (kg) {
      const int d = is_ssm ? 2 * (112 + 3 * (b - NMLP) + wg) + (w >> 1) : (wg < 2 ? 2 * b + wg : 344 + b);
      kgen_load(p, d, is_ssm ? 2 * (w & 1) : w, is_ssm ? 2 : 1, lane, kin);
    }
    if (tid == 256) {
      const unsigned epoch = *(volatile unsigned*)&g_epoch;
#pragma unroll 1
      for (int i = 0; i < 16; i++) { mbar_init(bar0 + 8 * i, 1); asm volatile("st.shared.b32 [%0], 0;" ::"r"(ms + M_REL + 4 * i) : "memory"); }
      asm volatile("fence.mbarrier_init.release.cluster;" ::: "memory");
      fence_async();
      if (!is_ssm) {
#pragma unroll 1
        for (int s = 0; s < 3; s++) {
          const int kc = mod7(kc0 + s);
          mbar_expect(bar0 + 8 * s, 49152);
          tma_2d(sb + OFF_X + s * 16384, &tm_x, 64 * kc, 128 * G, bar0 + 8 * s);
          tma_3d(sb + OFF_W + s * 32768, &tm_w1, 0, 64 * kc, 4 * rk, bar0 + 8 * s);
        }
      }
      asm volatile("st.shared.b32 [%0], %1;" ::"r"(ms + M_EP), "r"(epoch + 1) : "memory");
    }
    if (kg) {
      const uint32_t stg = is_ssm ? sb + S_WORK + wg * S_WGB + w * KSTG : sb + (wg < 2 ? OFF_A + 4 * wg * KSTG : OFF_B) + w * KSTG;
      const uint32_t tbl = is_ssm ? sb + (4 * wg + (w >> 1)) * TBL : sb + OFF_T + wg * TBL;
#pragma unroll 1
      for (int i = is_ssm ? t & 63 : t; i < TBL_SC / 16; i += is_ssm ? 64 : 128) sts128(tbl + i * 16, 0u, 0u, 0u, 0u);
      kgen_warp(kin, is_ssm ? 2 : 1, stg, tbl, lane);
    }
  }
  TSTAMP(1);

  if (is_ssm || __shfl_sync(0xffffffffu, tid0 >> 7, 0) == 2) {
    asm volatile("setmaxnreg.dec.sync.aligned.u32 120;");
    if (!is_ssm) bar_arrive(7, 384);
    {
      IDS
      uint32_t u[14], un[14];
      uint4 wv[7];
      const int rl0 = 4 * w + (lane >> 4);
      if (!is_ssm) {
        const uint2* xr = (const uint2*)(p.x + (size_t)(16 * b + rl0) * D_) + (lane & 15);
#pragma unroll
        for (int i = 0; i < 7; i++) {
          const uint2 v = __ldg(xr + 16 * i), v2 = __ldg(xr + 16 * i + 2 * (D_ / 4));
          u[2 * i] = v.x; u[2 * i + 1] = v.y; un[2 * i] = v2.x; un[2 * i + 1] = v2.y;
        }
        const uint4* wr = (const uint4*)(p.w1 + (size_t)(t >> 1) * F_ + 16 * b) + (t & 1);
#pragma unroll
        for (int i = 0; i < 7; i++) wv[i] = __ldg(wr + (size_t)i * 64 * (F_ / 8));
        if (t == 0)
          asm volatile("cp.async.bulk.prefetch.L2.global [%0], %1;" ::"l"(p.w2 + (size_t)(256 * rk + 16 * G) * D_), "r"(16 * D_ * 2) : "memory");
        if (b >= 104) bar_sync(6, 128);
      }
#pragma unroll 1
      for (int ph = 0; ph < 2; ph++) {
        if (ph == (b >= 104 && !is_ssm)) {
          bar_sync(1, 384);
          const int nc = is_ssm ? 2 : (b < 104 ? 3 : 2);
#pragma unroll 1
          for (int c = nc - 1; c >= 0; c--) {
            const uint32_t src = is_ssm ? sb + S_WORK + wg * S_WGB + 2 * c * KSTG : sb + (c < 2 ? OFF_A + 4 * c * KSTG : OFF_B);
            ktab_build(src, !is_ssm, w, (is_ssm ? sb + 4 * wg * TBL : sb + OFF_T) + c * TBL, lane);
          }
          fence_async();
          bar_sync(4 + wg, 128);
          if (t == 0 && b < 104) { bulk_s2g(g_tbl + b * (TBL / 16), sb + OFF_T + 2 * TBL, TBL); bulk_commit(); }
          TSTAMP(2);
        } else if (!is_ssm) {
          const uint32_t tag2 = (lds32(ms + M_EP) & 1) * 0x10001u;
          const float b1v = t < 16 ? __bfloat162float(p.b1[16 * b + t]) : 0.f;
          const int nit = b >= 104 ? 6 : 2;
#pragma unroll 1
          for (int i = 0; i < nit; i++) {
            const int rb = i < 2 ? b : 2 * b - 97 + (i >> 1), rl = rl0 + 2 * (i & 1);
            ln_rows(u, 16 * rb + rl, sb + OFF_B + rl * 912, tag2, lane);
#pragma unroll
            for (int k = 0; k < 14; k++) u[k] = un[k];
            if (i + 2 < nit) {
              const uint2* xr = (const uint2*)(p.x + (size_t)(16 * (2 * b - 96 + (i >> 1)) + rl) * D_) + (lane & 15);
#pragma unroll
              for (int k = 0; k < 7; k++) { const uint2 v = __ldg(xr + 16 * k); un[2 * k] = v.x; un[2 * k + 1] = v.y; }
            }
            if (i & 1) {
              bar_sync(6, 128);
              const uint32_t la = sb + OFF_B + (lane & 15) * 912 + (lane >> 4) * 16 + w * 224;
              uint2* dst = (uint2*)(g_xnT + (size_t)rb * 896) + lane + w * 448;
#pragma unroll
              for (int k = 0; k < 7; k++) {
                uint32_t r0, r1, r2, r3;
                ldsm4t(la + k * 32, r0, r1, r2, r3);
                st_relaxed2(dst + k * 64, r0, r1);
                st_relaxed2(dst + k * 64 + 32, r2, r3);
              }
              bar_sync(6, 128);
            }
          }
          TSTAMP(10);
          float cs[8];
#pragma unroll
          for (int k = 0; k < 8; k++) cs[k] = 0.f;
#pragma unroll
          for (int i = 0; i < 7; i++) {
            const uint32_t uu[4] = {wv[i].x, wv[i].y, wv[i].z, wv[i].w};
#pragma unroll
            for (int k = 0; k < 4; k++) { cs[2 * k] += bf_lo(uu[k]); cs[2 * k + 1] += bf_hi(uu[k]); }
          }
#pragma unroll
          for (int st = 0; st < 3; st++) {
            const int n = 4 >> st;
            const bool up = (lane >> (3 - st)) & 1;
#pragma unroll
            for (int k = 0; k < n; k++) {
              const float give = up ? cs[k] : cs[k + n], keep = up ? cs[k + n] : cs[k];
              cs[k] = keep + __shfl_xor_sync(0xffffffffu, give, 8 >> st);
            }
          }
          cs[0] += __shfl_xor_sync(0xffffffffu, cs[0], 16);
          if (lane < 16) sts32f(ms + M_CSR + (w * 16 + (lane & 1) * 8 + (lane >> 1)) * 4, cs[0]);
          bar_sync(6, 128);
          if (t < 16) {
            const uint32_t a = ms + M_CSR + t * 4;
            const float c = -0.5f * ((lds32f(a) + lds32f(a + 64)) + (lds32f(a + 128) + lds32f(a + 192)));
            const float ch = rbf(c), cl = rbf(c - ch);
            const uint32_t hl = pack_bf2(ch, cl);
            g_bx[16 * b + t] = make_uint4(pack_bf2(0.5f * b1v, 0.5f * b1v), hl, hl, pack_bf2(c - ch - cl, ch));
          }
          __syncwarp();
          TSTAMP(11);
        }
      }
      if (tid == 256) { bulk_wait0(); red_release(&g_cntA); }
    }
    TSTAMP(3);
#pragma unroll 1
    for (int pi = 0; pi < 2; pi++) {
      {
        IDS
        if (pi == 1 && (!is_ssm || (b >= NMLP + 12 && wg == 2))) break;
        const unsigned ep1 = lds32(ms + M_EP);
        const int pair = !is_ssm ? b : (pi == 0 ? 112 + 3 * (b - NMLP) : (b < NMLP + 12 ? 172 + 3 * (b - NMLP) : 184 + 2 * (b - NMLP))) + wg;
        const uint32_t work = is_ssm ? sb + S_WORK + wg * S_WGB : sb + OFF_A;
        const uint32_t z = work + SIG_V3 - 1024 + (t >> 6) * 4096 + (t & 63) * 16;
        sts128(z, 0u, 0u, 0u, 0u); sts128(z + SIG, 0u, 0u, 0u, 0u);
        if (t < 72) {
          const uint32_t zu = work + SIG_U + (t & 7) * U_LBO + (t >> 3) * 16;
          sts128(zu, 0u, 0u, 0u, 0u); sts128(zu + SIG, 0u, 0u, 0u, 0u);
        }
        const uint4* src = g_xnT + ((size_t)t * 448 + 2 * pair) * 2;
        uint4 v[4];
#pragma unroll 1
        for (int it = 0; it < SPIN_MAX; it++) {
#pragma unroll
          for (int q = 0; q < 4; q++) v[q] = ld_relaxed4(src + q);
          uint32_t bad = 0;
#pragma unroll
          for (int q = 0; q < 4; q++) bad |= (v[q].x ^ ep1) | (v[q].y ^ ep1) | (v[q].z ^ ep1) | (v[q].w ^ ep1);
          if (!(bad & 1)) break;
          __nanosleep(100);
        }
        TSTAMP(5);
        const uint32_t a = work + SIG_U + (2 * (t & 3)) * U_LBO + ((t >> 2) + 9) * 16, M = 0xfffefffeu;
        sts128(a, v[0].x & M, v[0].z & M, v[1].x & M, v[1].z & M);
        sts128(a + U_LBO, v[0].y & M, v[0].w & M, v[1].y & M, v[1].w & M);
        sts128(a + SIG, v[2].x & M, v[2].z & M, v[3].x & M, v[3].z & M);
        sts128(a + SIG + U_LBO, v[2].y & M, v[2].w & M, v[3].y & M, v[3].w & M);
        bar_sync(4 + wg, 128);
#pragma unroll 1
        for (int k = w; k < 6; k += 4) sig_windows(work + (k & 1) * SIG, (k >> 1) * 32 + lane);
        fence_async();
        if (t == 96 && pi == 0) {
          wait_count(&g_cntA, ep1 * NCTA);
          if (b == 0) *(volatile unsigned*)&g_epoch = ep1;
          asm volatile("fence.proxy.async;" ::: "memory");
          if (!is_ssm) {
            mbar_expect(bar0 + 8 * 15, 2048 + 4096 + 512);
            bulk_g2s(sb + OFF_B + B_AX, g_ax + 128 * G, 2048, bar0 + 8 * 15);
            bulk_g2s(sb + OFF_B + B_BX, g_bx + 256 * rk, 4096, bar0 + 8 * 15);
            bulk_g2s(sb + OFF_B + B_R, g_r + 128 * G, 512, bar0 + 8 * 15);
          } else if (b < NMLP + 12 || wg < 2) {
            const int j = (b < NMLP + 12 ? 3 * (b - NMLP) : 2 * (b - NMLP) + 12) + wg;
            mbar_expect(bar0 + 8 * wg, 2 * TBL);
            bulk_g2s(sb + (4 * wg + 2) * TBL, g_tbl + 2 * j * (TBL / 16), 2 * TBL, bar0 + 8 * wg);
          }
        }
        if (pi == 1) mbar_wait(bar0 + 8 * wg, 0);
        TSTAMP(6);
        bar_sync(is_ssm ? 4 + wg : 3, is_ssm ? 128 : 384);
        TSTAMP(7);
      }
      uint32_t keep[8];
      float res[16];
#pragma unroll 1
      for (int c = 0; c < 2; c++) {
        IDS
        const int wgu = __shfl_sync(0xffffffffu, wg, 0);
        const uint32_t work = is_ssm ? sb + S_WORK + wgu * S_WGB : sb + OFF_A;
        const uint32_t tbl = (is_ssm ? sb + (4 * wgu + 2 * pi) * TBL : sb + OFF_T) + c * TBL;
        conv_channel(tbl, work + c * SIG, is_ssm ? work + 2 * SIG + Y3B : sb + OFF_B, work + 2 * SIG, lds32f(tbl + TBL_SC), w, lane, 4 + wgu, res);
        const float os = lds32f(tbl + TBL_SC + 8);
        if (c == 0) {
#pragma unroll
          for (int i = 0; i < 8; i++) keep[i] = pack_bf2(res[2 * i] * os, res[2 * i + 1] * os);
        } else {
          const int pair = !is_ssm ? b : (pi == 0 ? 112 + 3 * (b - NMLP) : (b < NMLP + 12 ? 172 + 3 * (b - NMLP) : 184 + 2 * (b - NMLP))) + wg;
          uint4* dst = g_s2 + ((size_t)(lane & 3) * 224 + pair) * 32 + w * 8 + (lane >> 2);
          const uint32_t tag = lds32(ms + M_EP) & 1;
#pragma unroll
          for (int nt = 0; nt < 4; nt++) {
            const uint32_t n0 = pack_bf2(res[4 * nt] * os, res[4 * nt + 1] * os), n1 = pack_bf2(res[4 * nt + 2] * os, res[4 * nt + 3] * os);
            st_b128(dst + nt * 4 * 224 * 32, tag, __byte_perm(keep[2 * nt], n0, 0x5410), __byte_perm(keep[2 * nt + 1], n1, 0x5410),
                    __byte_perm(keep[2 * nt], n0, 0x7632), __byte_perm(keep[2 * nt + 1], n1, 0x7632));
          }
        }
      }
      TSTAMP(8 + pi);
    }
    if (!is_ssm) {
      IDS
      const uint32_t tag = lds32(ms + M_EP) & 1;
      float pre[64];
#pragma unroll
      for (int i = 0; i < 64; i++) pre[i] = 0.f;
#pragma unroll 1
      for (int s = 0; s < 4; s++) recv_part<8, 128>(g_part + ((size_t)b * 6 + s) * 1024 + t, tag, pre);
      bar_sync(6, 128);
#pragma unroll
      for (int i = 0; i < 16; i++)
        sts128(sb + OFF_A + ((2 * (i >> 2) + (i & 1)) * 256 + ((i >> 1) & 1) * 128 + t) * 16, __float_as_uint(pre[4 * i]),
               __float_as_uint(pre[4 * i + 1]), __float_as_uint(pre[4 * i + 2]), __float_as_uint(pre[4 * i + 3]));
      bar_arrive(2, 384);
      TSTAMP(12);
    }
  } else {
    bar_arrive(1, 384);
    asm volatile("setmaxnreg.inc.sync.aligned.u32 192;");
    bar_sync(7, 384);
    uint32_t H[64];
    {
      float acc[128];
      float p0, q0, p1, q1;
      {
        IDS
        const int wgu = __shfl_sync(0xffffffffu, wg, 0);
        int sl = 0;
#pragma unroll 1
        for (int s = 0; s < 7; s++) {
          mbar_wait(bar0 + 8 * s, 0);
          const uint64_t da = mkdesc(sb + OFF_X + sl * 16384 + wgu * 8192, 16, 1024, 1);
          const uint64_t db = mkdesc(sb + OFF_W + sl * 32768, 8192, 1024, 1);
          wg_fence();
#pragma unroll
          for (int k = 0; k < 4; k++) wg_ss_bf16_n256(acc, da + 2 * k, db + 128 * k, (s | k) != 0);
          wg_commit();
          wg_wait<1>();
          const int pl = sl == 0 ? 2 : sl - 1;
          sl = sl == 2 ? 0 : sl + 1;
          if (s > 0 && lane == 0 && last_release(ms + M_REL + 4 * s)) {
            const uint32_t bx = bar0 + 8 * (s < 5 ? s + 2 : 14);
            mbar_expect(bar0 + 8 * (s + 2), s < 5 ? 49152 : 32768);
            if (s < 5) tma_3d(sb + OFF_W + pl * 32768, &tm_w1, 0, 64 * mod7(kc0 + s + 2), 4 * rk, bar0 + 8 * (s + 2));
            else tma_2d(sb + OFF_W + pl * 32768, &tm_w2, 64 * mod7(rk + s - 4), 256 * rk, bar0 + 8 * (s + 2));
            if (s == 6) mbar_expect(bx, 16384);
            if (s != 5) tma_2d(sb + OFF_X + pl * 16384, &tm_x, 64 * (s < 5 ? mod7(kc0 + s + 2) : rk), 128 * G, bx);
          }
        }
        TSTAMP(9);
        mbar_wait(bar0 + 8 * 15, 0);
        wg_fence();
        wg_ss_bf16_n256k(acc, mkdesc(sb + OFF_B + B_AX + wgu * 1024, 0, 128, 0), mkdesc(sb + OFF_B + B_BX, 0, 128, 0), 1);
        wg_commit();
        wg_wait<1>();
        if (lane == 0 && last_release(ms + M_REL + 4 * 7)) {
#pragma unroll 1
          for (int c = 2; c < 4; c++) {
            mbar_expect(bar0 + 8 * (7 + c), 32768);
            tma_2d(sb + (c - 2) * OFF_X, &tm_w2, 64 * mod7(rk + 1 + c), 256 * rk, bar0 + 8 * (7 + c));
          }
        }
        bar_arrive(3, 384);
        const float r0 = lds32f(sb + OFF_B + B_R + (16 * (tid >> 5) + (lane >> 2)) * 4);
        const float r1 = lds32f(sb + OFF_B + B_R + (16 * (tid >> 5) + (lane >> 2) + 8) * 4);
        p0 = 0.7978845608028654f * r0; q0 = 0.0356774081363001f * r0 * r0 * r0;
        p1 = 0.7978845608028654f * r1; q1 = 0.0356774081363001f * r1 * r1 * r1;
      }
      wg_wait<0>();
      fence_regs<128>(acc);
      TSTAMP(2);
      float hq[4];
#pragma unroll
      for (int i = 0; i < 64; i++) {
        const float pp = (i & 1) ? p1 : p0, qq = (i & 1) ? q1 : q0;
        const float a = acc[2 * i], c = acc[2 * i + 1];
        const float ta = tanhf_(a * fmaf(a * a, qq, pp)), tc = tanhf_(c * fmaf(c * c, qq, pp));
        if (i >= 2) H[i - 2] = pack_bf2v(hq[(i & 1) * 2], hq[(i & 1) * 2 + 1]);
        hq[(i & 1) * 2] = fmaf(a, ta, a); hq[(i & 1) * 2 + 1] = fmaf(c, tc, c);
      }
      H[62] = pack_bf2v(hq[0], hq[1]); H[63] = pack_bf2v(hq[2], hq[3]);
    }
    TSTAMP(3);
    float accA[32], accB[32];
    const uint32_t tag = lds32(ms + M_EP) & 1;
    auto issue2 = [&](int c, float* acc) {
      const uint32_t base = sb + ((0x0213021u >> (4 * c)) & 3) * 32768;
      mbar_wait(bar0 + 8 * (7 + c), 0);
      const uint64_t db = mkdesc(base, 8192, 1024, 1);
      wg_fence();
#pragma unroll
      for (int k = 0; k < 16; k++) wg_rs_bf16_n64(acc, H[4 * k], H[4 * k + 1], H[4 * k + 2], H[4 * k + 3], db + 128 * k, k != 0);
      wg_commit();
    };
    auto process = [&](int s, float* acc) {
      wg_wait<1>();
      fence_regs<32>(acc);
      const int tid = opaque(tid0);
      if (s < 3 && (tid & 31) == 0 && last_release(ms + M_REL + 4 * (8 + s))) {
        mbar_expect(bar0 + 8 * (11 + s), 32768);
        tma_2d(sb + ((0x021u >> (4 * s)) & 3) * 32768, &tm_w2, 64 * mod7(mod7(rk + 5 + s)), 256 * rk, bar0 + 8 * (11 + s));
      }
      send_part(g_part + ((size_t)(G * 7 + mod7(rk + 1 + s)) * 6 + s) * 1024 + tid, tag, acc);
      TSTAMP(10 + s);
    };
    issue2(0, accA);
#pragma unroll
    for (int s = 0; s < 6; s += 2) {
      issue2(s + 1, accB);
      process(s, accA);
      issue2(s + 2, accA);
      process(s + 1, accB);
    }
    TSTAMP(4);
    IDS
    const int g = lane >> 2, tq = lane & 3;
    uint32_t sw[16];
    {
      const uint4* sp = g_s2 + ((size_t)G * 224 + 32 * rk + tq) * 32 + w * 8 + g;
#pragma unroll 1
      for (int it = 0; it < SPIN_MAX; it++) {
        uint32_t bad = 0;
#pragma unroll
        for (int i = 0; i < 8; i++) {
          const uint4 v = ld_b128(sp + i * 4 * 32);
          bad |= v.x ^ tag;
          sw[2 * i] = wg ? v.z : v.x; sw[2 * i + 1] = wg ? v.w : v.y;
        }
        if (!(bad & 1)) break;
        __nanosleep(40);
      }
    }
    TSTAMP(5);
    uint32_t b2w[8];
#pragma unroll
    for (int i = 0; i < 8; i++) b2w[i] = __ldg((const uint32_t*)(p.b2 + 64 * rk) + 4 * i + tq);
    wg_wait<0>();
    fence_regs<32>(accA);
    TSTAMP(6);
    bar_sync(2, 384);
#pragma unroll
    for (int i = 0; i < 8; i++) {
      const uint4 v = lds128(sb + OFF_A + (i * 256 + tid) * 16);
      accA[4 * i] += __uint_as_float(v.x); accA[4 * i + 1] += __uint_as_float(v.y);
      accA[4 * i + 2] += __uint_as_float(v.z); accA[4 * i + 3] += __uint_as_float(v.w);
    }
    mbar_wait(bar0 + 8 * 14, 0);
    const uint32_t xa = sb + OFF_X + 2 * 16384 + (16 * (tid >> 5) + (lane & 15)) * 128;
    uint32_t xw[16];
#pragma unroll
    for (int q = 0; q < 4; q++) ldsm4(xa + (((2 * q + (lane >> 4)) ^ (lane & 7)) << 4), xw[4 * q], xw[4 * q + 1], xw[4 * q + 2], xw[4 * q + 3]);
    const float r0 = 0.5f * lds32f(sb + OFF_B + B_R + (16 * (tid >> 5) + g) * 4);
    const float r1 = 0.5f * lds32f(sb + OFF_B + B_R + (16 * (tid >> 5) + g + 8) * 4);
#pragma unroll 1
    for (int s = 4; s < 6; s++) recv_part<4, 256>(g_part + ((size_t)b * 6 + s) * 1024 + tid, tag, accA);
    TSTAMP(7);
#pragma unroll
    for (int k = 0; k < 16; k++) {
      const float rr = (k & 1) ? r1 : r0;
      const float o0 = fmaf(accA[2 * k], rr, bf_lo(b2w[k >> 1])), o1 = fmaf(accA[2 * k + 1], rr, bf_hi(b2w[k >> 1]));
      const float g0 = o0 * rcpf_(1.f + ex2f(o0 * -1.4426950408889634f)), g1 = o1 * rcpf_(1.f + ex2f(o1 * -1.4426950408889634f));
      xw[k] = pack_bf2(fmaf(bf_lo(sw[k]), g0, bf_lo(xw[k])), fmaf(bf_hi(sw[k]), g1, bf_hi(xw[k])));
    }
#pragma unroll
    for (int q = 0; q < 4; q++) stsm4(xa + (((2 * q + (lane >> 4)) ^ (lane & 7)) << 4), xw[4 * q], xw[4 * q + 1], xw[4 * q + 2], xw[4 * q + 3]);
    fence_async();
    __syncwarp();
    if (lane == 0) {
      tma_store_2d(&tm_out, sb + OFF_X + 2 * 16384 + (tid >> 5) * 2048, 64 * rk, 128 * G + 16 * (tid >> 5));
      bulk_commit();
      bulk_wait0_read();
    }
    TSTAMP(8);
  }
}

typedef CUresult (*EncodeFn)(CUtensorMap*, CUtensorMapDataType, cuuint32_t, void*, const cuuint64_t*, const cuuint64_t*,
                             const cuuint32_t*, const cuuint32_t*, CUtensorMapInterleave, CUtensorMapSwizzle,
                             CUtensorMapL2promotion, CUtensorMapFloatOOBfill);

void make_map(EncodeFn fn, CUtensorMap* m, const void* ptr, int rank, const cuuint64_t* dims, const cuuint64_t* strides, const cuuint32_t* box) {
  const cuuint32_t es[3] = {1, 1, 1};
  fn(m, CU_TENSOR_MAP_DATA_TYPE_BFLOAT16, rank, const_cast<void*>(ptr), dims, strides, box, es, CU_TENSOR_MAP_INTERLEAVE_NONE,
     CU_TENSOR_MAP_SWIZZLE_128B, CU_TENSOR_MAP_L2_PROMOTION_L2_128B, CU_TENSOR_MAP_FLOAT_OOB_FILL_NONE);
}

}

extern "C" void kernel_launch(void* const* d_in, const int* in_sizes, int n_in, void* d_out, int out_size) {
  (void)in_sizes; (void)n_in; (void)out_size;
  void* fnp = nullptr;
  cudaDriverEntryPointQueryResult qr;
  cudaGetDriverEntryPoint("cuTensorMapEncodeTiled", &fnp, cudaEnableDefault, &qr);
  EncodeFn fn = (EncodeFn)fnp;
  Params p;
  p.x = (const __nv_bfloat16*)d_in[0];
  p.a_re = (const __nv_bfloat16*)d_in[1]; p.a_im = (const __nv_bfloat16*)d_in[2];
  p.b_re = (const __nv_bfloat16*)d_in[3]; p.b_im = (const __nv_bfloat16*)d_in[4];
  p.c_re = (const __nv_bfloat16*)d_in[5]; p.c_im = (const __nv_bfloat16*)d_in[6];
  p.log_dt = (const __nv_bfloat16*)d_in[7]; p.dskip = (const __nv_bfloat16*)d_in[8];
  p.w1 = (const __nv_bfloat16*)d_in[10]; p.b1 = (const __nv_bfloat16*)d_in[11];
  p.w2 = (const __nv_bfloat16*)d_in[12]; p.b2 = (const __nv_bfloat16*)d_in[13];
  CUtensorMap mx, mw1, mw2, mo;
  {
    const cuuint64_t dims[2] = {448, 2048}, str[1] = {896};
    const cuuint32_t box[2] = {64, 128}, boxo[2] = {64, 16};
    make_map(fn, &mx, p.x, 2, dims, str, box);
    make_map(fn, &mo, d_out, 2, dims, str, boxo);
  }
  {
    const cuuint64_t dims[3] = {64, 448, 28}, str[2] = {3584, 128};
    const cuuint32_t box[3] = {64, 64, 4};
    make_map(fn, &mw1, p.w1, 3, dims, str, box);
  }
  {
    const cuuint64_t dims[2] = {448, 1792}, str[1] = {896};
    const cuuint32_t box[2] = {64, 256};
    make_map(fn, &mw2, p.w2, 2, dims, str, box);
  }
  cudaFuncSetAttribute(fused_kernel, cudaFuncAttributeMaxDynamicSharedMemorySize, SMEM_BYTES);
  fused_kernel<<<NCTA, 384, SMEM_BYTES>>>(mx, mw1, mw2, mo, p);
}
```

```cpp
#include <cuda_runtime.h>
#include <cuda_bf16.h>
#include <cuda_fp16.h>
#include <cuda.h>
#include <stdint.h>

namespace {

constexpr int D_ = 448, NST = 256, F_ = 1792;
constexpr int NRK = 7, NMLP = 112, NCTA = 132;
constexpr int SPIN_MAX = 1 << 20, RETRY_MAX = 512;

__device__ uint4 g_xnT[128 * 448 * 2];
__device__ uint4 g_ax[2048];
__device__ float g_r[2048];
__device__ uint4 g_bx[F_];
__device__ uint4 g_part[16 * 7 * 6 * 1024];
__device__ uint4 g_s2[16 * 224 * 32];
__device__ uint4 g_tbl[112 * 329];
__device__ unsigned g_cntA;
__device__ unsigned g_epoch;
#define TSTAMP(i)

constexpr int TBL_SC = 5248, TBL = 5264;
constexpr int TBL_C1 = 2624;
constexpr int SIG = 19584;
constexpr int SIG_U = 0, U_LBO = 656, SIG_V3 = 6272, SIG_V5 = 10368, SIG_V7 = 13440, SIG_V9 = 15488, SIG_V2 = 17536;
constexpr int Y2B = 6528, Y3B = 4352;
constexpr int KREC = 160, KSTG = 32 * KREC;
constexpr int OFF_W = 0, OFF_X = 98304, OFF_A = 147456, OFF_B = OFF_A + 8 * KSTG + 2560, OFF_T = OFF_B + 4 * KSTG;
constexpr int OFF_M = OFF_T + 15872;
constexpr int B_AX = Y2B, B_BX = B_AX + 2048, B_R = B_BX + 4096;
constexpr int M_BAR = 0, M_REL = 128, M_EP = 192, M_CSR = 256, M_END = 512;
constexpr int SMEM_BYTES = OFF_M + M_END;
constexpr int S_WORK = 63232, S_WGB = 2 * SIG + Y2B + Y3B;
static_assert(S_WORK + 3 * S_WGB <= OFF_M && SMEM_BYTES <= 232448, "smem");

struct Params {
  const __nv_bfloat16 *x, *a_re, *a_im, *b_re, *b_im, *c_re, *c_im, *log_dt, *dskip, *w1, *b1, *w2, *b2;
};

__device__ __forceinline__ int opaque(int x) { int v; asm volatile("mov.u32 %0, %1;" : "=r"(v) : "r"(x)); return v; }
__device__ __forceinline__ int rd_bid() { int v; asm volatile("mov.u32 %0, %%ctaid.x;" : "=r"(v)); return v; }
__device__ __forceinline__ uint32_t smem_u32(const void* p) { return (uint32_t)__cvta_generic_to_shared(p); }
__device__ __forceinline__ void mbar_init(uint32_t bar, int cnt) { asm volatile("mbarrier.init.shared::cta.b64 [%0], %1;" ::"r"(bar), "r"(cnt)); }
__device__ __forceinline__ void mbar_expect(uint32_t bar, uint32_t bytes) {
  asm volatile("mbarrier.arrive.expect_tx.shared::cta.b64 _, [%0], %1;" ::"r"(bar), "r"(bytes) : "memory");
}
__device__ __forceinline__ void mbar_wait(uint32_t bar, uint32_t parity) {
  uint32_t done = 0;
#pragma unroll 1
  for (int it = 0; it < SPIN_MAX; it++) {
    asm volatile("{.reg .pred p; mbarrier.try_wait.parity.shared::cta.b64 p, [%1], %2; selp.u32 %0,1,0,p;}"
                 : "=r"(done) : "r"(bar), "r"(parity) : "memory");
    if (done) break;
  }
}
__device__ __forceinline__ void tma_2d(uint32_t dst, const CUtensorMap* m, int c0, int c1, uint32_t bar) {
  asm volatile("cp.async.bulk.tensor.2d.shared::cluster.global.mbarrier::complete_tx::bytes [%0], [%1, {%3, %4}], [%2];"
               ::"r"(dst), "l"(m), "r"(bar), "r"(c0), "r"(c1) : "memory");
}
__device__ __forceinline__ void tma_3d(uint32_t dst, const CUtensorMap* m, int c0, int c1, int c2, uint32_t bar) {
  asm volatile("cp.async.bulk.tensor.3d.shared::cluster.global.mbarrier::complete_tx::bytes [%0], [%1, {%3, %4, %5}], [%2];"
               ::"r"(dst), "l"(m), "r"(bar), "r"(c0), "r"(c1), "r"(c2) : "memory");
}
__device__ __forceinline__ void tma_store_2d(const CUtensorMap* m, uint32_t src, int c0, int c1) {
  asm volatile("cp.async.bulk.tensor.2d.global.shared::cta.bulk_group [%0, {%2, %3}], [%1];"
               ::"l"(m), "r"(src), "r"(c0), "r"(c1) : "memory");
}
__device__ __forceinline__ void bulk_s2g(void* dst, uint32_t src, uint32_t bytes) {
  asm volatile("cp.async.bulk.global.shared::cta.bulk_group [%0], [%1], %2;" ::"l"(dst), "r"(src), "r"(bytes) : "memory");
}
__device__ __forceinline__ void bulk_g2s(uint32_t dst, const void* src, uint32_t bytes, uint32_t bar) {
  asm volatile("cp.async.bulk.shared::cluster.global.mbarrier::complete_tx::bytes [%0], [%1], %2, [%3];"
               ::"r"(dst), "l"(src), "r"(bytes), "r"(bar) : "memory");
}
__device__ __forceinline__ void bulk_commit() { asm volatile("cp.async.bulk.commit_group;" ::: "memory"); }
__device__ __forceinline__ void bulk_wait0() { asm volatile("cp.async.bulk.wait_group 0;" ::: "memory"); }
__device__ __forceinline__ void bulk_wait0_read() { asm volatile("cp.async.bulk.wait_group.read 0;" ::: "memory"); }
__device__ __forceinline__ void fence_async() { asm volatile("fence.proxy.async.shared::cta;" ::: "memory"); }
__device__ __forceinline__ void bar_sync(int id, int n) { asm volatile("bar.sync %0, %1;" ::"r"(id), "r"(n) : "memory"); }
__device__ __forceinline__ void bar_arrive(int id, int n) { asm volatile("bar.arrive %0, %1;" ::"r"(id), "r"(n) : "memory"); }
__device__ __forceinline__ void wg_fence() { asm volatile("wgmma.fence.sync.aligned;" ::: "memory"); }
__device__ __forceinline__ void wg_commit() { asm volatile("wgmma.commit_group.sync.aligned;" ::: "memory"); }
template <int N> __device__ __forceinline__ void wg_wait() { asm volatile("wgmma.wait_group.sync.aligned %0;" ::"n"(N) : "memory"); }
template <int N> __device__ __forceinline__ void fence_regs(float* d) {
#pragma unroll
  for (int i = 0; i < N; i++) asm volatile("" : "+f"(d[i])::"memory");
}
__device__ __forceinline__ uint64_t mkdesc(uint32_t addr, uint32_t lbo, uint32_t sbo, uint32_t sw) {
  return (uint64_t)((addr & 0x3FFFF) >> 4) | ((uint64_t)(lbo >> 4) << 16) | ((uint64_t)(sbo >> 4) << 32) | ((uint64_t)sw << 62);
}
__device__ __forceinline__ uint32_t lds32(uint32_t a) { uint32_t v; asm volatile("ld.shared.b32 %0, [%1];" : "=r"(v) : "r"(a) : "memory"); return v; }
__device__ __forceinline__ float lds32f(uint32_t a) { float v; asm volatile("ld.shared.f32 %0, [%1];" : "=f"(v) : "r"(a) : "memory"); return v; }
__device__ __forceinline__ float2 lds64f(uint32_t a) { float2 v; asm volatile("ld.shared.v2.f32 {%0,%1}, [%2];" : "=f"(v.x), "=f"(v.y) : "r"(a) : "memory"); return v; }
__device__ __forceinline__ uint4 lds128(uint32_t a) {
  uint4 v; asm volatile("ld.shared.v4.b32 {%0,%1,%2,%3}, [%4];" : "=r"(v.x), "=r"(v.y), "=r"(v.z), "=r"(v.w) : "r"(a) : "memory"); return v;
}
__device__ __forceinline__ void sts16(uint32_t a, uint16_t v) { asm volatile("st.shared.b16 [%0], %1;" ::"r"(a), "h"(v) : "memory"); }
__device__ __forceinline__ void sts32f(uint32_t a, float v) { asm volatile("st.shared.f32 [%0], %1;" ::"r"(a), "f"(v) : "memory"); }
__device__ __forceinline__ void sts64f(uint32_t a, float x, float y) { asm volatile("st.shared.v2.f32 [%0], {%1,%2};" ::"r"(a), "f"(x), "f"(y) : "memory"); }
__device__ __forceinline__ void sts128(uint32_t a, uint32_t x, uint32_t y, uint32_t z, uint32_t w) {
  asm volatile("st.shared.v4.b32 [%0], {%1,%2,%3,%4};" ::"r"(a), "r"(x), "r"(y), "r"(z), "r"(w) : "memory");
}
__device__ __forceinline__ void ldsm4(uint32_t a, uint32_t& r0, uint32_t& r1, uint32_t& r2, uint32_t& r3) {
  asm volatile("ldmatrix.sync.aligned.m8n8.x4.shared.b16 {%0,%1,%2,%3}, [%4];" : "=r"(r0), "=r"(r1), "=r"(r2), "=r"(r3) : "r"(a) : "memory");
}
__device__ __forceinline__ void ldsm4t(uint32_t a, uint32_t& r0, uint32_t& r1, uint32_t& r2, uint32_t& r3) {
  asm volatile("ldmatrix.sync.aligned.m8n8.x4.trans.shared.b16 {%0,%1,%2,%3}, [%4];" : "=r"(r0), "=r"(r1), "=r"(r2), "=r"(r3) : "r"(a) : "memory");
}
__device__ __forceinline__ void ldsm2t(uint32_t a, uint32_t& r0, uint32_t& r1) {
  asm volatile("ldmatrix.sync.aligned.m8n8.x2.trans.shared.b16 {%0,%1}, [%2];" : "=r"(r0), "=r"(r1) : "r"(a) : "memory");
}
__device__ __forceinline__ void stsm4(uint32_t a, uint32_t r0, uint32_t r1, uint32_t r2, uint32_t r3) {
  asm volatile("stmatrix.sync.aligned.m8n8.x4.shared.b16 [%0], {%1,%2,%3,%4};" ::"r"(a), "r"(r0), "r"(r1), "r"(r2), "r"(r3) : "memory");
}
__device__ __forceinline__ void mma_f16(float* c, uint32_t a0, uint32_t a1, uint32_t a2, uint32_t a3, uint32_t b0, uint32_t b1) {
  asm volatile("mma.sync.aligned.m16n8k16.row.col.f32.f16.f16.f32 {%0,%1,%2,%3},{%4,%5,%6,%7},{%8,%9},{%0,%1,%2,%3};"
               : "+f"(c[0]), "+f"(c[1]), "+f"(c[2]), "+f"(c[3]) : "r"(a0), "r"(a1), "r"(a2), "r"(a3), "r"(b0), "r"(b1));
}
__device__ __forceinline__ uint4 ld_relaxed4(const void* p) {
  uint4 v; asm volatile("ld.relaxed.gpu.global.v4.b32 {%0,%1,%2,%3}, [%4];" : "=r"(v.x), "=r"(v.y), "=r"(v.z), "=r"(v.w) : "l"(p) : "memory"); return v;
}
__device__ __forceinline__ void st_relaxed2(void* p, uint32_t x, uint32_t y) {
  asm volatile("st.relaxed.gpu.global.v2.b32 [%0], {%1,%2};" ::"l"(p), "r"(x), "r"(y) : "memory");
}
__device__ __forceinline__ uint4 ld_b128(const void* p) {
  uint4 v;
  asm volatile("{.reg .b128 t; .reg .b64 a, c; ld.relaxed.gpu.global.b128 t, [%4]; mov.b128 {a, c}, t; mov.b64 {%0,%1}, a; mov.b64 {%2,%3}, c;}"
               : "=r"(v.x), "=r"(v.y), "=r"(v.z), "=r"(v.w) : "l"(p) : "memory");
  return v;
}
__device__ __forceinline__ void st_b128(void* p, uint32_t tag, uint32_t x, uint32_t y, uint32_t z, uint32_t w) {
  asm volatile("{.reg .b128 t; .reg .b64 a, c; mov.b64 a, {%1,%2}; mov.b64 c, {%3,%4}; mov.b128 t, {a, c}; st.relaxed.gpu.global.b128 [%0], t;}"
               ::"l"(p), "r"((x & ~1u) | tag), "r"(y), "r"(z), "r"(w) : "memory");
}
__device__ __forceinline__ unsigned ld_relaxed1(const unsigned* p) {
  unsigned v; asm volatile("ld.relaxed.gpu.global.u32 %0, [%1];" : "=r"(v) : "l"(p) : "memory"); return v;
}
__device__ __forceinline__ void red_release(unsigned* p) {
  asm volatile("red.release.gpu.global.add.u32 [%0], 1;" ::"l"(p) : "memory");
}
__device__ __forceinline__ void wait_count(const unsigned* p, unsigned target) {
#pragma unroll 1
  for (int it = 0; it < SPIN_MAX; it++) {
    if ((int)(ld_relaxed1(p) - target) >= 0) break;
    __nanosleep(40);
  }
  asm volatile("fence.acq_rel.gpu;" ::: "memory");
}
__device__ __forceinline__ uint32_t pack_h2(float lo, float hi) { uint32_t r; asm("cvt.rn.f16x2.f32 %0, %1, %2;" : "=r"(r) : "f"(hi), "f"(lo)); return r; }
__device__ __forceinline__ uint32_t pack_bf2(float lo, float hi) { uint32_t r; asm("cvt.rn.bf16x2.f32 %0, %1, %2;" : "=r"(r) : "f"(hi), "f"(lo)); return r; }
__device__ __forceinline__ uint32_t pack_bf2v(float lo, float hi) { uint32_t r; asm volatile("cvt.rn.bf16x2.f32 %0, %1, %2;" : "=r"(r) : "f"(hi), "f"(lo)); return r; }
__device__ __forceinline__ float bf_lo(uint32_t w) { return __uint_as_float(w << 16); }
__device__ __forceinline__ float bf_hi(uint32_t w) { return __uint_as_float(w & 0xffff0000u); }
__device__ __forceinline__ float rbf(float v) { return __bfloat162float(__float2bfloat16_rn(v)); }
__device__ __forceinline__ float2 h2f(uint32_t w) { return __half22float2(*reinterpret_cast<__half2*>(&w)); }
__device__ __forceinline__ float ex2f(float v) { float r; asm("ex2.approx.ftz.f32 %0, %1;" : "=f"(r) : "f"(v)); return r; }
__device__ __forceinline__ float rcpf_(float v) { float r; asm("rcp.approx.f32 %0, %1;" : "=f"(r) : "f"(v)); return r; }
__device__ __forceinline__ float sqrtf_(float v) { float r; asm("sqrt.approx.f32 %0, %1;" : "=f"(r) : "f"(v)); return r; }
__device__ __forceinline__ float tanhf_(float v) { float r; asm volatile("tanh.approx.f32 %0, %1;" : "=f"(r) : "f"(v)); return r; }

__device__ __forceinline__ void wg_ss_bf16_n256(float* d, uint64_t da, uint64_t db, int sc) {
  asm volatile("{.reg .pred p; setp.ne.b32 p, %130, 0;\n"
    "wgmma.mma_async.sync.aligned.m64n256k16.f32.bf16.bf16 {%0, %1, %2, %3, %4, %5, %6, %7, %8, %9, %10, %11, %12, %13, %14, %15, %16, %17, %18, %19, %20, %21, %22, %23, %24, %25, %26, %27, %28, %29, %30, %31, %32, %33, %34, %35, %36, %37, %38, %39, %40, %41, %42, %43, %44, %45, %46, %47, %48, %49, %50, %51, %52, %53, %54, %55, %56, %57, %58, %59, %60, %61, %62, %63, %64, %65, %66, %67, %68, %69, %70, %71, %72, %73, %74, %75, %76, %77, %78, %79, %80, %81, %82, %83, %84, %85, %86, %87, %88, %89, %90, %91, %92, %93, %94, %95, %96, %97, %98, %99, %100, %101, %102, %103, %104, %105, %106, %107, %108, %109, %110, %111, %112, %113, %114, %115, %116, %117, %118, %119, %120, %121, %122, %123, %124, %125, %126, %127}, %128, %129, p, 1, 1, 0, 1;}\n"
    : "+f"(d[0]), "+f"(d[1]), "+f"(d[2]), "+f"(d[3]), "+f"(d[4]), "+f"(d[5]), "+f"(d[6]), "+f"(d[7]), "+f"(d[8]), "+f"(d[9]), "+f"(d[10]), "+f"(d[11]), "+f"(d[12]), "+f"(d[13]), "+f"(d[14]), "+f"(d[15]), "+f"(d[16]), "+f"(d[17]), "+f"(d[18]), "+f"(d[19]), "+f"(d[20]), "+f"(d[21]), "+f"(d[22]), "+f"(d[23]), "+f"(d[24]), "+f"(d[25]), "+f"(d[26]), "+f"(d[27]), "+f"(d[28]), "+f"(d[29]), "+f"(d[30]), "+f"(d[31]), "+f"(d[32]), "+f"(d[33]), "+f"(d[34]), "+f"(d[35]), "+f"(d[36]), "+f"(d[37]), "+f"(d[38]), "+f"(d[39]), "+f"(d[40]), "+f"(d[41]), "+f"(d[42]), "+f"(d[43]), "+f"(d[44]), "+f"(d[45]), "+f"(d[46]), "+f"(d[47]), "+f"(d[48]), "+f"(d[49]), "+f"(d[50]), "+f"(d[51]), "+f"(d[52]), "+f"(d[53]), "+f"(d[54]), "+f"(d[55]), "+f"(d[56]), "+f"(d[57]), "+f"(d[58]), "+f"(d[59]), "+f"(d[60]), "+f"(d[61]), "+f"(d[62]), "+f"(d[63]), "+f"(d[64]), "+f"(d[65]), "+f"(d[66]), "+f"(d[67]), "+f"(d[68]), "+f"(d[69]), "+f"(d[70]), "+f"(d[71]), "+f"(d[72]), "+f"(d[73]), "+f"(d[74]), "+f"(d[75]), "+f"(d[76]), "+f"(d[77]), "+f"(d[78]), "+f"(d[79]), "+f"(d[80]), "+f"(d[81]), "+f"(d[82]), "+f"(d[83]), "+f"(d[84]), "+f"(d[85]), "+f"(d[86]), "+f"(d[87]), "+f"(d[88]), "+f"(d[89]), "+f"(d[90]), "+f"(d[91]), "+f"(d[92]), "+f"(d[93]), "+f"(d[94]), "+f"(d[95]), "+f"(d[96]), "+f"(d[97]), "+f"(d[98]), "+f"(d[99]), "+f"(d[100]), "+f"(d[101]), "+f"(d[102]), "+f"(d[103]), "+f"(d[104]), "+f"(d[105]), "+f"(d[106]), "+f"(d[107]), "+f"(d[108]), "+f"(d[109]), "+f"(d[110]), "+f"(d[111]), "+f"(d[112]), "+f"(d[113]), "+f"(d[114]), "+f"(d[115]), "+f"(d[116]), "+f"(d[117]), "+f"(d[118]), "+f"(d[119]), "+f"(d[120]), "+f"(d[121]), "+f"(d[122]), "+f"(d[123]), "+f"(d[124]), "+f"(d[125]), "+f"(d[126]), "+f"(d[127])
    : "l"(da), "l"(db), "r"(sc));
}

__device__ __forceinline__ void wg_ss_bf16_n256k(float* d, uint64_t da, uint64_t db, int sc) {
  asm volatile("{.reg .pred p; setp.ne.b32 p, %130, 0;\n"
    "wgmma.mma_async.sync.aligned.m64n256k16.f32.bf16.bf16 {%0, %1, %2, %3, %4, %5, %6, %7, %8, %9, %10, %11, %12, %13, %14, %15, %16, %17, %18, %19, %20, %21, %22, %23, %24, %25, %26, %27, %28, %29, %30, %31, %32, %33, %34, %35, %36, %37, %38, %39, %40, %41, %42, %43, %44, %45, %46, %47, %48, %49, %50, %51, %52, %53, %54, %55, %56, %57, %58, %59, %60, %61, %62, %63, %64, %65, %66, %67, %68, %69, %70, %71, %72, %73, %74, %75, %76, %77, %78, %79, %80, %81, %82, %83, %84, %85, %86, %87, %88, %89, %90, %91, %92, %93, %94, %95, %96, %97, %98, %99, %100, %101, %102, %103, %104, %105, %106, %107, %108, %109, %110, %111, %112, %113, %114, %115, %116, %117, %118, %119, %120, %121, %122, %123, %124, %125, %126, %127}, %128, %129, p, 1, 1, 0, 0;}\n"
    : "+f"(d[0]), "+f"(d[1]), "+f"(d[2]), "+f"(d[3]), "+f"(d[4]), "+f"(d[5]), "+f"(d[6]), "+f"(d[7]), "+f"(d[8]), "+f"(d[9]), "+f"(d[10]), "+f"(d[11]), "+f"(d[12]), "+f"(d[13]), "+f"(d[14]), "+f"(d[15]), "+f"(d[16]), "+f"(d[17]), "+f"(d[18]), "+f"(d[19]), "+f"(d[20]), "+f"(d[21]), "+f"(d[22]), "+f"(d[23]), "+f"(d[24]), "+f"(d[25]), "+f"(d[26]), "+f"(d[27]), "+f"(d[28]), "+f"(d[29]), "+f"(d[30]), "+f"(d[31]), "+f"(d[32]), "+f"(d[33]), "+f"(d[34]), "+f"(d[35]), "+f"(d[36]), "+f"(d[37]), "+f"(d[38]), "+f"(d[39]), "+f"(d[40]), "+f"(d[41]), "+f"(d[42]), "+f"(d[43]), "+f"(d[44]), "+f"(d[45]), "+f"(d[46]), "+f"(d[47]), "+f"(d[48]), "+f"(d[49]), "+f"(d[50]), "+f"(d[51]), "+f"(d[52]), "+f"(d[53]), "+f"(d[54]), "+f"(d[55]), "+f"(d[56]), "+f"(d[57]), "+f"(d[58]), "+f"(d[59]), "+f"(d[60]), "+f"(d[61]), "+f"(d[62]), "+f"(d[63]), "+f"(d[64]), "+f"(d[65]), "+f"(d[66]), "+f"(d[67]), "+f"(d[68]), "+f"(d[69]), "+f"(d[70]), "+f"(d[71]), "+f"(d[72]), "+f"(d[73]), "+f"(d[74]), "+f"(d[75]), "+f"(d[76]), "+f"(d[77]), "+f"(d[78]), "+f"(d[79]), "+f"(d[80]), "+f"(d[81]), "+f"(d[82]), "+f"(d[83]), "+f"(d[84]), "+f"(d[85]), "+f"(d[86]), "+f"(d[87]), "+f"(d[88]), "+f"(d[89]), "+f"(d[90]), "+f"(d[91]), "+f"(d[92]), "+f"(d[93]), "+f"(d[94]), "+f"(d[95]), "+f"(d[96]), "+f"(d[97]), "+f"(d[98]), "+f"(d[99]), "+f"(d[100]), "+f"(d[101]), "+f"(d[102]), "+f"(d[103]), "+f"(d[104]), "+f"(d[105]), "+f"(d[106]), "+f"(d[107]), "+f"(d[108]), "+f"(d[109]), "+f"(d[110]), "+f"(d[111]), "+f"(d[112]), "+f"(d[113]), "+f"(d[114]), "+f"(d[115]), "+f"(d[116]), "+f"(d[117]), "+f"(d[118]), "+f"(d[119]), "+f"(d[120]), "+f"(d[121]), "+f"(d[122]), "+f"(d[123]), "+f"(d[124]), "+f"(d[125]), "+f"(d[126]), "+f"(d[127])
    : "l"(da), "l"(db), "r"(sc));
}

__device__ __forceinline__ void wg_rs_bf16_n64(float* d, uint32_t a0, uint32_t a1, uint32_t a2, uint32_t a3, uint64_t db, int sc) {
  asm volatile("{.reg .pred p; setp.ne.b32 p, %37, 0;\n"
    "wgmma.mma_async.sync.aligned.m64n64k16.f32.bf16.bf16 {%0, %1, %2, %3, %4, %5, %6, %7, %8, %9, %10, %11, %12, %13, %14, %15, %16, %17, %18, %19, %20, %21, %22, %23, %24, %25, %26, %27, %28, %29, %30, %31}, {%32,%33,%34,%35}, %36, p, 1, 1, 1;}\n"
    : "+f"(d[0]), "+f"(d[1]), "+f"(d[2]), "+f"(d[3]), "+f"(d[4]), "+f"(d[5]), "+f"(d[6]), "+f"(d[7]), "+f"(d[8]), "+f"(d[9]), "+f"(d[10]), "+f"(d[11]), "+f"(d[12]), "+f"(d[13]), "+f"(d[14]), "+f"(d[15]), "+f"(d[16]), "+f"(d[17]), "+f"(d[18]), "+f"(d[19]), "+f"(d[20]), "+f"(d[21]), "+f"(d[22]), "+f"(d[23]), "+f"(d[24]), "+f"(d[25]), "+f"(d[26]), "+f"(d[27]), "+f"(d[28]), "+f"(d[29]), "+f"(d[30]), "+f"(d[31])
    : "r"(a0), "r"(a1), "r"(a2), "r"(a3), "l"(db), "r"(sc));
}

__device__ __forceinline__ void wg_rs_f16_n32k(float* d, uint32_t a0, uint32_t a1, uint32_t a2, uint32_t a3, uint64_t db, int sc) {
  asm volatile("{.reg .pred p; setp.ne.b32 p, %21, 0;\n"
    "wgmma.mma_async.sync.aligned.m64n32k16.f32.f16.f16 {%0, %1, %2, %3, %4, %5, %6, %7, %8, %9, %10, %11, %12, %13, %14, %15}, {%16,%17,%18,%19}, %20, p, 1, 1, 0;}\n"
    : "+f"(d[0]), "+f"(d[1]), "+f"(d[2]), "+f"(d[3]), "+f"(d[4]), "+f"(d[5]), "+f"(d[6]), "+f"(d[7]), "+f"(d[8]), "+f"(d[9]), "+f"(d[10]), "+f"(d[11]), "+f"(d[12]), "+f"(d[13]), "+f"(d[14]), "+f"(d[15])
    : "r"(a0), "r"(a1), "r"(a2), "r"(a3), "l"(db), "r"(sc));
}

__device__ __forceinline__ void wg_rs_f16_n24t(float* d, uint32_t a0, uint32_t a1, uint32_t a2, uint32_t a3, uint64_t db, int sc) {
  asm volatile("{.reg .pred p; setp.ne.b32 p, %17, 0;\n"
    "wgmma.mma_async.sync.aligned.m64n24k16.f32.f16.f16 {%0, %1, %2, %3, %4, %5, %6, %7, %8, %9, %10, %11}, {%12,%13,%14,%15}, %16, p, 1, 1, 1;}\n"
    : "+f"(d[0]), "+f"(d[1]), "+f"(d[2]), "+f"(d[3]), "+f"(d[4]), "+f"(d[5]), "+f"(d[6]), "+f"(d[7]), "+f"(d[8]), "+f"(d[9]), "+f"(d[10]), "+f"(d[11])
    : "r"(a0), "r"(a1), "r"(a2), "r"(a3), "l"(db), "r"(sc));
}

__device__ __forceinline__ void wg_rs_f16_n16t(float* d, uint32_t a0, uint32_t a1, uint32_t a2, uint32_t a3, uint64_t db, int sc) {
  asm volatile("{.reg .pred p; setp.ne.b32 p, %13, 0;\n"
    "wgmma.mma_async.sync.aligned.m64n16k16.f32.f16.f16 {%0, %1, %2, %3, %4, %5, %6, %7}, {%8,%9,%10,%11}, %12, p, 1, 1, 1;}\n"
    : "+f"(d[0]), "+f"(d[1]), "+f"(d[2]), "+f"(d[3]), "+f"(d[4]), "+f"(d[5]), "+f"(d[6]), "+f"(d[7])
    : "r"(a0), "r"(a1), "r"(a2), "r"(a3), "l"(db), "r"(sc));
}

struct cf { float x, y; };
__device__ __forceinline__ cf cmul(cf a, cf b) { cf r; r.x = fmaf(a.x, b.x, -a.y * b.y); r.y = fmaf(a.x, b.y, a.y * b.x); return r; }
__device__ __forceinline__ cf zpow(float rho2, float phi, float e) {
  const float m = ex2f(rho2 * e), ang = phi * e;
  cf r; r.x = m * __cosf(ang); r.y = m * __sinf(ang); return r;
}
__device__ __forceinline__ __half2 H2(uint32_t v) { return *reinterpret_cast<__half2*>(&v); }
__device__ __forceinline__ uint32_t U32(__half2 v) { return *reinterpret_cast<uint32_t*>(&v); }
__device__ __forceinline__ uint32_t hprod(uint32_t v, uint32_t r, uint32_t rr) {
  return U32(__hfma2(__high2half2(H2(v)), H2(rr), __hmul2(__low2half2(H2(v)), H2(r))));
}
__device__ __forceinline__ void hprod2(uint32_t re, uint32_t im, uint32_t r, uint32_t& ore, uint32_t& oim) {
  const __half2 rx = __low2half2(H2(r)), ry = __high2half2(H2(r));
  ore = U32(__hfma2(H2(re), rx, __hneg2(__hmul2(H2(im), ry))));
  oim = U32(__hfma2(H2(re), ry, __hmul2(H2(im), rx)));
}
__device__ __forceinline__ uint32_t rot90(uint32_t v) { return __byte_perm(v, 0, 0x1032) ^ 0x00008000u; }
__device__ __forceinline__ uint32_t hadd2u(uint32_t a, uint32_t b) { return U32(__hadd2(H2(a), H2(b))); }

struct KgIn { uint32_t cur[6], nxt[6]; uint4 m[4]; uint16_t ldt, dk; };
__device__ __forceinline__ void kgen_load(const Params& p, int d, int wd0, int nw, int lane, KgIn& k) {
  const int off = d * (NST / 2) + lane * 4;
  const uint32_t* P[6] = {(const uint32_t*)p.a_re, (const uint32_t*)p.a_im, (const uint32_t*)p.b_re,
                          (const uint32_t*)p.b_im, (const uint32_t*)p.c_re, (const uint32_t*)p.c_im};
  k.ldt = __ldg((const uint16_t*)p.log_dt + d); k.dk = __ldg((const uint16_t*)p.dskip + d);
#pragma unroll
  for (int i = 0; i < 4; i++) k.m[i] = __ldg((const uint4*)(P[2 + i] + off));
#pragma unroll
  for (int i = 0; i < 6; i++) { k.cur[i] = __ldg(P[i] + off + wd0); k.nxt[i] = __ldg(P[i] + off + wd0 + nw - 1); }
}
__device__ __forceinline__ void kgen_warp(KgIn& k, int nw, uint32_t stg, uint32_t tbl, int lane) {
  float dl, dt, inv_sc;
  {
    const uint32_t M = 0x7fff7fffu;
    uint32_t mx[2];
#pragma unroll
    for (int i = 0; i < 2; i++) {
      const uint4 a = k.m[2 * i], c = k.m[2 * i + 1];
      const uint32_t m = __vmaxu2(__vmaxu2(__vmaxu2(a.x & M, a.y & M), __vmaxu2(a.z & M, a.w & M)),
                                  __vmaxu2(__vmaxu2(c.x & M, c.y & M), __vmaxu2(c.z & M, c.w & M)));
      mx[i] = __reduce_max_sync(0xffffffffu, max(m << 16, m & 0xffff0000u));
    }
    dt = rbf(ex2f(bf_lo(k.ldt) * 1.4426950408889634f));
    const float dsk = bf_lo(k.dk) * rcpf_(dt);
    float sc = fmaxf(0.125f * __uint_as_float(mx[0]) * __uint_as_float(mx[1]), fabsf(dsk) * (1.f / 4096.f));
    sc = __uint_as_float(__float_as_uint(fminf(fmaxf(sc, 1e-30f), 1e30f)) & 0x7f800000u);
    inv_sc = rcpf_(sc);
    if (lane == 0) sts64f(tbl + TBL_SC + 8, dt * sc, dsk * inv_sc);
    dl = dt * 1.4426950408889634f;
  }
  const uint32_t st0 = stg + lane * KREC + (((lane >> 2) & 1) << 4), st1 = st0 ^ 16;
  const int mat = lane >> 3, rowi = lane & 7;
  const uint32_t ldB = stg + (4 * (mat & 1) + (rowi >> 1)) * KREC + ((((mat >> 1) * 2 + (rowi & 1)) << 4) ^ ((mat & 1) << 4));
  const uint32_t ldA = stg + (4 * (mat >> 1) + (rowi >> 1)) * KREC + ((((mat & 1) * 2 + (rowi & 1)) << 4) ^ ((mat >> 1) << 4)) + 96;
  const int csrc = 20 + (lane & 3);
  float acc[24];
#pragma unroll
  for (int i = 0; i < 24; i++) acc[i] = 0.f;
#pragma unroll 1
  for (int it = 0; it < 2 * nw; it++) {
    const uint32_t sel = (it & 1) ? 0x3244u : 0x1044u;
    float v[6];
#pragma unroll
    for (int i = 0; i < 6; i++) { v[i] = __uint_as_float(__byte_perm(k.cur[i], 0, sel)); if (it == 1) k.cur[i] = k.nxt[i]; }
    const float rho2 = v[0] * dl, phi = v[1] * dt;
    const cf bb = {v[2] * inv_sc, v[3] * -inv_sc}, cc = {v[4], -v[5]};
    cf X[8];
    X[0] = cmul(cc, bb);
    const cf z1 = zpow(rho2, -phi, 1.f), z8 = zpow(rho2, phi, 8.f), z64 = zpow(rho2, phi, 64.f);
    const cf y1 = zpow(rho2, -phi, 256.f), y4 = zpow(rho2, -phi, 1024.f);
    const cf z2 = cmul(z1, z1);
    X[1] = cmul(X[0], z1);
#pragma unroll
    for (int j = 2; j < 8; j++) X[j] = cmul(X[j - 2], z2);
    const cf a0 = cmul(X[0], y1), a1 = cmul(X[2], y1), a2 = cmul(X[4], y1), a3 = cmul(X[6], y1);
    const cf a4 = cmul(a0, y1), a5 = cmul(a2, y1);
    const cf a6 = cmul(a4, y1), a7 = cmul(a5, y1);
    const cf v0 = cmul(X[0], y4), v1 = cmul(a0, y4), v2 = cmul(a4, y4), v3 = cmul(a6, y4), v4 = cmul(v0, y4);
    const cf f2 = cmul(z8, z8), f3 = cmul(f2, z8), f4 = cmul(f2, f2), f5 = cmul(f3, f2), f6 = cmul(f4, f2), f7 = cmul(f4, f3);
    const cf z128 = cmul(z64, z64);
    const uint32_t fr[4] = {pack_h2(1.f, z8.x), pack_h2(f2.x, f3.x), pack_h2(f4.x, f5.x), pack_h2(f6.x, f7.x)};
    const uint32_t fi[4] = {pack_h2(0.f, z8.y), pack_h2(f2.y, f3.y), pack_h2(f4.y, f5.y), pack_h2(f6.y, f7.y)};
    const uint32_t h64 = pack_h2(z64.x, z64.y);
    uint32_t gr[4], gi[4];
#pragma unroll
    for (int j = 0; j < 4; j++) hprod2(fr[j], fi[j], h64, gr[j], gi[j]);
    __syncwarp();
    sts128(st0, pack_h2(X[0].x, X[1].x), pack_h2(X[2].x, X[3].x), pack_h2(X[4].x, X[5].x), pack_h2(X[6].x, X[7].x));
    sts128(st1, pack_h2(X[0].y, X[1].y), pack_h2(X[2].y, X[3].y), pack_h2(X[4].y, X[5].y), pack_h2(X[6].y, X[7].y));
    sts128(st0 + 32, pack_h2(a0.x, a1.x), pack_h2(a2.x, a3.x), pack_h2(a4.x, a5.x), pack_h2(a6.x, a7.x));
    sts128(st1 + 32, pack_h2(a0.y, a1.y), pack_h2(a2.y, a3.y), pack_h2(a4.y, a5.y), pack_h2(a6.y, a7.y));
    asm volatile("st.shared.v2.b32 [%0], {%1,%2};" ::"r"(st0 + 64), "r"(pack_h2(v0.x, v1.x)), "r"(pack_h2(v2.x, v3.x)) : "memory");
    asm volatile("st.shared.v2.b32 [%0], {%1,%2};" ::"r"(st1 + 64), "r"(pack_h2(v0.y, v1.y)), "r"(pack_h2(v2.y, v3.y)) : "memory");
    asm volatile("st.shared.v2.b32 [%0], {%1,%1};" ::"r"(st0 + 72), "r"(pack_h2(v4.x, z128.x)) : "memory");
    asm volatile("st.shared.v2.b32 [%0], {%1,%1};" ::"r"(st1 + 72), "r"(pack_h2(v4.y, z128.y)) : "memory");
    sts128(st0 + 96, fr[0], fr[1], fr[2], fr[3]);
    sts128(st1 + 96, fi[0], fi[1], fi[2], fi[3]);
    sts128(st0 + 128, gr[0], gr[1], gr[2], gr[3]);
    sts128(st1 + 128, gi[0], gi[1], gi[2], gi[3]);
    __syncwarp();
    uint32_t B[4][6], A[4][4];
#pragma unroll
    for (int ks = 0; ks < 4; ks++) {
      ldsm2t(ldB + ks * 8 * KREC + 64, B[ks][4], B[ks][5]);
      ldsm4t(ldA + ks * 8 * KREC, A[ks][0], A[ks][1], A[ks][2], A[ks][3]);
      ldsm4t(ldB + ks * 8 * KREC, B[ks][0], B[ks][1], B[ks][2], B[ks][3]);
    }
#pragma unroll
    for (int ks = 0; ks < 4; ks++) {
      const uint32_t rl = __shfl_sync(0xffffffffu, B[ks][4], csrc), rh = __shfl_sync(0xffffffffu, B[ks][5], csrc);
      const uint32_t rlr = rot90(rl), rhr = rot90(rh);
      mma_f16(acc + 0, A[ks][0], A[ks][1], A[ks][2], A[ks][3], B[ks][0], B[ks][1]);
      mma_f16(acc + 4, A[ks][0], A[ks][1], A[ks][2], A[ks][3], B[ks][2], B[ks][3]);
      mma_f16(acc + 8, A[ks][0], A[ks][1], A[ks][2], A[ks][3], B[ks][4], B[ks][5]);
      const uint32_t c0 = hprod(A[ks][0], rl, rlr), c1 = hprod(A[ks][1], rl, rlr);
      const uint32_t c2 = hprod(A[ks][2], rh, rhr), c3 = hprod(A[ks][3], rh, rhr);
      mma_f16(acc + 12, c0, c1, c2, c3, B[ks][0], B[ks][1]);
      mma_f16(acc + 16, c0, c1, c2, c3, B[ks][2], B[ks][3]);
      mma_f16(acc + 20, c0, c1, c2, c3, B[ks][4], B[ks][5]);
    }
  }
  __syncwarp();
#pragma unroll
  for (int q = 0; q < 4; q++)
#pragma unroll
    for (int nt = 0; nt < 3; nt++) {
      const float* a = acc + 12 * (q >> 1) + 4 * nt + 2 * (q & 1);
      sts64f(stg + (q * 3 + nt) * 256 + lane * 8, a[0], a[1]);
    }
}

__device__ __forceinline__ void tput(uint32_t tbl, int X, uint32_t h) {
  sts16(tbl + 2 * (1296 - X), (uint16_t)h);
  sts16(tbl + TBL_C1 + 2 * (1297 - X), (uint16_t)h);
}
__device__ __forceinline__ void ktab_build(uint32_t src, bool four, int q, uint32_t tbl, int lane) {
  const int tq = lane & 3, r = 8 * q + (lane >> 2);
  float v[6];
  src += q * 768 + lane * 8;
#pragma unroll
  for (int nt = 0; nt < 3; nt++) {
    const float2 a = lds64f(src + nt * 256), c = lds64f(src + nt * 256 + KSTG);
    v[2 * nt] = a.x + c.x; v[2 * nt + 1] = a.y + c.y;
  }
  if (four) {
#pragma unroll
    for (int nt = 0; nt < 3; nt++) {
      const float2 a = lds64f(src + nt * 256 + 2 * KSTG), c = lds64f(src + nt * 256 + 3 * KSTG);
      v[2 * nt] += a.x + c.x; v[2 * nt + 1] += a.y + c.y;
    }
  }
  const bool first = (r == 0);
  if (first && tq == 0) { v[0] += lds32f(tbl + TBL_SC + 12); sts32f(tbl + TBL_SC, v[4]); }
  const uint32_t h0 = pack_h2(v[0], v[1]), h1 = pack_h2(v[2], v[3]), h2 = pack_h2(v[4], v[5]);
  tput(tbl, 64 + 8 * r + 2 * tq, h0);
  tput(tbl, 65 + 8 * r + 2 * tq, h0 >> 16);
  const bool lo = tq < 2;
  const int Xd = 320 + 8 * r + 4 * tq, k2 = 32 * (tq - 2) + r;
  tput(tbl, lo ? Xd + 2 : 720 + k2, h1 >> 16);
  const bool sp = first && tq == 2;
  const int Xa = lo ? Xd : (sp ? 576 : 911 + k2);
  tput(tbl, Xa, h1);
  if (lo || sp) {
    tput(tbl, Xa + 1, h1);
    if (Xa != 320) tput(tbl, Xa - 1, h1);
  }
  if (sp) { tput(tbl, 578, h1); tput(tbl, 1295, h2); }
  if (lo) {
    const int X3 = ((r & 1) ? 1104 : 1231) + 32 * tq + (r >> 1);
    tput(tbl, X3 == 1231 ? 975 : X3, h2);
    tput(tbl, X3 + 16, h2 >> 16);
  }
}

__device__ __forceinline__ void sig_windows(uint32_t sig, int t) {
  uint32_t U[20];
#pragma unroll
  for (int c = 0; c < 5; c++) {
    const int kap = 2 * t - 3 + c + 72;
    const uint4 v = lds128(sig + SIG_U + (kap & 7) * U_LBO + (kap >> 3) * 16);
    U[4 * c] = v.x; U[4 * c + 1] = v.y; U[4 * c + 2] = v.z; U[4 * c + 3] = v.w;
  }
  uint32_t O[19], A2[17], A4[17], V2[8], V5[8];
#pragma unroll
  for (int i = 3; i < 19; i++) O[i] = __byte_perm(U[i - 1], U[i], 0x5432);
#pragma unroll
  for (int i = 3; i < 17; i++) A2[i] = hadd2u(U[i], O[i]);
#pragma unroll
  for (int i = 4; i < 17; i++) A4[i] = hadd2u(A2[i], A2[i - 1]);
#pragma unroll
  for (int k = 0; k < 8; k++) { V2[k] = hadd2u(O[11 + k], U[10 + k]); V5[k] = hadd2u(A4[9 + k], U[7 + k]); }
#pragma unroll
  for (int h = 0; h < 2; h++) {
    sts128(sig + SIG_V3 + t * 32 + h * 16, hadd2u(V2[4 * h], O[10 + 4 * h]), hadd2u(V2[4 * h + 1], O[11 + 4 * h]),
           hadd2u(V2[4 * h + 2], O[12 + 4 * h]), hadd2u(V2[4 * h + 3], O[13 + 4 * h]));
    sts128(sig + SIG_V5 + t * 32 + h * 16, V5[4 * h], V5[4 * h + 1], V5[4 * h + 2], V5[4 * h + 3]);
  }
  if (t < 64) {
    uint32_t V7[8], V9[8];
#pragma unroll
    for (int k = 0; k < 8; k++) {
      V7[k] = hadd2u(V5[k], hadd2u(O[10 + k], O[7 + k]));
      V9[k] = hadd2u(hadd2u(A4[6 + k], A4[4 + k]), U[2 + k]);
    }
#pragma unroll
    for (int h = 0; h < 2; h++) {
      sts128(sig + SIG_V7 + h * 1024 + t * 16, V7[4 * h], V7[4 * h + 1], V7[4 * h + 2], V7[4 * h + 3]);
      sts128(sig + SIG_V9 + h * 1024 + t * 16, V9[4 * h], V9[4 * h + 1], V9[4 * h + 2], V9[4 * h + 3]);
      sts128(sig + SIG_V2 + h * 1024 + t * 16, V2[4 * h], V2[4 * h + 1], V2[4 * h + 2], V2[4 * h + 3]);
    }
  }
}

__device__ __forceinline__ void conv_channel(uint32_t tbl, uint32_t sig, uint32_t y2b, uint32_t y3b, float k1024,
                                             int w, int lane, int barid, float* res, int ts) {
  TSTAMP(ts);
  const int g = lane >> 2, tq = lane & 3;
  const uint32_t tb = tbl + ((g & 1) ? TBL_C1 + 2 : 0) + 2 * (1296 - (g - 2 * tq)) - 32 * w + 112;
  float a2[12], a3[8];
#pragma unroll
  for (int i = 0; i < 16; i++) res[i] = 0.f;
#pragma unroll
  for (int i = 0; i < 12; i++) a2[i] = 0.f;
#pragma unroll
  for (int q = 0; q < 4; q++) {
    const float2 f = h2f(lds32(sig + SIG_V2 + (q >> 1) * 1024 + (16 * w + 8 * (q & 1) + g) * 16 + tq * 4));
    a3[2 * q] = k1024 * f.x;
    a3[2 * q + 1] = k1024 * f.y;
  }
  const uint64_t dU = mkdesc(sig + SIG_U, U_LBO, 128, 0);
  const uint64_t dV = mkdesc(sig, 128, 1024, 0);
  fence_regs<16>(res); fence_regs<12>(a2); fence_regs<8>(a3);
  constexpr int LB = 2 * U_LBO / 16;
  uint32_t Rd[75], R2[2][17], R3[2][9];
  auto load_group = [&](int gi) {
    const int it = gi >> 1, hb = gi & 1;
    if (gi == 0) Rd[0] = lds32(tb - 128);
#pragma unroll
    for (int i = 1; i < (gi == 17 ? 7 : 5); i++) Rd[4 * gi + i] = lds32(tb - 128 - 16 * (4 * gi + i));
    if (gi < 16) {
      const int sg = it >> 2, n2 = gi & 7;
      if (n2 == 0) R2[sg][0] = lds32(tb - 1440 - 384 * sg);
      R2[sg][2 * n2 + 1] = lds32(tb - 1440 - 384 * sg - 16 * (2 * n2 + 1));
      R2[sg][2 * n2 + 2] = lds32(tb - 1440 - 384 * sg - 16 * (2 * n2 + 2));
      if (!hb) {
        const int n3 = it & 3;
        if (n3 == 0) R3[sg][0] = lds32(tb - 2208 - 256 * sg);
        R3[sg][2 * n3 + 1] = lds32(tb - 2208 - 256 * sg - 16 * (2 * n3 + 1));
        R3[sg][2 * n3 + 2] = lds32(tb - 2208 - 256 * sg - 16 * (2 * n3 + 2));
      }
    }
  };
  auto dense = [&](int n) {
    wg_rs_f16_n32k(res, Rd[2 * n + 1], Rd[2 * n + 2], Rd[2 * n], Rd[2 * n + 1], dU + ((3 - (n & 3)) * LB + 9 - (n >> 2)), 1);
  };
  load_group(0);
  load_group(1);
#pragma unroll
  for (int gi = 0; gi < 18; gi++) {
    const int it = gi >> 1, sg = it >> 2, n2 = gi & 7, n3 = it & 3;
    wg_fence();
    dense(2 * gi);
    if (gi < 16)
      wg_rs_f16_n24t(a2, R2[sg][2 * n2 + 1], R2[sg][2 * n2 + 2], R2[sg][2 * n2], R2[sg][2 * n2 + 1],
                     dV + ((SIG_V3 + 768) / 16 + 256 * sg - 16 * (n2 & 3) - 64 * (n2 >> 2)), 1);
    dense(2 * gi + 1);
    if (gi < 16 && !(gi & 1))
      wg_rs_f16_n16t(a3, R3[sg][2 * n3 + 1], R3[sg][2 * n3 + 2], R3[sg][2 * n3], R3[sg][2 * n3 + 1],
                     dV + ((SIG_V7 + 768) / 16 + 128 * sg - 16 * n3), 1);
    if (gi == 17) dense(36);
    wg_commit();
    if (gi < 16) { wg_wait<1>(); load_group(gi + 2); }
  }
  TSTAMP(ts + 1);
  wg_wait<2>();
  fence_regs<12>(a2); fence_regs<8>(a3);
  bar_sync(barid, 128);
  {
    const uint32_t o2 = y2b + (136 * w + 8 * g + 2 * tq) * 4, o3 = y3b + (272 * w + 16 * g + 2 * tq) * 4;
#pragma unroll
    for (int q = 0; q < 6; q++) sts64f(o2 + (544 * (q >> 1) + 64 * (q & 1)) * 4, a2[2 * q], a2[2 * q + 1]);
#pragma unroll
    for (int q = 0; q < 4; q++) sts64f(o3 + (8 * (q >> 1) + 136 * (q & 1)) * 4, a3[2 * q], a3[2 * q + 1]);
  }
  bar_sync(barid, 128);
  const uint32_t go = (136 * tq + 16 * w + g) * 4;
  float ex[12];
#pragma unroll
  for (int i = 0; i < 12; i++) {
    const int o = 544 * (i >> 2) + 64 * (i & 1) + 8 * ((i >> 1) & 1);
    ex[i] = lds32f(y2b + go + o * 4);
    if (i >= 4) ex[i] += lds32f(y3b + go + (o - 544) * 4);
  }
  wg_wait<0>();
  fence_regs<16>(res);
#pragma unroll
  for (int i = 0; i < 12; i++) res[4 + i] += ex[i];
  TSTAMP(ts + 2);
}

__device__ __forceinline__ void red16x2(float& a, float& c) {
#pragma unroll
  for (int o = 1; o < 16; o <<= 1) { a += __shfl_xor_sync(0xffffffffu, a, o); c += __shfl_xor_sync(0xffffffffu, c, o); }
}
__device__ __forceinline__ void ln_rows(uint32_t* u, int row, uint32_t stg_row, uint32_t tag2, int lane) {
  const int j = lane & 15;
  const float piv = __shfl_sync(0xffffffffu, bf_lo(u[0]), lane & 16);
  float s0 = 0.f, s1 = 0.f, q0 = 0.f, q1 = 0.f;
#pragma unroll
  for (int i = 0; i < 14; i++) {
    const float a = bf_lo(u[i]) - piv, c = bf_hi(u[i]) - piv;
    s0 += a; s1 += c; q0 = fmaf(a, a, q0); q1 = fmaf(c, c, q1);
  }
  float s = s0 + s1, q = q0 + q1;
  red16x2(s, q);
  s *= (1.f / D_); q *= (1.f / D_);
  const __nv_bfloat16 m1b = __float2bfloat16_rn(s + piv);
  const __nv_bfloat162 m1v = __halves2bfloat162(m1b, m1b);
  const float den = rbf(sqrtf_(rbf(rbf(fmaxf(fmaf(-s, s, q), 0.f)) + 1e-5f)));
  const float rden = rcpf_(den);
  s0 = s1 = q0 = q1 = 0.f;
#pragma unroll
  for (int i = 0; i < 14; i++) {
    const __nv_bfloat162 cv = __hsub2(*reinterpret_cast<__nv_bfloat162*>(&u[i]), m1v);
    const uint32_t c = *reinterpret_cast<const uint32_t*>(&cv);
    const uint32_t n = pack_bf2(bf_lo(c) * rden, bf_hi(c) * rden);
    const float a = bf_lo(n), e = bf_hi(n);
    s0 += a; s1 += e; q0 = fmaf(a, a, q0); q1 = fmaf(e, e, q1);
    u[i] = (pack_h2(a, e) & 0xfffefffeu) | tag2;
  }
#pragma unroll
  for (int i = 0; i < 7; i++)
    asm volatile("st.shared.v2.b32 [%0], {%1,%2};" ::"r"(stg_row + (j + 16 * i) * 8), "r"(u[2 * i]), "r"(u[2 * i + 1]) : "memory");
  s = s0 + s1; q = q0 + q1;
  red16x2(s, q);
  s *= (1.f / D_); q *= (1.f / D_);
  const float den2 = rbf(sqrtf_(rbf(rbf(fmaxf(fmaf(-s, s, q), 0.f)) + 1e-5f)));
  if (j == 0) {
    const float ir = den * den2, mu = fmaf(rbf(s), den, __bfloat162float(m1b));
    const float ih = rbf(ir), mh = rbf(mu), ml = rbf(mu - mh);
    g_ax[row] = make_uint4(pack_bf2(ih, ir - ih), pack_bf2(mh, mh), pack_bf2(ml, ml), pack_bf2(mh, mu - mh - ml));
    g_r[row] = rcpf_(ir);
  }
}

__device__ __forceinline__ void poll_tag(const unsigned* p, uint32_t tag) {
#pragma unroll 1
  for (int it = 0; it < 4096; it++) {
    if (!((ld_relaxed1(p) ^ tag) & 1)) break;
    __nanosleep(32);
  }
}
template <int NV, int STRIDE>
__device__ __forceinline__ void recv_part(const uint4* src, uint32_t tag, float* pre) {
  uint4 v[NV];
#pragma unroll 1
  for (int it = 0; it < RETRY_MAX; it++) {
    uint32_t bad = 0;
#pragma unroll
    for (int q = 0; q < NV; q++) v[q] = ld_b128(src + q * STRIDE);
#pragma unroll
    for (int q = 0; q < NV; q++) bad |= v[q].x ^ tag;
    const unsigned m = __ballot_sync(0xffffffffu, bad & 1);
    if (!m) break;
    if ((threadIdx.x & 31) == __ffs(m) - 1) poll_tag((const unsigned*)(src + (NV - 1) * STRIDE), tag);
    __syncwarp();
  }
#pragma unroll
  for (int q = 0; q < NV; q++) {
    const uint32_t u[4] = {v[q].x, v[q].y, v[q].z, v[q].w};
#pragma unroll
    for (int k = 0; k < 4; k++) { pre[8 * q + 2 * k] += bf_lo(u[k]); pre[8 * q + 2 * k + 1] += bf_hi(u[k]); }
  }
}
__device__ __forceinline__ void send_part(uint4* dst, uint32_t tag, const float* a) {
#pragma unroll
  for (int q = 0; q < 4; q++)
    st_b128(dst + q * 256, tag, pack_bf2(a[8 * q], a[8 * q + 1]), pack_bf2(a[8 * q + 2], a[8 * q + 3]),
            pack_bf2(a[8 * q + 4], a[8 * q + 5]), pack_bf2(a[8 * q + 6], a[8 * q + 7]));
}
__device__ __forceinline__ bool last_release(uint32_t cnt) {
  unsigned old;
  asm volatile("atom.relaxed.cta.shared.inc.u32 %0, [%1], 7;" : "=r"(old) : "r"(cnt) : "memory");
  return old == 7;
}
__device__ __forceinline__ int mod7(int v) { return v >= 7 ? v - 7 : v; }

#define IDS const int tid = opaque(tid0), lane = tid & 31, t = tid & 127, wg = tid >> 7, w = (tid >> 5) & 3; \
            (void)lane; (void)t; (void)wg; (void)w;

__global__ void __launch_bounds__(384, 1)
fused_kernel(const __grid_constant__ CUtensorMap tm_x, const __grid_constant__ CUtensorMap tm_w1,
             const __grid_constant__ CUtensorMap tm_w2, const __grid_constant__ CUtensorMap tm_out, const Params p) {
  extern __shared__ __align__(1024) uint8_t smem_raw[];
  const uint32_t sb = smem_u32(smem_raw);
  const uint32_t ms = sb + OFF_M;
  const uint32_t bar0 = ms + M_BAR;
  const int tid0 = threadIdx.x;
  const int b = blockIdx.x;
  const bool is_ssm = b >= NMLP;
  const int G = b / NRK, rk = b - G * NRK;
  const int kc0 = (G + rk) % 7;
  TSTAMP(0);
  {
    IDS
    if (wg == 2 && w == 0) {
      if (lane < 16) { mbar_init(bar0 + 8 * lane, 1); asm volatile("st.shared.b32 [%0], 0;" ::"r"(ms + M_REL + 4 * lane) : "memory"); }
      fence_async();
      if (lane < 3 && !is_ssm) {
        const int kc = mod7(kc0 + lane);
        mbar_expect(bar0 + 8 * lane, 49152);
        tma_2d(sb + OFF_X + lane * 16384, &tm_x, 64 * kc, 128 * G, bar0 + 8 * lane);
        tma_3d(sb + OFF_W + lane * 32768, &tm_w1, 0, 64 * kc, 4 * rk, bar0 + 8 * lane);
      }
    }
    TSTAMP(28);
    const unsigned ep1 = *(volatile unsigned*)&g_epoch + 1;
    uint4 ld[7];
    const int rl = 2 * (tid >> 5) + (lane >> 4);
    if (wg < 2) {
      const uint2* xr = (const uint2*)(p.x + (size_t)(16 * (b & 127) + rl) * D_) + (lane & 15);
#pragma unroll
      for (int i = 0; i < 7; i++) { const uint2 v = __ldg(xr + 16 * i); ld[i].x = v.x; ld[i].y = v.y; }
    } else {
      const uint4* wr = (const uint4*)(p.w1 + (size_t)(t >> 1) * F_ + 16 * (is_ssm ? 0 : b)) + (t & 1);
#pragma unroll
      for (int i = 0; i < 7; i++) ld[i] = __ldg(wr + (size_t)i * 64 * (F_ / 8));
    }
    KgIn kin;
    {
      const int d = is_ssm ? 2 * (112 + 3 * (b - NMLP) + wg) + (w >> 1) : (wg < 2 ? 2 * b + wg : 336 + b);
      kgen_load(p, d, is_ssm ? 2 * (w & 1) : w, is_ssm ? 2 : 1, lane, kin);
    }
    const uint32_t tbl = is_ssm ? sb + (4 * wg + (w >> 1)) * TBL : sb + OFF_T + wg * TBL;
#pragma unroll 1
    for (int i = is_ssm ? t & 63 : t; i < TBL_SC / 16; i += is_ssm ? 64 : 128) sts128(tbl + i * 16, 0u, 0u, 0u, 0u);
    const uint32_t lns = is_ssm ? sb + S_WORK + 2 * S_WGB : sb + OFF_B;
    TSTAMP(31);
    if (wg < 2) {
      uint32_t u[14];
#pragma unroll
      for (int i = 0; i < 7; i++) { u[2 * i] = ld[i].x; u[2 * i + 1] = ld[i].y; }
      ln_rows(u, 16 * (b & 127) + rl, lns + rl * 912, (ep1 & 1) * 0x10001u, lane);
      bar_arrive(7, 384);
    } else {
      const float b1v = __bfloat162float(p.b1[16 * (is_ssm ? 0 : b) + (t & 15)]);
      if (t == 0) asm volatile("st.shared.b32 [%0], %1;" ::"r"(ms + M_EP), "r"(ep1) : "memory");
      float cs[8];
#pragma unroll
      for (int k = 0; k < 8; k++) cs[k] = 0.f;
#pragma unroll
      for (int i = 0; i < 7; i++) {
        const uint32_t uu[4] = {ld[i].x, ld[i].y, ld[i].z, ld[i].w};
#pragma unroll
        for (int k = 0; k < 4; k++) { cs[2 * k] += bf_lo(uu[k]); cs[2 * k + 1] += bf_hi(uu[k]); }
      }
#pragma unroll
      for (int st = 0; st < 3; st++) {
        const int n = 4 >> st;
        const bool up = (lane >> (3 - st)) & 1;
#pragma unroll
        for (int k = 0; k < n; k++) {
          const float give = up ? cs[k] : cs[k + n], keep = up ? cs[k + n] : cs[k];
          cs[k] = keep + __shfl_xor_sync(0xffffffffu, give, 8 >> st);
        }
      }
      cs[0] += __shfl_xor_sync(0xffffffffu, cs[0], 16);
      if (lane < 16) sts32f(ms + M_CSR + (w * 16 + (lane & 1) * 8 + (lane >> 1)) * 4, cs[0]);
      bar_sync(7, 384);
      const uint32_t la = lns + (lane & 15) * 912 + (lane >> 4) * 16 + w * 224;
      uint2* dst = (uint2*)(g_xnT + (size_t)b * 896) + lane + w * 448;
      uint32_t r[28];
#pragma unroll
      for (int k = 0; k < 7; k++) ldsm4t(la + k * 32, r[4 * k], r[4 * k + 1], r[4 * k + 2], r[4 * k + 3]);
      if (b < 128) {
#pragma unroll
        for (int k = 0; k < 14; k++) st_relaxed2(dst + k * 32, r[2 * k], r[2 * k + 1]);
      }
      if (t < 16 && !is_ssm) {
        const uint32_t a = ms + M_CSR + t * 4;
        const float c = -0.5f * ((lds32f(a) + lds32f(a + 64)) + (lds32f(a + 128) + lds32f(a + 192)));
        const float ch = rbf(c), cl = rbf(c - ch);
        const uint32_t hl = pack_bf2(ch, cl);
        g_bx[16 * b + t] = make_uint4(pack_bf2(0.5f * b1v, 0.5f * b1v), hl, hl, pack_bf2(c - ch - cl, ch));
      }
      bar_sync(6, 128);
    }
    TSTAMP(29);
    const uint32_t stg = is_ssm ? sb + S_WORK + wg * S_WGB + w * KSTG : sb + (wg < 2 ? OFF_A + 4 * wg * KSTG : OFF_B) + w * KSTG;
    kgen_warp(kin, is_ssm ? 2 : 1, stg, tbl, lane);
  }
  TSTAMP(1);
  __syncthreads();

  if (is_ssm || __shfl_sync(0xffffffffu, tid0 >> 7, 0) == 2) {
    asm volatile("setmaxnreg.dec.sync.aligned.u32 136;");
    {
      IDS
      if (t == 0 && !is_ssm)
        asm volatile("cp.async.bulk.prefetch.L2.global [%0], %1;" ::"l"(p.w2 + (size_t)(256 * rk + 16 * G) * D_), "r"(16 * D_ * 2) : "memory");
#pragma unroll 1
      for (int c = is_ssm ? 1 : 2; c >= 0; c--) {
        const uint32_t src = is_ssm ? sb + S_WORK + wg * S_WGB + 2 * c * KSTG : sb + (c < 2 ? OFF_A + 4 * c * KSTG : OFF_B);
        ktab_build(src, !is_ssm, w, (is_ssm ? sb + 4 * wg * TBL : sb + OFF_T) + c * TBL, lane);
        if (c == 2) {
          fence_async();
          bar_sync(6, 128);
          if (t == 96) { bulk_s2g(g_tbl + b * (TBL / 16), sb + OFF_T + 2 * TBL, TBL); bulk_commit(); }
        }
      }
      if (tid == 256 + 96) { bulk_wait0(); red_release(&g_cntA); }
      bar_sync(4 + wg, 128);
    }
    TSTAMP(3);
#pragma unroll 1
    for (int pi = 0; pi < 2; pi++) {
      {
        IDS
        if (pi == 1 && (!is_ssm || (b >= NMLP + 12 && wg == 2))) break;
        const unsigned ep1 = lds32(ms + M_EP);
        const int pair = !is_ssm ? b : (pi == 0 ? 112 + 3 * (b - NMLP) : (b < NMLP + 12 ? 172 + 3 * (b - NMLP) : 184 + 2 * (b - NMLP))) + wg;
        const uint32_t work = is_ssm ? sb + S_WORK + wg * S_WGB : sb + OFF_A;
        const uint32_t z = work + SIG_V3 - 1024 + (t >> 6) * 4096 + (t & 63) * 16;
        sts128(z, 0u, 0u, 0u, 0u); sts128(z + SIG, 0u, 0u, 0u, 0u);
        if (t < 72) {
          const uint32_t zu = work + SIG_U + (t & 7) * U_LBO + (t >> 3) * 16;
          sts128(zu, 0u, 0u, 0u, 0u); sts128(zu + SIG, 0u, 0u, 0u, 0u);
        }
        const uint4* src = g_xnT + ((size_t)t * 448 + 2 * pair) * 2;
        uint4 v[4];
#pragma unroll 1
        for (int it = 0; it < RETRY_MAX; it++) {
#pragma unroll
          for (int q = 0; q < 4; q++) v[q] = ld_relaxed4(src + q);
          uint32_t bad = 0;
#pragma unroll
          for (int q = 0; q < 4; q++) bad |= (v[q].x ^ ep1) | (v[q].y ^ ep1) | (v[q].z ^ ep1) | (v[q].w ^ ep1);
          const unsigned m = __ballot_sync(0xffffffffu, bad & 1);
          if (!m) break;
          if (lane == __ffs(m) - 1) poll_tag((const unsigned*)(src + 3) + 3, ep1);
          __syncwarp();
        }
        TSTAMP(5);
        const uint32_t a = work + SIG_U + (2 * (t & 3)) * U_LBO + ((t >> 2) + 9) * 16, M = 0xfffefffeu;
        sts128(a, v[0].x & M, v[0].z & M, v[1].x & M, v[1].z & M);
        sts128(a + U_LBO, v[0].y & M, v[0].w & M, v[1].y & M, v[1].w & M);
        sts128(a + SIG, v[2].x & M, v[2].z & M, v[3].x & M, v[3].z & M);
        sts128(a + SIG + U_LBO, v[2].y & M, v[2].w & M, v[3].y & M, v[3].w & M);
        bar_sync(4 + wg, 128);
#pragma unroll 1
        for (int k = w; k < 6; k += 4) sig_windows(work + (k & 1) * SIG, (k >> 1) * 32 + lane);
        fence_async();
        if (t == 96 && pi == 0) {
          wait_count(&g_cntA, ep1 * NCTA);
          if (b == 0) *(volatile unsigned*)&g_epoch = ep1;
          asm volatile("fence.proxy.async;" ::: "memory");
          if (!is_ssm) {
            mbar_expect(bar0 + 8 * 15, 2048 + 4096 + 512);
            bulk_g2s(sb + OFF_B + B_AX, g_ax + 128 * G, 2048, bar0 + 8 * 15);
            bulk_g2s(sb + OFF_B + B_BX, g_bx + 256 * rk, 4096, bar0 + 8 * 15);
            bulk_g2s(sb + OFF_B + B_R, g_r + 128 * G, 512, bar0 + 8 * 15);
          } else if (b < NMLP + 12 || wg < 2) {
            const int j = (b < NMLP + 12 ? 3 * (b - NMLP) : 2 * (b - NMLP) + 12) + wg;
            mbar_expect(bar0 + 8 * wg, 2 * TBL);
            bulk_g2s(sb + (4 * wg + 2) * TBL, g_tbl + (2 * j + 8) * (TBL / 16), 2 * TBL, bar0 + 8 * wg);
          }
        }
        if (pi == 1) mbar_wait(bar0 + 8 * wg, 0);
        TSTAMP(6);
        bar_sync(is_ssm ? 4 + wg : 3, is_ssm ? 128 : 384);
        TSTAMP(7);
      }
      uint32_t keep[8];
      float res[16];
#pragma unroll 1
      for (int c = 0; c < 2; c++) {
        IDS
        const int wgu = __shfl_sync(0xffffffffu, wg, 0);
        const uint32_t work = is_ssm ? sb + S_WORK + wgu * S_WGB : sb + OFF_A;
        const uint32_t tbl = (is_ssm ? sb + (4 * wgu + 2 * pi) * TBL : sb + OFF_T) + c * TBL;
        conv_channel(tbl, work + c * SIG, is_ssm ? work + 2 * SIG + Y3B : sb + OFF_B, work + 2 * SIG, lds32f(tbl + TBL_SC), w, lane, 4 + wgu, res, 16 + 3 * (2 * pi + c));
        const float os = lds32f(tbl + TBL_SC + 8);
        if (c == 0) {
#pragma unroll
          for (int i = 0; i < 8; i++) keep[i] = pack_bf2(res[2 * i] * os, res[2 * i + 1] * os);
        } else {
          const int pair = !is_ssm ? b : (pi == 0 ? 112 + 3 * (b - NMLP) : (b < NMLP + 12 ? 172 + 3 * (b - NMLP) : 184 + 2 * (b - NMLP))) + wg;
          uint4* dst = g_s2 + ((size_t)(lane & 3) * 224 + pair) * 32 + w * 8 + (lane >> 2);
          const uint32_t tag = lds32(ms + M_EP) & 1;
#pragma unroll
          for (int nt = 0; nt < 4; nt++) {
            const uint32_t n0 = pack_bf2(res[4 * nt] * os, res[4 * nt + 1] * os), n1 = pack_bf2(res[4 * nt + 2] * os, res[4 * nt + 3] * os);
            st_b128(dst + nt * 4 * 224 * 32, tag, __byte_perm(keep[2 * nt], n0, 0x5410), __byte_perm(keep[2 * nt + 1], n1, 0x5410),
                    __byte_perm(keep[2 * nt], n0, 0x7632), __byte_perm(keep[2 * nt + 1], n1, 0x7632));
          }
        }
      }
      TSTAMP(8 + pi);
    }
    if (!is_ssm) {
      IDS
      const uint32_t tag = lds32(ms + M_EP) & 1;
      float pre[64];
#pragma unroll
      for (int i = 0; i < 64; i++) pre[i] = 0.f;
#pragma unroll 1
      for (int s = 0; s < 4; s++) recv_part<8, 128>(g_part + ((size_t)b * 6 + s) * 1024 + t, tag, pre);
      bar_sync(6, 128);
#pragma unroll
      for (int i = 0; i < 16; i++)
        sts128(sb + OFF_A + ((2 * (i >> 2) + (i & 1)) * 256 + ((i >> 1) & 1) * 128 + t) * 16, __float_as_uint(pre[4 * i]),
               __float_as_uint(pre[4 * i + 1]), __float_as_uint(pre[4 * i + 2]), __float_as_uint(pre[4 * i + 3]));
      bar_arrive(2, 384);
      TSTAMP(12);
    }
  } else {
    bar_arrive(1, 384);
    asm volatile("setmaxnreg.inc.sync.aligned.u32 192;");
    bar_sync(7, 384);
    uint32_t H[64];
    {
      float acc[128];
      float p0, q0, p1, q1;
      {
        IDS
        const int wgu = __shfl_sync(0xffffffffu, wg, 0);
        int sl = 0;
#pragma unroll 1
        for (int s = 0; s < 7; s++) {
          mbar_wait(bar0 + 8 * s, 0);
          const uint64_t da = mkdesc(sb + OFF_X + sl * 16384 + wgu * 8192, 16, 1024, 1);
          const uint64_t db = mkdesc(sb + OFF_W + sl * 32768, 8192, 1024, 1);
          wg_fence();
#pragma unroll
          for (int k = 0; k < 4; k++) wg_ss_bf16_n256(acc, da + 2 * k, db + 128 * k, (s | k) != 0);
          wg_commit();
          wg_wait<1>();
          const int pl = sl == 0 ? 2 : sl - 1;
          sl = sl == 2 ? 0 : sl + 1;
          if (s > 0 && lane == 0 && last_release(ms + M_REL + 4 * s)) {
            const uint32_t bx = bar0 + 8 * (s < 5 ? s + 2 : 14);
            mbar_expect(bar0 + 8 * (s + 2), s < 5 ? 49152 : 32768);
            if (s < 5) tma_3d(sb + OFF_W + pl * 32768, &tm_w1, 0, 64 * mod7(kc0 + s + 2), 4 * rk, bar0 + 8 * (s + 2));
            else tma_2d(sb + OFF_W + pl * 32768, &tm_w2, 64 * mod7(rk + s - 4), 256 * rk, bar0 + 8 * (s + 2));
            if (s == 6) mbar_expect(bx, 16384);
            if (s != 5) tma_2d(sb + OFF_X + pl * 16384, &tm_x, 64 * (s < 5 ? mod7(kc0 + s + 2) : rk), 128 * G, bx);
          }
        }
        TSTAMP(9);
        mbar_wait(bar0 + 8 * 15, 0);
        wg_fence();
        wg_ss_bf16_n256k(acc, mkdesc(sb + OFF_B + B_AX + wgu * 1024, 0, 128, 0), mkdesc(sb + OFF_B + B_BX, 0, 128, 0), 1);
        wg_commit();
        wg_wait<1>();
        if (lane == 0 && last_release(ms + M_REL + 4 * 7)) {
#pragma unroll 1
          for (int c = 2; c < 4; c++) {
            mbar_expect(bar0 + 8 * (7 + c), 32768);
            tma_2d(sb + (c - 2) * OFF_X, &tm_w2, 64 * mod7(rk + 1 + c), 256 * rk, bar0 + 8 * (7 + c));
          }
        }
        bar_arrive(3, 384);
        const float r0 = lds32f(sb + OFF_B + B_R + (16 * (tid >> 5) + (lane >> 2)) * 4);
        const float r1 = lds32f(sb + OFF_B + B_R + (16 * (tid >> 5) + (lane >> 2) + 8) * 4);
        p0 = 0.7978845608028654f * r0; q0 = 0.0356774081363001f * r0 * r0 * r0;
        p1 = 0.7978845608028654f * r1; q1 = 0.0356774081363001f * r1 * r1 * r1;
      }
      wg_wait<0>();
      fence_regs<128>(acc);
      TSTAMP(2);
      float hq[4];
#pragma unroll
      for (int i = 0; i < 64; i++) {
        const float pp = (i & 1) ? p1 : p0, qq = (i & 1) ? q1 : q0;
        const float a = acc[2 * i], c = acc[2 * i + 1];
        const float ta = tanhf_(a * fmaf(a * a, qq, pp)), tc = tanhf_(c * fmaf(c * c, qq, pp));
        if (i >= 2) H[i - 2] = pack_bf2v(hq[(i & 1) * 2], hq[(i & 1) * 2 + 1]);
        hq[(i & 1) * 2] = fmaf(a, ta, a); hq[(i & 1) * 2 + 1] = fmaf(c, tc, c);
      }
      H[62] = pack_bf2v(hq[0], hq[1]); H[63] = pack_bf2v(hq[2], hq[3]);
    }
    TSTAMP(3);
    float accA[32], accB[32];
    const uint32_t tag = lds32(ms + M_EP) & 1;
    auto issue2 = [&](int c, float* acc) {
      const uint32_t base = sb + ((0x0213021u >> (4 * c)) & 3) * 32768;
      mbar_wait(bar0 + 8 * (7 + c), 0);
      const uint64_t db = mkdesc(base, 8192, 1024, 1);
      wg_fence();
#pragma unroll
      for (int k = 0; k < 16; k++) wg_rs_bf16_n64(acc, H[4 * k], H[4 * k + 1], H[4 * k + 2], H[4 * k + 3], db + 128 * k, k != 0);
      wg_commit();
    };
    auto process = [&](int s, float* acc) {
      wg_wait<1>();
      fence_regs<32>(acc);
      const int tid = opaque(tid0);
      if (s < 3 && (tid & 31) == 0 && last_release(ms + M_REL + 4 * (8 + s))) {
        mbar_expect(bar0 + 8 * (11 + s), 32768);
        tma_2d(sb + ((0x021u >> (4 * s)) & 3) * 32768, &tm_w2, 64 * mod7(mod7(rk + 5 + s)), 256 * rk, bar0 + 8 * (11 + s));
      }
      send_part(g_part + ((size_t)(G * 7 + mod7(rk + 1 + s)) * 6 + s) * 1024 + tid, tag, acc);
      TSTAMP(10 + s);
    };
    issue2(0, accA);
#pragma unroll
    for (int s = 0; s < 6; s += 2) {
      issue2(s + 1, accB);
      process(s, accA);
      issue2(s + 2, accA);
      process(s + 1, accB);
    }
    TSTAMP(4);
    IDS
    const int g = lane >> 2, tq = lane & 3;
    uint32_t sw[16];
    {
      const uint4* sp = g_s2 + ((size_t)G * 224 + 32 * rk + tq) * 32 + w * 8 + g;
#pragma unroll 1
      for (int it = 0; it < RETRY_MAX; it++) {
        uint32_t bad = 0;
#pragma unroll
        for (int i = 0; i < 8; i++) {
          const uint4 v = ld_b128(sp + i * 4 * 32);
          bad |= ((v.x ^ tag) & 1) << i;
          sw[2 * i] = wg ? v.z : v.x; sw[2 * i + 1] = wg ? v.w : v.y;
        }
        const unsigned m = __ballot_sync(0xffffffffu, bad);
        if (!m) break;
        if (lane == __ffs(m) - 1) poll_tag((const unsigned*)(sp + (__ffs(bad) - 1) * 4 * 32), tag);
        __syncwarp();
      }
    }
    TSTAMP(5);
    uint32_t b2w[8];
#pragma unroll
    for (int i = 0; i < 8; i++) b2w[i] = __ldg((const uint32_t*)(p.b2 + 64 * rk) + 4 * i + tq);
    wg_wait<0>();
    fence_regs<32>(accA);
    TSTAMP(6);
    bar_sync(2, 384);
#pragma unroll
    for (int i = 0; i < 8; i++) {
      const uint4 v = lds128(sb + OFF_A + (i * 256 + tid) * 16);
      accA[4 * i] += __uint_as_float(v.x); accA[4 * i + 1] += __uint_as_float(v.y);
      accA[4 * i + 2] += __uint_as_float(v.z); accA[4 * i + 3] += __uint_as_float(v.w);
    }
    mbar_wait(bar0 + 8 * 14, 0);
    const uint32_t xa = sb + OFF_X + 2 * 16384 + (16 * (tid >> 5) + (lane & 15)) * 128;
    uint32_t xw[16];
#pragma unroll
    for (int q = 0; q < 4; q++) ldsm4(xa + (((2 * q + (lane >> 4)) ^ (lane & 7)) << 4), xw[4 * q], xw[4 * q + 1], xw[4 * q + 2], xw[4 * q + 3]);
    const float r0 = 0.5f * lds32f(sb + OFF_B + B_R + (16 * (tid >> 5) + g) * 4);
    const float r1 = 0.5f * lds32f(sb + OFF_B + B_R + (16 * (tid >> 5) + g + 8) * 4);
#pragma unroll 1
    for (int s = 4; s < 6; s++) recv_part<4, 256>(g_part + ((size_t)b * 6 + s) * 1024 + tid, tag, accA);
    TSTAMP(7);
#pragma unroll
    for (int k = 0; k < 16; k++) {
      const float rr = (k & 1) ? r1 : r0;
      const float o0 = fmaf(accA[2 * k], rr, bf_lo(b2w[k >> 1])), o1 = fmaf(accA[2 * k + 1], rr, bf_hi(b2w[k >> 1]));
      const float g0 = o0 * rcpf_(1.f + ex2f(o0 * -1.4426950408889634f)), g1 = o1 * rcpf_(1.f + ex2f(o1 * -1.4426950408889634f));
      xw[k] = pack_bf2(fmaf(bf_lo(sw[k]), g0, bf_lo(xw[k])), fmaf(bf_hi(sw[k]), g1, bf_hi(xw[k])));
    }
#pragma unroll
    for (int q = 0; q < 4; q++) stsm4(xa + (((2 * q + (lane >> 4)) ^ (lane & 7)) << 4), xw[4 * q], xw[4 * q + 1], xw[4 * q + 2], xw[4 * q + 3]);
    fence_async();
    __syncwarp();
    if (lane == 0) {
      tma_store_2d(&tm_out, sb + OFF_X + 2 * 16384 + (tid >> 5) * 2048, 64 * rk, 128 * G + 16 * (tid >> 5));
      bulk_commit();
      bulk_wait0_read();
    }
    TSTAMP(8);
  }
}

typedef CUresult (*EncodeFn)(CUtensorMap*, CUtensorMapDataType, cuuint32_t, void*, const cuuint64_t*, const cuuint64_t*,
                             const cuuint32_t*, const cuuint32_t*, CUtensorMapInterleave, CUtensorMapSwizzle,
                             CUtensorMapL2promotion, CUtensorMapFloatOOBfill);

void make_map(EncodeFn fn, CUtensorMap* m, const void* ptr, int rank, const cuuint64_t* dims, const cuuint64_t* strides, const cuuint32_t* box) {
  const cuuint32_t es[3] = {1, 1, 1};
  fn(m, CU_TENSOR_MAP_DATA_TYPE_BFLOAT16, rank, const_cast<void*>(ptr), dims, strides, box, es, CU_TENSOR_MAP_INTERLEAVE_NONE,
     CU_TENSOR_MAP_SWIZZLE_128B, CU_TENSOR_MAP_L2_PROMOTION_L2_128B, CU_TENSOR_MAP_FLOAT_OOB_FILL_NONE);
}

}

extern "C" void kernel_launch(void* const* d_in, const int* in_sizes, int n_in, void* d_out, int out_size) {
  (void)in_sizes; (void)n_in; (void)out_size;
  void* fnp = nullptr;
  cudaDriverEntryPointQueryResult qr;
  cudaGetDriverEntryPoint("cuTensorMapEncodeTiled", &fnp, cudaEnableDefault, &qr);
  EncodeFn fn = (EncodeFn)fnp;
  Params p;
  p.x = (const __nv_bfloat16*)d_in[0];
  p.a_re = (const __nv_bfloat16*)d_in[1]; p.a_im = (const __nv_bfloat16*)d_in[2];
  p.b_re = (const __nv_bfloat16*)d_in[3]; p.b_im = (const __nv_bfloat16*)d_in[4];
  p.c_re = (const __nv_bfloat16*)d_in[5]; p.c_im = (const __nv_bfloat16*)d_in[6];
  p.log_dt = (const __nv_bfloat16*)d_in[7]; p.dskip = (const __nv_bfloat16*)d_in[8];
  p.w1 = (const __nv_bfloat16*)d_in[10]; p.b1 = (const __nv_bfloat16*)d_in[11];
  p.w2 = (const __nv_bfloat16*)d_in[12]; p.b2 = (const __nv_bfloat16*)d_in[13];
  CUtensorMap mx, mw1, mw2, mo;
  {
    const cuuint64_t dims[2] = {448, 2048}, str[1] = {896};
    const cuuint32_t box[2] = {64, 128}, boxo[2] = {64, 16};
    make_map(fn, &mx, p.x, 2, dims, str, box);
    make_map(fn, &mo, d_out, 2, dims, str, boxo);
  }
  {
    const cuuint64_t dims[3] = {64, 448, 28}, str[2] = {3584, 128};
    const cuuint32_t box[3] = {64, 64, 4};
    make_map(fn, &mw1, p.w1, 3, dims, str, box);
  }
  {
    const cuuint64_t dims[2] = {448, 1792}, str[1] = {896};
    const cuuint32_t box[2] = {64, 256};
    make_map(fn, &mw2, p.w2, 2, dims, str, box);
  }
  cudaFuncSetAttribute(fused_kernel, cudaFuncAttributeMaxDynamicSharedMemorySize, SMEM_BYTES);
  fused_kernel<<<NCTA, 384, SMEM_BYTES>>>(mx, mw1, mw2, mo, p);
}
```

```cpp
#include <cuda_runtime.h>
#include <cuda_bf16.h>
#include <cuda_fp16.h>
#include <cuda.h>
#include <stdint.h>

namespace {

constexpr int D_ = 448, NST = 256, F_ = 1792;
constexpr int NRK = 7, NMLP = 112, NCTA = 132;
constexpr int SPIN_MAX = 1 << 20, RETRY_MAX = 512;

__device__ uint4 g_xnT[224 * 512];
__device__ uint4 g_ax[2048];
__device__ float g_r[2048];
__device__ uint4 g_bx[7 * 512];
__device__ uint4 g_part[16 * 7 * 6 * 1024];
__device__ uint4 g_s2[16 * 224 * 32];
__device__ uint4 g_tbl[112 * 329];
__device__ unsigned g_cntA;
__device__ unsigned g_epoch;
#define TSTAMP(i)

constexpr int TBL_SC = 5248, TBL = 5264;
constexpr int TBL_C1 = 2624;
constexpr int SIG = 19584;
constexpr int SIG_U = 0, U_LBO = 656, SIG_V3 = 6272, SIG_V5 = 10368, SIG_V7 = 13440, SIG_V9 = 15488, SIG_V2 = 17536;
constexpr int Y2B = 6528, Y3B = 4352;
constexpr int KREC = 160, KSTG = 32 * KREC;
constexpr int OFF_W = 0, OFF_X = 98304, OFF_A = 147456, OFF_B = OFF_A + 8 * KSTG + 2560, OFF_T = OFF_B + 4 * KSTG;
constexpr int OFF_M = OFF_T + 15872;
constexpr int B_AX = Y2B, B_BX = B_AX + 2048, B_R = B_BX + 8192;
constexpr int M_BAR = 0, M_REL = 128, M_EP = 192, M_CSR = 256, M_END = 1280;
constexpr int SMEM_BYTES = OFF_M + M_END;
constexpr int S_WORK = 63232, S_WGB = 2 * SIG + Y2B + Y3B;
static_assert(S_WORK + 3 * S_WGB <= OFF_M && SMEM_BYTES <= 232448, "smem");

struct Params {
  const __nv_bfloat16 *x, *a_re, *a_im, *b_re, *b_im, *c_re, *c_im, *log_dt, *dskip, *w1, *b1, *w2, *b2;
};

__device__ __forceinline__ int opaque(int x) { int v; asm volatile("mov.u32 %0, %1;" : "=r"(v) : "r"(x)); return v; }
__device__ __forceinline__ int rd_bid() { int v; asm volatile("mov.u32 %0, %%ctaid.x;" : "=r"(v)); return v; }
__device__ __forceinline__ uint32_t smem_u32(const void* p) { return (uint32_t)__cvta_generic_to_shared(p); }
__device__ __forceinline__ void mbar_init(uint32_t bar, int cnt) { asm volatile("mbarrier.init.shared::cta.b64 [%0], %1;" ::"r"(bar), "r"(cnt)); }
__device__ __forceinline__ void mbar_expect(uint32_t bar, uint32_t bytes) {
  asm volatile("mbarrier.arrive.expect_tx.shared::cta.b64 _, [%0], %1;" ::"r"(bar), "r"(bytes) : "memory");
}
__device__ __forceinline__ void mbar_wait(uint32_t bar, uint32_t parity) {
  uint32_t done = 0;
#pragma unroll 1
  for (int it = 0; it < SPIN_MAX; it++) {
    asm volatile("{.reg .pred p; mbarrier.try_wait.parity.shared::cta.b64 p, [%1], %2; selp.u32 %0,1,0,p;}"
                 : "=r"(done) : "r"(bar), "r"(parity) : "memory");
    if (done) break;
  }
}
__device__ __forceinline__ void tma_2d(uint32_t dst, const CUtensorMap* m, int c0, int c1, uint32_t bar) {
  asm volatile("cp.async.bulk.tensor.2d.shared::cluster.global.mbarrier::complete_tx::bytes [%0], [%1, {%3, %4}], [%2];"
               ::"r"(dst), "l"(m), "r"(bar), "r"(c0), "r"(c1) : "memory");
}
__device__ __forceinline__ void tma_3d(uint32_t dst, const CUtensorMap* m, int c0, int c1, int c2, uint32_t bar) {
  asm volatile("cp.async.bulk.tensor.3d.shared::cluster.global.mbarrier::complete_tx::bytes [%0], [%1, {%3, %4, %5}], [%2];"
               ::"r"(dst), "l"(m), "r"(bar), "r"(c0), "r"(c1), "r"(c2) : "memory");
}
__device__ __forceinline__ void tma_store_2d(const CUtensorMap* m, uint32_t src, int c0, int c1) {
  asm volatile("cp.async.bulk.tensor.2d.global.shared::cta.bulk_group [%0, {%2, %3}], [%1];"
               ::"l"(m), "r"(src), "r"(c0), "r"(c1) : "memory");
}
__device__ __forceinline__ void bulk_s2g(void* dst, uint32_t src, uint32_t bytes) {
  asm volatile("cp.async.bulk.global.shared::cta.bulk_group [%0], [%1], %2;" ::"l"(dst), "r"(src), "r"(bytes) : "memory");
}
__device__ __forceinline__ void bulk_g2s(uint32_t dst, const void* src, uint32_t bytes, uint32_t bar) {
  asm volatile("cp.async.bulk.shared::cluster.global.mbarrier::complete_tx::bytes [%0], [%1], %2, [%3];"
               ::"r"(dst), "l"(src), "r"(bytes), "r"(bar) : "memory");
}
__device__ __forceinline__ void bulk_commit() { asm volatile("cp.async.bulk.commit_group;" ::: "memory"); }
__device__ __forceinline__ void bulk_wait0() { asm volatile("cp.async.bulk.wait_group 0;" ::: "memory"); }
__device__ __forceinline__ void bulk_wait0_read() { asm volatile("cp.async.bulk.wait_group.read 0;" ::: "memory"); }
__device__ __forceinline__ void fence_async() { asm volatile("fence.proxy.async.shared::cta;" ::: "memory"); }
__device__ __forceinline__ void bar_sync(int id, int n) { asm volatile("bar.sync %0, %1;" ::"r"(id), "r"(n) : "memory"); }
__device__ __forceinline__ void bar_arrive(int id, int n) { asm volatile("bar.arrive %0, %1;" ::"r"(id), "r"(n) : "memory"); }
__device__ __forceinline__ void wg_fence() { asm volatile("wgmma.fence.sync.aligned;" ::: "memory"); }
__device__ __forceinline__ void wg_commit() { asm volatile("wgmma.commit_group.sync.aligned;" ::: "memory"); }
template <int N> __device__ __forceinline__ void wg_wait() { asm volatile("wgmma.wait_group.sync.aligned %0;" ::"n"(N) : "memory"); }
template <int N> __device__ __forceinline__ void fence_regs(float* d) {
#pragma unroll
  for (int i = 0; i < N; i++) asm volatile("" : "+f"(d[i])::"memory");
}
__device__ __forceinline__ uint64_t mkdesc(uint32_t addr, uint32_t lbo, uint32_t sbo, uint32_t sw) {
  return (uint64_t)((addr & 0x3FFFF) >> 4) | ((uint64_t)(lbo >> 4) << 16) | ((uint64_t)(sbo >> 4) << 32) | ((uint64_t)sw << 62);
}
__device__ __forceinline__ uint32_t lds32(uint32_t a) { uint32_t v; asm volatile("ld.shared.b32 %0, [%1];" : "=r"(v) : "r"(a) : "memory"); return v; }
__device__ __forceinline__ float lds32f(uint32_t a) { float v; asm volatile("ld.shared.f32 %0, [%1];" : "=f"(v) : "r"(a) : "memory"); return v; }
__device__ __forceinline__ float2 lds64f(uint32_t a) { float2 v; asm volatile("ld.shared.v2.f32 {%0,%1}, [%2];" : "=f"(v.x), "=f"(v.y) : "r"(a) : "memory"); return v; }
__device__ __forceinline__ uint4 lds128(uint32_t a) {
  uint4 v; asm volatile("ld.shared.v4.b32 {%0,%1,%2,%3}, [%4];" : "=r"(v.x), "=r"(v.y), "=r"(v.z), "=r"(v.w) : "r"(a) : "memory"); return v;
}
__device__ __forceinline__ void sts16(uint32_t a, uint16_t v) { asm volatile("st.shared.b16 [%0], %1;" ::"r"(a), "h"(v) : "memory"); }
__device__ __forceinline__ void sts32f(uint32_t a, float v) { asm volatile("st.shared.f32 [%0], %1;" ::"r"(a), "f"(v) : "memory"); }
__device__ __forceinline__ void sts64f(uint32_t a, float x, float y) { asm volatile("st.shared.v2.f32 [%0], {%1,%2};" ::"r"(a), "f"(x), "f"(y) : "memory"); }
__device__ __forceinline__ void sts128(uint32_t a, uint32_t x, uint32_t y, uint32_t z, uint32_t w) {
  asm volatile("st.shared.v4.b32 [%0], {%1,%2,%3,%4};" ::"r"(a), "r"(x), "r"(y), "r"(z), "r"(w) : "memory");
}
__device__ __forceinline__ void ldsm4(uint32_t a, uint32_t& r0, uint32_t& r1, uint32_t& r2, uint32_t& r3) {
  asm volatile("ldmatrix.sync.aligned.m8n8.x4.shared.b16 {%0,%1,%2,%3}, [%4];" : "=r"(r0), "=r"(r1), "=r"(r2), "=r"(r3) : "r"(a) : "memory");
}
__device__ __forceinline__ void ldsm4t(uint32_t a, uint32_t& r0, uint32_t& r1, uint32_t& r2, uint32_t& r3) {
  asm volatile("ldmatrix.sync.aligned.m8n8.x4.trans.shared.b16 {%0,%1,%2,%3}, [%4];" : "=r"(r0), "=r"(r1), "=r"(r2), "=r"(r3) : "r"(a) : "memory");
}
__device__ __forceinline__ void ldsm2t(uint32_t a, uint32_t& r0, uint32_t& r1) {
  asm volatile("ldmatrix.sync.aligned.m8n8.x2.trans.shared.b16 {%0,%1}, [%2];" : "=r"(r0), "=r"(r1) : "r"(a) : "memory");
}
__device__ __forceinline__ void stsm4(uint32_t a, uint32_t r0, uint32_t r1, uint32_t r2, uint32_t r3) {
  asm volatile("stmatrix.sync.aligned.m8n8.x4.shared.b16 [%0], {%1,%2,%3,%4};" ::"r"(a), "r"(r0), "r"(r1), "r"(r2), "r"(r3) : "memory");
}
__device__ __forceinline__ void mma_f16(float* c, uint32_t a0, uint32_t a1, uint32_t a2, uint32_t a3, uint32_t b0, uint32_t b1) {
  asm volatile("mma.sync.aligned.m16n8k16.row.col.f32.f16.f16.f32 {%0,%1,%2,%3},{%4,%5,%6,%7},{%8,%9},{%0,%1,%2,%3};"
               : "+f"(c[0]), "+f"(c[1]), "+f"(c[2]), "+f"(c[3]) : "r"(a0), "r"(a1), "r"(a2), "r"(a3), "r"(b0), "r"(b1));
}
__device__ __forceinline__ uint4 ld_relaxed4(const void* p) {
  uint4 v; asm volatile("ld.relaxed.gpu.global.v4.b32 {%0,%1,%2,%3}, [%4];" : "=r"(v.x), "=r"(v.y), "=r"(v.z), "=r"(v.w) : "l"(p) : "memory"); return v;
}
__device__ __forceinline__ void st_relaxed2(void* p, uint32_t x, uint32_t y) {
  asm volatile("st.relaxed.gpu.global.v2.b32 [%0], {%1,%2};" ::"l"(p), "r"(x), "r"(y) : "memory");
}
__device__ __forceinline__ uint4 ld_b128(const void* p) {
  uint4 v;
  asm volatile("{.reg .b128 t; .reg .b64 a, c; ld.relaxed.gpu.global.b128 t, [%4]; mov.b128 {a, c}, t; mov.b64 {%0,%1}, a; mov.b64 {%2,%3}, c;}"
               : "=r"(v.x), "=r"(v.y), "=r"(v.z), "=r"(v.w) : "l"(p) : "memory");
  return v;
}
__device__ __forceinline__ void st_b128(void* p, uint32_t tag, uint32_t x, uint32_t y, uint32_t z, uint32_t w) {
  asm volatile("{.reg .b128 t; .reg .b64 a, c; mov.b64 a, {%1,%2}; mov.b64 c, {%3,%4}; mov.b128 t, {a, c}; st.relaxed.gpu.global.b128 [%0], t;}"
               ::"l"(p), "r"((x & ~1u) | tag), "r"(y), "r"(z), "r"(w) : "memory");
}
__device__ __forceinline__ unsigned ld_relaxed1(const unsigned* p) {
  unsigned v; asm volatile("ld.relaxed.gpu.global.u32 %0, [%1];" : "=r"(v) : "l"(p) : "memory"); return v;
}
__device__ __forceinline__ void red_release(unsigned* p) {
  asm volatile("red.release.gpu.global.add.u32 [%0], 1;" ::"l"(p) : "memory");
}
__device__ __forceinline__ void wait_count(const unsigned* p, unsigned target) {
#pragma unroll 1
  for (int it = 0; it < SPIN_MAX; it++) {
    if ((int)(ld_relaxed1(p) - target) >= 0) break;
    __nanosleep(40);
  }
  asm volatile("fence.acq_rel.gpu;" ::: "memory");
}
__device__ __forceinline__ uint32_t pack_h2(float lo, float hi) { uint32_t r; asm("cvt.rn.f16x2.f32 %0, %1, %2;" : "=r"(r) : "f"(hi), "f"(lo)); return r; }
__device__ __forceinline__ uint32_t pack_bf2(float lo, float hi) { uint32_t r; asm("cvt.rn.bf16x2.f32 %0, %1, %2;" : "=r"(r) : "f"(hi), "f"(lo)); return r; }
__device__ __forceinline__ uint32_t pack_bf2v(float lo, float hi) { uint32_t r; asm volatile("cvt.rn.bf16x2.f32 %0, %1, %2;" : "=r"(r) : "f"(hi), "f"(lo)); return r; }
__device__ __forceinline__ float bf_lo(uint32_t w) { return __uint_as_float(w << 16); }
__device__ __forceinline__ float bf_hi(uint32_t w) { return __uint_as_float(w & 0xffff0000u); }
__device__ __forceinline__ float rbf(float v) { return __bfloat162float(__float2bfloat16_rn(v)); }
__device__ __forceinline__ float2 h2f(uint32_t w) { return __half22float2(*reinterpret_cast<__half2*>(&w)); }
__device__ __forceinline__ float ex2f(float v) { float r; asm("ex2.approx.ftz.f32 %0, %1;" : "=f"(r) : "f"(v)); return r; }
__device__ __forceinline__ float rcpf_(float v) { float r; asm("rcp.approx.f32 %0, %1;" : "=f"(r) : "f"(v)); return r; }
__device__ __forceinline__ float sqrtf_(float v) { float r; asm("sqrt.approx.f32 %0, %1;" : "=f"(r) : "f"(v)); return r; }
__device__ __forceinline__ float tanhf_(float v) { float r; asm volatile("tanh.approx.f32 %0, %1;" : "=f"(r) : "f"(v)); return r; }

__device__ __forceinline__ void wg_ss_bf16_n256(float* d, uint64_t da, uint64_t db, int sc) {
  asm volatile("{.reg .pred p; setp.ne.b32 p, %130, 0;\n"
    "wgmma.mma_async.sync.aligned.m64n256k16.f32.bf16.bf16 {%0, %1, %2, %3, %4, %5, %6, %7, %8, %9, %10, %11, %12, %13, %14, %15, %16, %17, %18, %19, %20, %21, %22, %23, %24, %25, %26, %27, %28, %29, %30, %31, %32, %33, %34, %35, %36, %37, %38, %39, %40, %41, %42, %43, %44, %45, %46, %47, %48, %49, %50, %51, %52, %53, %54, %55, %56, %57, %58, %59, %60, %61, %62, %63, %64, %65, %66, %67, %68, %69, %70, %71, %72, %73, %74, %75, %76, %77, %78, %79, %80, %81, %82, %83, %84, %85, %86, %87, %88, %89, %90, %91, %92, %93, %94, %95, %96, %97, %98, %99, %100, %101, %102, %103, %104, %105, %106, %107, %108, %109, %110, %111, %112, %113, %114, %115, %116, %117, %118, %119, %120, %121, %122, %123, %124, %125, %126, %127}, %128, %129, p, 1, 1, 0, 1;}\n"
    : "+f"(d[0]), "+f"(d[1]), "+f"(d[2]), "+f"(d[3]), "+f"(d[4]), "+f"(d[5]), "+f"(d[6]), "+f"(d[7]), "+f"(d[8]), "+f"(d[9]), "+f"(d[10]), "+f"(d[11]), "+f"(d[12]), "+f"(d[13]), "+f"(d[14]), "+f"(d[15]), "+f"(d[16]), "+f"(d[17]), "+f"(d[18]), "+f"(d[19]), "+f"(d[20]), "+f"(d[21]), "+f"(d[22]), "+f"(d[23]), "+f"(d[24]), "+f"(d[25]), "+f"(d[26]), "+f"(d[27]), "+f"(d[28]), "+f"(d[29]), "+f"(d[30]), "+f"(d[31]), "+f"(d[32]), "+f"(d[33]), "+f"(d[34]), "+f"(d[35]), "+f"(d[36]), "+f"(d[37]), "+f"(d[38]), "+f"(d[39]), "+f"(d[40]), "+f"(d[41]), "+f"(d[42]), "+f"(d[43]), "+f"(d[44]), "+f"(d[45]), "+f"(d[46]), "+f"(d[47]), "+f"(d[48]), "+f"(d[49]), "+f"(d[50]), "+f"(d[51]), "+f"(d[52]), "+f"(d[53]), "+f"(d[54]), "+f"(d[55]), "+f"(d[56]), "+f"(d[57]), "+f"(d[58]), "+f"(d[59]), "+f"(d[60]), "+f"(d[61]), "+f"(d[62]), "+f"(d[63]), "+f"(d[64]), "+f"(d[65]), "+f"(d[66]), "+f"(d[67]), "+f"(d[68]), "+f"(d[69]), "+f"(d[70]), "+f"(d[71]), "+f"(d[72]), "+f"(d[73]), "+f"(d[74]), "+f"(d[75]), "+f"(d[76]), "+f"(d[77]), "+f"(d[78]), "+f"(d[79]), "+f"(d[80]), "+f"(d[81]), "+f"(d[82]), "+f"(d[83]), "+f"(d[84]), "+f"(d[85]), "+f"(d[86]), "+f"(d[87]), "+f"(d[88]), "+f"(d[89]), "+f"(d[90]), "+f"(d[91]), "+f"(d[92]), "+f"(d[93]), "+f"(d[94]), "+f"(d[95]), "+f"(d[96]), "+f"(d[97]), "+f"(d[98]), "+f"(d[99]), "+f"(d[100]), "+f"(d[101]), "+f"(d[102]), "+f"(d[103]), "+f"(d[104]), "+f"(d[105]), "+f"(d[106]), "+f"(d[107]), "+f"(d[108]), "+f"(d[109]), "+f"(d[110]), "+f"(d[111]), "+f"(d[112]), "+f"(d[113]), "+f"(d[114]), "+f"(d[115]), "+f"(d[116]), "+f"(d[117]), "+f"(d[118]), "+f"(d[119]), "+f"(d[120]), "+f"(d[121]), "+f"(d[122]), "+f"(d[123]), "+f"(d[124]), "+f"(d[125]), "+f"(d[126]), "+f"(d[127])
    : "l"(da), "l"(db), "r"(sc));
}

__device__ __forceinline__ void wg_ss_bf16_n256k(float* d, uint64_t da, uint64_t db, int sc) {
  asm volatile("{.reg .pred p; setp.ne.b32 p, %130, 0;\n"
    "wgmma.mma_async.sync.aligned.m64n256k16.f32.bf16.bf16 {%0, %1, %2, %3, %4, %5, %6, %7, %8, %9, %10, %11, %12, %13, %14, %15, %16, %17, %18, %19, %20, %21, %22, %23, %24, %25, %26, %27, %28, %29, %30, %31, %32, %33, %34, %35, %36, %37, %38, %39, %40, %41, %42, %43, %44, %45, %46, %47, %48, %49, %50, %51, %52, %53, %54, %55, %56, %57, %58, %59, %60, %61, %62, %63, %64, %65, %66, %67, %68, %69, %70, %71, %72, %73, %74, %75, %76, %77, %78, %79, %80, %81, %82, %83, %84, %85, %86, %87, %88, %89, %90, %91, %92, %93, %94, %95, %96, %97, %98, %99, %100, %101, %102, %103, %104, %105, %106, %107, %108, %109, %110, %111, %112, %113, %114, %115, %116, %117, %118, %119, %120, %121, %122, %123, %124, %125, %126, %127}, %128, %129, p, 1, 1, 0, 0;}\n"
    : "+f"(d[0]), "+f"(d[1]), "+f"(d[2]), "+f"(d[3]), "+f"(d[4]), "+f"(d[5]), "+f"(d[6]), "+f"(d[7]), "+f"(d[8]), "+f"(d[9]), "+f"(d[10]), "+f"(d[11]), "+f"(d[12]), "+f"(d[13]), "+f"(d[14]), "+f"(d[15]), "+f"(d[16]), "+f"(d[17]), "+f"(d[18]), "+f"(d[19]), "+f"(d[20]), "+f"(d[21]), "+f"(d[22]), "+f"(d[23]), "+f"(d[24]), "+f"(d[25]), "+f"(d[26]), "+f"(d[27]), "+f"(d[28]), "+f"(d[29]), "+f"(d[30]), "+f"(d[31]), "+f"(d[32]), "+f"(d[33]), "+f"(d[34]), "+f"(d[35]), "+f"(d[36]), "+f"(d[37]), "+f"(d[38]), "+f"(d[39]), "+f"(d[40]), "+f"(d[41]), "+f"(d[42]), "+f"(d[43]), "+f"(d[44]), "+f"(d[45]), "+f"(d[46]), "+f"(d[47]), "+f"(d[48]), "+f"(d[49]), "+f"(d[50]), "+f"(d[51]), "+f"(d[52]), "+f"(d[53]), "+f"(d[54]), "+f"(d[55]), "+f"(d[56]), "+f"(d[57]), "+f"(d[58]), "+f"(d[59]), "+f"(d[60]), "+f"(d[61]), "+f"(d[62]), "+f"(d[63]), "+f"(d[64]), "+f"(d[65]), "+f"(d[66]), "+f"(d[67]), "+f"(d[68]), "+f"(d[69]), "+f"(d[70]), "+f"(d[71]), "+f"(d[72]), "+f"(d[73]), "+f"(d[74]), "+f"(d[75]), "+f"(d[76]), "+f"(d[77]), "+f"(d[78]), "+f"(d[79]), "+f"(d[80]), "+f"(d[81]), "+f"(d[82]), "+f"(d[83]), "+f"(d[84]), "+f"(d[85]), "+f"(d[86]), "+f"(d[87]), "+f"(d[88]), "+f"(d[89]), "+f"(d[90]), "+f"(d[91]), "+f"(d[92]), "+f"(d[93]), "+f"(d[94]), "+f"(d[95]), "+f"(d[96]), "+f"(d[97]), "+f"(d[98]), "+f"(d[99]), "+f"(d[100]), "+f"(d[101]), "+f"(d[102]), "+f"(d[103]), "+f"(d[104]), "+f"(d[105]), "+f"(d[106]), "+f"(d[107]), "+f"(d[108]), "+f"(d[109]), "+f"(d[110]), "+f"(d[111]), "+f"(d[112]), "+f"(d[113]), "+f"(d[114]), "+f"(d[115]), "+f"(d[116]), "+f"(d[117]), "+f"(d[118]), "+f"(d[119]), "+f"(d[120]), "+f"(d[121]), "+f"(d[122]), "+f"(d[123]), "+f"(d[124]), "+f"(d[125]), "+f"(d[126]), "+f"(d[127])
    : "l"(da), "l"(db), "r"(sc));
}

__device__ __forceinline__ void wg_rs_bf16_n64(float* d, uint32_t a0, uint32_t a1, uint32_t a2, uint32_t a3, uint64_t db, int sc) {
  asm volatile("{.reg .pred p; setp.ne.b32 p, %37, 0;\n"
    "wgmma.mma_async.sync.aligned.m64n64k16.f32.bf16.bf16 {%0, %1, %2, %3, %4, %5, %6, %7, %8, %9, %10, %11, %12, %13, %14, %15, %16, %17, %18, %19, %20, %21, %22, %23, %24, %25, %26, %27, %28, %29, %30, %31}, {%32,%33,%34,%35}, %36, p, 1, 1, 1;}\n"
    : "+f"(d[0]), "+f"(d[1]), "+f"(d[2]), "+f"(d[3]), "+f"(d[4]), "+f"(d[5]), "+f"(d[6]), "+f"(d[7]), "+f"(d[8]), "+f"(d[9]), "+f"(d[10]), "+f"(d[11]), "+f"(d[12]), "+f"(d[13]), "+f"(d[14]), "+f"(d[15]), "+f"(d[16]), "+f"(d[17]), "+f"(d[18]), "+f"(d[19]), "+f"(d[20]), "+f"(d[21]), "+f"(d[22]), "+f"(d[23]), "+f"(d[24]), "+f"(d[25]), "+f"(d[26]), "+f"(d[27]), "+f"(d[28]), "+f"(d[29]), "+f"(d[30]), "+f"(d[31])
    : "r"(a0), "r"(a1), "r"(a2), "r"(a3), "l"(db), "r"(sc));
}

__device__ __forceinline__ void wg_rs_f16_n32k(float* d, uint32_t a0, uint32_t a1, uint32_t a2, uint32_t a3, uint64_t db, int sc) {
  asm volatile("{.reg .pred p; setp.ne.b32 p, %21, 0;\n"
    "wgmma.mma_async.sync.aligned.m64n32k16.f32.f16.f16 {%0, %1, %2, %3, %4, %5, %6, %7, %8, %9, %10, %11, %12, %13, %14, %15}, {%16,%17,%18,%19}, %20, p, 1, 1, 0;}\n"
    : "+f"(d[0]), "+f"(d[1]), "+f"(d[2]), "+f"(d[3]), "+f"(d[4]), "+f"(d[5]), "+f"(d[6]), "+f"(d[7]), "+f"(d[8]), "+f"(d[9]), "+f"(d[10]), "+f"(d[11]), "+f"(d[12]), "+f"(d[13]), "+f"(d[14]), "+f"(d[15])
    : "r"(a0), "r"(a1), "r"(a2), "r"(a3), "l"(db), "r"(sc));
}

__device__ __forceinline__ void wg_rs_f16_n24t(float* d, uint32_t a0, uint32_t a1, uint32_t a2, uint32_t a3, uint64_t db, int sc) {
  asm volatile("{.reg .pred p; setp.ne.b32 p, %17, 0;\n"
    "wgmma.mma_async.sync.aligned.m64n24k16.f32.f16.f16 {%0, %1, %2, %3, %4, %5, %6, %7, %8, %9, %10, %11}, {%12,%13,%14,%15}, %16, p, 1, 1, 1;}\n"
    : "+f"(d[0]), "+f"(d[1]), "+f"(d[2]), "+f"(d[3]), "+f"(d[4]), "+f"(d[5]), "+f"(d[6]), "+f"(d[7]), "+f"(d[8]), "+f"(d[9]), "+f"(d[10]), "+f"(d[11])
    : "r"(a0), "r"(a1), "r"(a2), "r"(a3), "l"(db), "r"(sc));
}

__device__ __forceinline__ void wg_rs_f16_n16t(float* d, uint32_t a0, uint32_t a1, uint32_t a2, uint32_t a3, uint64_t db, int sc) {
  asm volatile("{.reg .pred p; setp.ne.b32 p, %13, 0;\n"
    "wgmma.mma_async.sync.aligned.m64n16k16.f32.f16.f16 {%0, %1, %2, %3, %4, %5, %6, %7}, {%8,%9,%10,%11}, %12, p, 1, 1, 1;}\n"
    : "+f"(d[0]), "+f"(d[1]), "+f"(d[2]), "+f"(d[3]), "+f"(d[4]), "+f"(d[5]), "+f"(d[6]), "+f"(d[7])
    : "r"(a0), "r"(a1), "r"(a2), "r"(a3), "l"(db), "r"(sc));
}

struct cf { float x, y; };
__device__ __forceinline__ cf cmul(cf a, cf b) { cf r; r.x = fmaf(a.x, b.x, -a.y * b.y); r.y = fmaf(a.x, b.y, a.y * b.x); return r; }
__device__ __forceinline__ cf zpow(float rho2, float phi, float e) {
  const float m = ex2f(rho2 * e), ang = phi * e;
  cf r; r.x = m * __cosf(ang); r.y = m * __sinf(ang); return r;
}
__device__ __forceinline__ __half2 H2(uint32_t v) { return *reinterpret_cast<__half2*>(&v); }
__device__ __forceinline__ uint32_t U32(__half2 v) { return *reinterpret_cast<uint32_t*>(&v); }
__device__ __forceinline__ uint32_t hprod(uint32_t v, uint32_t r, uint32_t rr) {
  return U32(__hfma2(__high2half2(H2(v)), H2(rr), __hmul2(__low2half2(H2(v)), H2(r))));
}
__device__ __forceinline__ void hprod2(uint32_t re, uint32_t im, uint32_t r, uint32_t& ore, uint32_t& oim) {
  const __half2 rx = __low2half2(H2(r)), ry = __high2half2(H2(r));
  ore = U32(__hfma2(H2(re), rx, __hneg2(__hmul2(H2(im), ry))));
  oim = U32(__hfma2(H2(re), ry, __hmul2(H2(im), rx)));
}
__device__ __forceinline__ uint32_t rot90(uint32_t v) { return __byte_perm(v, 0, 0x1032) ^ 0x00008000u; }
__device__ __forceinline__ uint32_t hadd2u(uint32_t a, uint32_t b) { return U32(__hadd2(H2(a), H2(b))); }

struct KgIn { uint32_t cur[6], nxt[6]; uint4 m[4]; uint16_t ldt, dk; };
__device__ __forceinline__ void kgen_load(const Params& p, int d, int wd0, int nw, int lane, KgIn& k) {
  const int off = d * (NST / 2) + lane * 4;
  const uint32_t* P[6] = {(const uint32_t*)p.a_re, (const uint32_t*)p.a_im, (const uint32_t*)p.b_re,
                          (const uint32_t*)p.b_im, (const uint32_t*)p.c_re, (const uint32_t*)p.c_im};
  k.ldt = __ldg((const uint16_t*)p.log_dt + d); k.dk = __ldg((const uint16_t*)p.dskip + d);
#pragma unroll
  for (int i = 0; i < 4; i++) k.m[i] = __ldg((const uint4*)(P[2 + i] + off));
#pragma unroll
  for (int i = 0; i < 6; i++) { k.cur[i] = __ldg(P[i] + off + wd0); k.nxt[i] = __ldg(P[i] + off + wd0 + nw - 1); }
}
__device__ __forceinline__ void kgen_warp(KgIn& k, int nw, uint32_t stg, uint32_t tbl, int lane) {
  float dl, dt, inv_sc;
  {
    const uint32_t M = 0x7fff7fffu;
    uint32_t mx[2];
#pragma unroll
    for (int i = 0; i < 2; i++) {
      const uint4 a = k.m[2 * i], c = k.m[2 * i + 1];
      const uint32_t m = __vmaxu2(__vmaxu2(__vmaxu2(a.x & M, a.y & M), __vmaxu2(a.z & M, a.w & M)),
                                  __vmaxu2(__vmaxu2(c.x & M, c.y & M), __vmaxu2(c.z & M, c.w & M)));
      mx[i] = __reduce_max_sync(0xffffffffu, max(m << 16, m & 0xffff0000u));
    }
    dt = rbf(ex2f(bf_lo(k.ldt) * 1.4426950408889634f));
    const float dsk = bf_lo(k.dk) * rcpf_(dt);
    float sc = fmaxf(0.125f * __uint_as_float(mx[0]) * __uint_as_float(mx[1]), fabsf(dsk) * (1.f / 4096.f));
    sc = __uint_as_float(__float_as_uint(fminf(fmaxf(sc, 1e-30f), 1e30f)) & 0x7f800000u);
    inv_sc = rcpf_(sc);
    if (lane == 0) sts64f(tbl + TBL_SC + 8, dt * sc, dsk * inv_sc);
    dl = dt * 1.4426950408889634f;
  }
  const uint32_t st0 = stg + lane * KREC + (((lane >> 2) & 1) << 4), st1 = st0 ^ 16;
  const int mat = lane >> 3, rowi = lane & 7;
  const uint32_t ldB = stg + (4 * (mat & 1) + (rowi >> 1)) * KREC + ((((mat >> 1) * 2 + (rowi & 1)) << 4) ^ ((mat & 1) << 4));
  const uint32_t ldA = stg + (4 * (mat >> 1) + (rowi >> 1)) * KREC + ((((mat & 1) * 2 + (rowi & 1)) << 4) ^ ((mat >> 1) << 4)) + 96;
  const int csrc = 20 + (lane & 3);
  float acc[24];
#pragma unroll
  for (int i = 0; i < 24; i++) acc[i] = 0.f;
#pragma unroll 1
  for (int it = 0; it < 2 * nw; it++) {
    const uint32_t sel = (it & 1) ? 0x3244u : 0x1044u;
    float v[6];
#pragma unroll
    for (int i = 0; i < 6; i++) { v[i] = __uint_as_float(__byte_perm(k.cur[i], 0, sel)); if (it == 1) k.cur[i] = k.nxt[i]; }
    const float rho2 = v[0] * dl, phi = v[1] * dt;
    const cf bb = {v[2] * inv_sc, v[3] * -inv_sc}, cc = {v[4], -v[5]};
    cf X[8];
    X[0] = cmul(cc, bb);
    const cf z1 = zpow(rho2, -phi, 1.f), z8 = zpow(rho2, phi, 8.f), z64 = zpow(rho2, phi, 64.f);
    const cf y1 = zpow(rho2, -phi, 256.f), y4 = zpow(rho2, -phi, 1024.f);
    const cf z2 = cmul(z1, z1);
    X[1] = cmul(X[0], z1);
#pragma unroll
    for (int j = 2; j < 8; j++) X[j] = cmul(X[j - 2], z2);
    const cf a0 = cmul(X[0], y1), a1 = cmul(X[2], y1), a2 = cmul(X[4], y1), a3 = cmul(X[6], y1);
    const cf a4 = cmul(a0, y1), a5 = cmul(a2, y1);
    const cf a6 = cmul(a4, y1), a7 = cmul(a5, y1);
    const cf v0 = cmul(X[0], y4), v1 = cmul(a0, y4), v2 = cmul(a4, y4), v3 = cmul(a6, y4), v4 = cmul(v0, y4);
    const cf f2 = cmul(z8, z8), f3 = cmul(f2, z8), f4 = cmul(f2, f2), f5 = cmul(f3, f2), f6 = cmul(f4, f2), f7 = cmul(f4, f3);
    const cf z128 = cmul(z64, z64);
    const uint32_t fr[4] = {pack_h2(1.f, z8.x), pack_h2(f2.x, f3.x), pack_h2(f4.x, f5.x), pack_h2(f6.x, f7.x)};
    const uint32_t fi[4] = {pack_h2(0.f, z8.y), pack_h2(f2.y, f3.y), pack_h2(f4.y, f5.y), pack_h2(f6.y, f7.y)};
    const uint32_t h64 = pack_h2(z64.x, z64.y);
    uint32_t gr[4], gi[4];
#pragma unroll
    for (int j = 0; j < 4; j++) hprod2(fr[j], fi[j], h64, gr[j], gi[j]);
    __syncwarp();
    sts128(st0, pack_h2(X[0].x, X[1].x), pack_h2(X[2].x, X[3].x), pack_h2(X[4].x, X[5].x), pack_h2(X[6].x, X[7].x));
    sts128(st1, pack_h2(X[0].y, X[1].y), pack_h2(X[2].y, X[3].y), pack_h2(X[4].y, X[5].y), pack_h2(X[6].y, X[7].y));
    sts128(st0 + 32, pack_h2(a0.x, a1.x), pack_h2(a2.x, a3.x), pack_h2(a4.x, a5.x), pack_h2(a6.x, a7.x));
    sts128(st1 + 32, pack_h2(a0.y, a1.y), pack_h2(a2.y, a3.y), pack_h2(a4.y, a5.y), pack_h2(a6.y, a7.y));
    asm volatile("st.shared.v2.b32 [%0], {%1,%2};" ::"r"(st0 + 64), "r"(pack_h2(v0.x, v1.x)), "r"(pack_h2(v2.x, v3.x)) : "memory");
    asm volatile("st.shared.v2.b32 [%0], {%1,%2};" ::"r"(st1 + 64), "r"(pack_h2(v0.y, v1.y)), "r"(pack_h2(v2.y, v3.y)) : "memory");
    asm volatile("st.shared.v2.b32 [%0], {%1,%1};" ::"r"(st0 + 72), "r"(pack_h2(v4.x, z128.x)) : "memory");
    asm volatile("st.shared.v2.b32 [%0], {%1,%1};" ::"r"(st1 + 72), "r"(pack_h2(v4.y, z128.y)) : "memory");
    sts128(st0 + 96, fr[0], fr[1], fr[2], fr[3]);
    sts128(st1 + 96, fi[0], fi[1], fi[2], fi[3]);
    sts128(st0 + 128, gr[0], gr[1], gr[2], gr[3]);
    sts128(st1 + 128, gi[0], gi[1], gi[2], gi[3]);
    __syncwarp();
    uint32_t B[4][6], A[4][4];
#pragma unroll
    for (int ks = 0; ks < 4; ks++) {
      ldsm2t(ldB + ks * 8 * KREC + 64, B[ks][4], B[ks][5]);
      ldsm4t(ldA + ks * 8 * KREC, A[ks][0], A[ks][1], A[ks][2], A[ks][3]);
      ldsm4t(ldB + ks * 8 * KREC, B[ks][0], B[ks][1], B[ks][2], B[ks][3]);
    }
#pragma unroll
    for (int ks = 0; ks < 4; ks++) {
      const uint32_t rl = __shfl_sync(0xffffffffu, B[ks][4], csrc), rh = __shfl_sync(0xffffffffu, B[ks][5], csrc);
      const uint32_t rlr = rot90(rl), rhr = rot90(rh);
      mma_f16(acc + 0, A[ks][0], A[ks][1], A[ks][2], A[ks][3], B[ks][0], B[ks][1]);
      mma_f16(acc + 4, A[ks][0], A[ks][1], A[ks][2], A[ks][3], B[ks][2], B[ks][3]);
      mma_f16(acc + 8, A[ks][0], A[ks][1], A[ks][2], A[ks][3], B[ks][4], B[ks][5]);
      const uint32_t c0 = hprod(A[ks][0], rl, rlr), c1 = hprod(A[ks][1], rl, rlr);
      const uint32_t c2 = hprod(A[ks][2], rh, rhr), c3 = hprod(A[ks][3], rh, rhr);
      mma_f16(acc + 12, c0, c1, c2, c3, B[ks][0], B[ks][1]);
      mma_f16(acc + 16, c0, c1, c2, c3, B[ks][2], B[ks][3]);
      mma_f16(acc + 20, c0, c1, c2, c3, B[ks][4], B[ks][5]);
    }
  }
  __syncwarp();
#pragma unroll
  for (int q = 0; q < 4; q++)
#pragma unroll
    for (int nt = 0; nt < 3; nt++) {
      const float* a = acc + 12 * (q >> 1) + 4 * nt + 2 * (q & 1);
      sts64f(stg + (q * 3 + nt) * 256 + lane * 8, a[0], a[1]);
    }
}

__device__ __forceinline__ void tput(uint32_t tbl, int X, uint32_t h) {
  sts16(tbl + 2 * (1296 - X), (uint16_t)h);
  sts16(tbl + TBL_C1 + 2 * (1297 - X), (uint16_t)h);
}
__device__ __forceinline__ void ktab_build(uint32_t src, bool four, int q, uint32_t tbl, int lane) {
  const int tq = lane & 3, r = 8 * q + (lane >> 2);
  float v[6];
  src += q * 768 + lane * 8;
#pragma unroll
  for (int nt = 0; nt < 3; nt++) {
    const float2 a = lds64f(src + nt * 256), c = lds64f(src + nt * 256 + KSTG);
    v[2 * nt] = a.x + c.x; v[2 * nt + 1] = a.y + c.y;
  }
  if (four) {
#pragma unroll
    for (int nt = 0; nt < 3; nt++) {
      const float2 a = lds64f(src + nt * 256 + 2 * KSTG), c = lds64f(src + nt * 256 + 3 * KSTG);
      v[2 * nt] += a.x + c.x; v[2 * nt + 1] += a.y + c.y;
    }
  }
  const bool first = (r == 0);
  if (first && tq == 0) { v[0] += lds32f(tbl + TBL_SC + 12); sts32f(tbl + TBL_SC, v[4]); }
  const uint32_t h0 = pack_h2(v[0], v[1]), h1 = pack_h2(v[2], v[3]), h2 = pack_h2(v[4], v[5]);
  tput(tbl, 64 + 8 * r + 2 * tq, h0);
  tput(tbl, 65 + 8 * r + 2 * tq, h0 >> 16);
  const bool lo = tq < 2;
  const int Xd = 320 + 8 * r + 4 * tq, k2 = 32 * (tq - 2) + r;
  tput(tbl, lo ? Xd + 2 : 720 + k2, h1 >> 16);
  const bool sp = first && tq == 2;
  const int Xa = lo ? Xd : (sp ? 576 : 911 + k2);
  tput(tbl, Xa, h1);
  if (lo || sp) {
    tput(tbl, Xa + 1, h1);
    if (Xa != 320) tput(tbl, Xa - 1, h1);
  }
  if (sp) { tput(tbl, 578, h1); tput(tbl, 1295, h2); }
  if (lo) {
    const int X3 = ((r & 1) ? 1104 : 1231) + 32 * tq + (r >> 1);
    tput(tbl, X3 == 1231 ? 975 : X3, h2);
    tput(tbl, X3 + 16, h2 >> 16);
  }
}

__device__ __forceinline__ void sig_windows(uint32_t sig, int t) {
  uint32_t U[20];
#pragma unroll
  for (int c = 0; c < 5; c++) {
    const int kap = 2 * t - 3 + c + 72;
    const uint4 v = lds128(sig + SIG_U + (kap & 7) * U_LBO + (kap >> 3) * 16);
    U[4 * c] = v.x; U[4 * c + 1] = v.y; U[4 * c + 2] = v.z; U[4 * c + 3] = v.w;
  }
  uint32_t O[19], A2[17], A4[17], V2[8], V5[8];
#pragma unroll
  for (int i = 3; i < 19; i++) O[i] = __byte_perm(U[i - 1], U[i], 0x5432);
#pragma unroll
  for (int i = 3; i < 17; i++) A2[i] = hadd2u(U[i], O[i]);
#pragma unroll
  for (int i = 4; i < 17; i++) A4[i] = hadd2u(A2[i], A2[i - 1]);
#pragma unroll
  for (int k = 0; k < 8; k++) { V2[k] = hadd2u(O[11 + k], U[10 + k]); V5[k] = hadd2u(A4[9 + k], U[7 + k]); }
#pragma unroll
  for (int h = 0; h < 2; h++) {
    sts128(sig + SIG_V3 + t * 32 + h * 16, hadd2u(V2[4 * h], O[10 + 4 * h]), hadd2u(V2[4 * h + 1], O[11 + 4 * h]),
           hadd2u(V2[4 * h + 2], O[12 + 4 * h]), hadd2u(V2[4 * h + 3], O[13 + 4 * h]));
    sts128(sig + SIG_V5 + t * 32 + h * 16, V5[4 * h], V5[4 * h + 1], V5[4 * h + 2], V5[4 * h + 3]);
  }
  if (t < 64) {
    uint32_t V7[8], V9[8];
#pragma unroll
    for (int k = 0; k < 8; k++) {
      V7[k] = hadd2u(V5[k], hadd2u(O[10 + k], O[7 + k]));
      V9[k] = hadd2u(hadd2u(A4[6 + k], A4[4 + k]), U[2 + k]);
    }
#pragma unroll
    for (int h = 0; h < 2; h++) {
      sts128(sig + SIG_V7 + h * 1024 + t * 16, V7[4 * h], V7[4 * h + 1], V7[4 * h + 2], V7[4 * h + 3]);
      sts128(sig + SIG_V9 + h * 1024 + t * 16, V9[4 * h], V9[4 * h + 1], V9[4 * h + 2], V9[4 * h + 3]);
      sts128(sig + SIG_V2 + h * 1024 + t * 16, V2[4 * h], V2[4 * h + 1], V2[4 * h + 2], V2[4 * h + 3]);
    }
  }
}

__device__ __forceinline__ void conv_channel(uint32_t tbl, uint32_t sig, uint32_t y2b, uint32_t y3b, float k1024,
                                             int w, int lane, int barid, float* res, int ts) {
  TSTAMP(ts);
  const int g = lane >> 2, tq = lane & 3;
  const uint32_t tb = tbl + ((g & 1) ? TBL_C1 + 2 : 0) + 2 * (1296 - (g - 2 * tq)) - 32 * w + 112;
  float a2[12], a3[8];
#pragma unroll
  for (int i = 0; i < 16; i++) res[i] = 0.f;
#pragma unroll
  for (int i = 0; i < 12; i++) a2[i] = 0.f;
#pragma unroll
  for (int q = 0; q < 4; q++) {
    const float2 f = h2f(lds32(sig + SIG_V2 + (q >> 1) * 1024 + (16 * w + 8 * (q & 1) + g) * 16 + tq * 4));
    a3[2 * q] = k1024 * f.x;
    a3[2 * q + 1] = k1024 * f.y;
  }
  const uint64_t dU = mkdesc(sig + SIG_U, U_LBO, 128, 0);
  const uint64_t dV = mkdesc(sig, 128, 1024, 0);
  fence_regs<16>(res); fence_regs<12>(a2); fence_regs<8>(a3);
  constexpr int LB = 2 * U_LBO / 16;
  uint32_t Rd[75], R2[2][17], R3[2][9];
  auto load_group = [&](int gi) {
    const int it = gi >> 1, hb = gi & 1;
    if (gi == 0) Rd[0] = lds32(tb - 128);
#pragma unroll
    for (int i = 1; i < (gi == 17 ? 7 : 5); i++) Rd[4 * gi + i] = lds32(tb - 128 - 16 * (4 * gi + i));
    if (gi < 16) {
      const int sg = it >> 2, n2 = gi & 7;
      if (n2 == 0) R2[sg][0] = lds32(tb - 1440 - 384 * sg);
      R2[sg][2 * n2 + 1] = lds32(tb - 1440 - 384 * sg - 16 * (2 * n2 + 1));
      R2[sg][2 * n2 + 2] = lds32(tb - 1440 - 384 * sg - 16 * (2 * n2 + 2));
      if (!hb) {
        const int n3 = it & 3;
        if (n3 == 0) R3[sg][0] = lds32(tb - 2208 - 256 * sg);
        R3[sg][2 * n3 + 1] = lds32(tb - 2208 - 256 * sg - 16 * (2 * n3 + 1));
        R3[sg][2 * n3 + 2] = lds32(tb - 2208 - 256 * sg - 16 * (2 * n3 + 2));
      }
    }
  };
  auto dense = [&](int n) {
    wg_rs_f16_n32k(res, Rd[2 * n + 1], Rd[2 * n + 2], Rd[2 * n], Rd[2 * n + 1], dU + ((3 - (n & 3)) * LB + 9 - (n >> 2)), 1);
  };
  load_group(0);
  load_group(1);
#pragma unroll
  for (int gi = 0; gi < 18; gi++) {
    const int it = gi >> 1, sg = it >> 2, n2 = gi & 7, n3 = it & 3;
    wg_fence();
    dense(2 * gi);
    if (gi < 16)
      wg_rs_f16_n24t(a2, R2[sg][2 * n2 + 1], R2[sg][2 * n2 + 2], R2[sg][2 * n2], R2[sg][2 * n2 + 1],
                     dV + ((SIG_V3 + 768) / 16 + 256 * sg - 16 * (n2 & 3) - 64 * (n2 >> 2)), 1);
    dense(2 * gi + 1);
    if (gi < 16 && !(gi & 1))
      wg_rs_f16_n16t(a3, R3[sg][2 * n3 + 1], R3[sg][2 * n3 + 2], R3[sg][2 * n3], R3[sg][2 * n3 + 1],
                     dV + ((SIG_V7 + 768) / 16 + 128 * sg - 16 * n3), 1);
    if (gi == 17) dense(36);
    wg_commit();
    if (gi < 16) { wg_wait<1>(); load_group(gi + 2); }
  }
  TSTAMP(ts + 1);
  wg_wait<2>();
  fence_regs<12>(a2); fence_regs<8>(a3);
  bar_sync(barid, 128);
  {
    const uint32_t o2 = y2b + (136 * w + 8 * g + 2 * tq) * 4, o3 = y3b + (272 * w + 16 * g + 2 * tq) * 4;
#pragma unroll
    for (int q = 0; q < 6; q++) sts64f(o2 + (544 * (q >> 1) + 64 * (q & 1)) * 4, a2[2 * q], a2[2 * q + 1]);
#pragma unroll
    for (int q = 0; q < 4; q++) sts64f(o3 + (8 * (q >> 1) + 136 * (q & 1)) * 4, a3[2 * q], a3[2 * q + 1]);
  }
  bar_sync(barid, 128);
  const uint32_t go = (136 * tq + 16 * w + g) * 4;
  float ex[12];
#pragma unroll
  for (int i = 0; i < 12; i++) {
    const int o = 544 * (i >> 2) + 64 * (i & 1) + 8 * ((i >> 1) & 1);
    ex[i] = lds32f(y2b + go + o * 4);
    if (i >= 4) ex[i] += lds32f(y3b + go + (o - 544) * 4);
  }
  wg_wait<0>();
  fence_regs<16>(res);
#pragma unroll
  for (int i = 0; i < 12; i++) res[4 + i] += ex[i];
  TSTAMP(ts + 2);
}

__device__ __forceinline__ void red16x2(float& a, float& c) {
#pragma unroll
  for (int o = 1; o < 16; o <<= 1) { a += __shfl_xor_sync(0xffffffffu, a, o); c += __shfl_xor_sync(0xffffffffu, c, o); }
}
__device__ __forceinline__ void ln_rows(uint32_t* u, int row, uint32_t stg_row, int lane) {
  const int j = lane & 15;
  const float piv = __shfl_sync(0xffffffffu, bf_lo(u[0]), lane & 16);
  float s0 = 0.f, s1 = 0.f, q0 = 0.f, q1 = 0.f;
#pragma unroll
  for (int i = 0; i < 14; i++) {
    const float a = bf_lo(u[i]) - piv, c = bf_hi(u[i]) - piv;
    s0 += a; s1 += c; q0 = fmaf(a, a, q0); q1 = fmaf(c, c, q1);
  }
  float s = s0 + s1, q = q0 + q1;
  red16x2(s, q);
  s *= (1.f / D_); q *= (1.f / D_);
  const __nv_bfloat16 m1b = __float2bfloat16_rn(s + piv);
  const __nv_bfloat162 m1v = __halves2bfloat162(m1b, m1b);
  const float den = rbf(sqrtf_(rbf(rbf(fmaxf(fmaf(-s, s, q), 0.f)) + 1e-5f)));
  const float rden = rcpf_(den);
  s0 = s1 = q0 = q1 = 0.f;
#pragma unroll
  for (int i = 0; i < 14; i++) {
    const __nv_bfloat162 cv = __hsub2(*reinterpret_cast<__nv_bfloat162*>(&u[i]), m1v);
    const uint32_t c = *reinterpret_cast<const uint32_t*>(&cv);
    const uint32_t n = pack_bf2(bf_lo(c) * rden, bf_hi(c) * rden);
    const float a = bf_lo(n), e = bf_hi(n);
    s0 += a; s1 += e; q0 = fmaf(a, a, q0); q1 = fmaf(e, e, q1);
    u[i] = pack_h2(a, e);
  }
#pragma unroll
  for (int i = 0; i < 7; i++)
    asm volatile("st.shared.v2.b32 [%0], {%1,%2};" ::"r"(stg_row + (j + 16 * i) * 8), "r"(u[2 * i]), "r"(u[2 * i + 1]) : "memory");
  s = s0 + s1; q = q0 + q1;
  red16x2(s, q);
  s *= (1.f / D_); q *= (1.f / D_);
  const float den2 = rbf(sqrtf_(rbf(rbf(fmaxf(fmaf(-s, s, q), 0.f)) + 1e-5f)));
  if (j == 0) {
    const float ir = den * den2, mu = fmaf(rbf(s), den, __bfloat162float(m1b));
    const float ih = rbf(ir), mh = rbf(mu);
    const uint32_t mm = pack_bf2(mh, mh);
    g_ax[row] = make_uint4(mm, pack_bf2(mu - mh, ih), mm, pack_bf2(mu - mh, ir - ih));
    g_r[row] = rcpf_(ir);
  }
}

__device__ __forceinline__ void poll_tag(const unsigned* p, uint32_t tag) {
#pragma unroll 1
  for (int it = 0; it < 4096; it++) {
    if (!((ld_relaxed1(p) ^ tag) & 1)) break;
    __nanosleep(32);
  }
}
template <int NV, int STRIDE>
__device__ __forceinline__ void recv_part(const uint4* src, uint32_t tag, float* pre) {
  uint4 v[NV];
#pragma unroll 1
  for (int it = 0; it < RETRY_MAX; it++) {
    uint32_t bad = 0;
#pragma unroll
    for (int q = 0; q < NV; q++) v[q] = ld_b128(src + q * STRIDE);
#pragma unroll
    for (int q = 0; q < NV; q++) bad |= v[q].x ^ tag;
    const unsigned m = __ballot_sync(0xffffffffu, bad & 1);
    if (!m) break;
    if ((threadIdx.x & 31) == __ffs(m) - 1) poll_tag((const unsigned*)(src + (NV - 1) * STRIDE), tag);
    __syncwarp();
  }
#pragma unroll
  for (int q = 0; q < NV; q++) {
    const uint32_t u[4] = {v[q].x, v[q].y, v[q].z, v[q].w};
#pragma unroll
    for (int k = 0; k < 4; k++) { pre[8 * q + 2 * k] += bf_lo(u[k]); pre[8 * q + 2 * k + 1] += bf_hi(u[k]); }
  }
}
__device__ __forceinline__ void send_part(uint4* dst, uint32_t tag, const float* a) {
#pragma unroll
  for (int q = 0; q < 4; q++)
    st_b128(dst + q * 256, tag, pack_bf2(a[8 * q], a[8 * q + 1]), pack_bf2(a[8 * q + 2], a[8 * q + 3]),
            pack_bf2(a[8 * q + 4], a[8 * q + 5]), pack_bf2(a[8 * q + 6], a[8 * q + 7]));
}
__device__ __forceinline__ bool last_release(uint32_t cnt) {
  unsigned old;
  asm volatile("atom.relaxed.cta.shared.inc.u32 %0, [%1], 7;" : "=r"(old) : "r"(cnt) : "memory");
  return old == 7;
}
__device__ __forceinline__ int mod7(int v) { return v >= 7 ? v - 7 : v; }

#define IDS const int tid = opaque(tid0), lane = tid & 31, t = tid & 127, wg = tid >> 7, w = (tid >> 5) & 3; \
            (void)lane; (void)t; (void)wg; (void)w;

__global__ void __launch_bounds__(384, 1)
fused_kernel(const __grid_constant__ CUtensorMap tm_x, const __grid_constant__ CUtensorMap tm_w1,
             const __grid_constant__ CUtensorMap tm_w2, const __grid_constant__ CUtensorMap tm_out, const Params p) {
  extern __shared__ __align__(1024) uint8_t smem_raw[];
  const uint32_t sb = smem_u32(smem_raw);
  const uint32_t ms = sb + OFF_M;
  const uint32_t bar0 = ms + M_BAR;
  const int tid0 = threadIdx.x;
  const int b = blockIdx.x;
  const bool is_ssm = b >= NMLP;
  const int G = b / NRK, rk = b - G * NRK;
  const int kc0 = (G + rk) % 7;
  TSTAMP(0);
  {
    IDS
    if (wg == 2 && w == 0) {
      if (lane < 16) { mbar_init(bar0 + 8 * lane, 1); asm volatile("st.shared.b32 [%0], 0;" ::"r"(ms + M_REL + 4 * lane) : "memory"); }
      fence_async();
      if (lane < 3 && !is_ssm) {
        const int kc = mod7(kc0 + lane);
        mbar_expect(bar0 + 8 * lane, 49152);
        tma_2d(sb + OFF_X + lane * 16384, &tm_x, 64 * kc, 128 * G, bar0 + 8 * lane);
        tma_3d(sb + OFF_W + lane * 32768, &tm_w1, 0, 64 * kc, 4 * rk, bar0 + 8 * lane);
      }
    }
    TSTAMP(28);
    unsigned ep = 0;
    if (tid == 256 + 32) ep = *(volatile unsigned*)&g_epoch;
    uint4 ld[7];
    const int rl = 2 * (tid >> 5) + (lane >> 4);
    if (wg < 2) {
      const uint2* xr = (const uint2*)(p.x + (size_t)(16 * (b & 127) + rl) * D_) + (lane & 15);
#pragma unroll
      for (int i = 0; i < 7; i++) { const uint2 v = __ldg(xr + 16 * i); ld[i].x = v.x; ld[i].y = v.y; }
    } else {
      const uint4* wr = (const uint4*)(p.w1 + (size_t)(112 * (b & 3) + (t >> 3)) * F_ + 64 * (is_ssm ? 0 : b >> 2)) + (t & 7);
#pragma unroll
      for (int i = 0; i < 7; i++) ld[i] = __ldg(wr + (size_t)i * 16 * (F_ / 8));
    }
    KgIn kin;
    {
      const int d = is_ssm ? 2 * (112 + 3 * (b - NMLP) + wg) + (w >> 1) : (wg < 2 ? 2 * b + wg : 336 + b);
      kgen_load(p, d, is_ssm ? 2 * (w & 1) : w, is_ssm ? 2 : 1, lane, kin);
    }
    const uint32_t tbl = is_ssm ? sb + (4 * wg + (w >> 1)) * TBL : sb + OFF_T + wg * TBL;
#pragma unroll 1
    for (int i = is_ssm ? t & 63 : t; i < TBL_SC / 16; i += is_ssm ? 64 : 128) sts128(tbl + i * 16, 0u, 0u, 0u, 0u);
    const uint32_t lns = is_ssm ? sb + S_WORK + 2 * S_WGB : sb + OFF_B;
    TSTAMP(31);
    if (wg < 2) {
      uint32_t u[14];
#pragma unroll
      for (int i = 0; i < 7; i++) { u[2 * i] = ld[i].x; u[2 * i + 1] = ld[i].y; }
      ln_rows(u, 16 * (b & 127) + rl, lns + ((rl & 1) | ((rl >> 2) << 1) | ((rl & 2) << 2)) * 912, lane);
      bar_arrive(7, 384);
    } else {
      const float b1v = __bfloat162float(p.b1[64 * (is_ssm ? 0 : b >> 2) + (t & 63)]);
      float cs[8];
#pragma unroll
      for (int k = 0; k < 8; k++) cs[k] = 0.f;
#pragma unroll
      for (int i = 0; i < 7; i++) {
        const uint32_t uu[4] = {ld[i].x, ld[i].y, ld[i].z, ld[i].w};
#pragma unroll
        for (int k = 0; k < 4; k++) { cs[2 * k] += bf_lo(uu[k]); cs[2 * k + 1] += bf_hi(uu[k]); }
      }
#pragma unroll
      for (int st = 0; st < 2; st++) {
        const int n = 4 >> st;
        const bool up = (lane >> (4 - st)) & 1;
#pragma unroll
        for (int k = 0; k < n; k++) {
          const float give = up ? cs[k] : cs[k + n], keep = up ? cs[k + n] : cs[k];
          cs[k] = keep + __shfl_xor_sync(0xffffffffu, give, 16 >> st);
        }
      }
      sts64f(ms + M_CSR + (w * 64 + (lane & 7) * 8 + (lane >> 3) * 2) * 4, cs[0], cs[1]);
      if (t == 32) asm volatile("st.shared.b32 [%0], %1;" ::"r"(ms + M_EP), "r"(ep + 1) : "memory");
      bar_sync(7, 384);
      const uint32_t la = lns + (lane & 15) * 912 + (lane >> 4) * 16 + w * 224;
      uint2* dst = (uint2*)(g_xnT + (size_t)(56 * w + (lane >> 3)) * 512 + 4 * b) + (lane & 7);
      uint32_t r[28];
#pragma unroll
      for (int k = 0; k < 7; k++) ldsm4t(la + k * 32, r[4 * k], r[4 * k + 1], r[4 * k + 2], r[4 * k + 3]);
      const uint32_t tag = lds32(ms + M_EP) & 1;
      if (b < 128) {
#pragma unroll
        for (int k = 0; k < 14; k++) st_relaxed2(dst + k * 4096, (r[2 * k] & ~1u) | tag, (r[2 * k + 1] & ~1u) | tag);
      }
      if (t < 64 && !is_ssm) {
        const uint32_t a = ms + M_CSR + t * 4;
        const float c = -((lds32f(a) + lds32f(a + 256)) + (lds32f(a + 512) + lds32f(a + 768)));
        const float ch = rbf(c);
        uint2* dx = (uint2*)(g_bx + (b >> 4) * 512 + ((b >> 1) & 1) * 256 + ((b >> 2) & 3) * 64 + t) + (b & 1);
        *dx = make_uint2(pack_bf2(ch, c - ch), pack_bf2(ch, (b & 2) ? 0.f : b1v));
      }
      bar_sync(6, 128);
    }
    TSTAMP(29);
    const uint32_t stg = is_ssm ? sb + S_WORK + wg * S_WGB + w * KSTG : sb + (wg < 2 ? OFF_A + 4 * wg * KSTG : OFF_B) + w * KSTG;
    kgen_warp(kin, is_ssm ? 2 : 1, stg, tbl, lane);
  }
  TSTAMP(1);
  __syncthreads();

  if (is_ssm || __shfl_sync(0xffffffffu, tid0 >> 7, 0) == 2) {
    asm volatile("setmaxnreg.dec.sync.aligned.u32 136;");
    {
      IDS
      if (t == 0 && !is_ssm)
        asm volatile("cp.async.bulk.prefetch.L2.global [%0], %1;" ::"l"(p.w2 + (size_t)(256 * rk + 16 * G) * D_), "r"(16 * D_ * 2) : "memory");
#pragma unroll 1
      for (int c = is_ssm ? 1 : 2; c >= 0; c--) {
        const uint32_t src = is_ssm ? sb + S_WORK + wg * S_WGB + 2 * c * KSTG : sb + (c < 2 ? OFF_A + 4 * c * KSTG : OFF_B);
        ktab_build(src, !is_ssm, w, (is_ssm ? sb + 4 * wg * TBL : sb + OFF_T) + c * TBL, lane);
        if (c == 2) {
          fence_async();
          bar_sync(6, 128);
          if (t == 96) { bulk_s2g(g_tbl + b * (TBL / 16), sb + OFF_T + 2 * TBL, TBL); bulk_commit(); }
        }
      }
      if (tid == 256 + 96) { bulk_wait0(); red_release(&g_cntA); }
      bar_sync(4 + wg, 128);
    }
    TSTAMP(3);
#pragma unroll 1
    for (int pi = 0; pi < 2; pi++) {
      {
        IDS
        if (pi == 1 && (!is_ssm || (b >= NMLP + 12 && wg == 2))) break;
        const unsigned ep1 = lds32(ms + M_EP);
        const int pair = !is_ssm ? b : (pi == 0 ? 112 + 3 * (b - NMLP) : (b < NMLP + 12 ? 172 + 3 * (b - NMLP) : 184 + 2 * (b - NMLP))) + wg;
        const uint32_t work = is_ssm ? sb + S_WORK + wg * S_WGB : sb + OFF_A;
        const uint32_t z = work + SIG_V3 - 1024 + (t >> 6) * 4096 + (t & 63) * 16;
        sts128(z, 0u, 0u, 0u, 0u); sts128(z + SIG, 0u, 0u, 0u, 0u);
        if (t < 72) {
          const uint32_t zu = work + SIG_U + (t & 7) * U_LBO + (t >> 3) * 16;
          sts128(zu, 0u, 0u, 0u, 0u); sts128(zu + SIG, 0u, 0u, 0u, 0u);
        }
        const uint4* src = g_xnT + (size_t)pair * 512 + t;
        uint4 v[4];
#pragma unroll 1
        for (int it = 0; it < RETRY_MAX; it++) {
#pragma unroll
          for (int q = 0; q < 4; q++) v[q] = ld_relaxed4(src + q * 128);
          uint32_t bad = 0;
#pragma unroll
          for (int q = 0; q < 4; q++) bad |= (((v[q].x ^ ep1) | (v[q].y ^ ep1) | (v[q].z ^ ep1) | (v[q].w ^ ep1)) & 1) << q;
          const unsigned m = __ballot_sync(0xffffffffu, bad);
          if (!m) break;
          if (lane == __ffs(m) - 1) poll_tag((const unsigned*)(src + (__ffs(bad) - 1) * 128) + 3, ep1);
          __syncwarp();
        }
        TSTAMP(5);
        const uint32_t a = work + ((t >> 1) & 1) * SIG + SIG_U + (2 * ((t >> 2) & 3) + (t & 1)) * U_LBO + ((t >> 4) + 9) * 16;
#pragma unroll
        for (int q = 0; q < 4; q++) sts128(a + q * 128, v[q].x & ~1u, v[q].y & ~1u, v[q].z & ~1u, v[q].w & ~1u);
        bar_sync(4 + wg, 128);
#pragma unroll 1
        for (int k = w; k < 6; k += 4) sig_windows(work + (k & 1) * SIG, (k >> 1) * 32 + lane);
        fence_async();
        if (t == 96 && pi == 0) {
          wait_count(&g_cntA, ep1 * NCTA);
          if (b == 0) *(volatile unsigned*)&g_epoch = ep1;
          asm volatile("fence.proxy.async;" ::: "memory");
          if (!is_ssm) {
            mbar_expect(bar0 + 8 * 15, 2048 + 8192 + 512);
            bulk_g2s(sb + OFF_B + B_AX, g_ax + 128 * G, 2048, bar0 + 8 * 15);
            bulk_g2s(sb + OFF_B + B_BX, g_bx + 512 * rk, 8192, bar0 + 8 * 15);
            bulk_g2s(sb + OFF_B + B_R, g_r + 128 * G, 512, bar0 + 8 * 15);
          } else if (b < NMLP + 12 || wg < 2) {
            const int j = (b < NMLP + 12 ? 3 * (b - NMLP) : 2 * (b - NMLP) + 12) + wg;
            mbar_expect(bar0 + 8 * wg, 2 * TBL);
            bulk_g2s(sb + (4 * wg + 2) * TBL, g_tbl + (2 * j + 8) * (TBL / 16), 2 * TBL, bar0 + 8 * wg);
          }
        }
        if (pi == 1) mbar_wait(bar0 + 8 * wg, 0);
        TSTAMP(6);
        bar_sync(is_ssm ? 4 + wg : 3, is_ssm ? 128 : 384);
        TSTAMP(7);
      }
      uint32_t keep[8];
      float res[16];
#pragma unroll 1
      for (int c = 0; c < 2; c++) {
        IDS
        const int wgu = __shfl_sync(0xffffffffu, wg, 0);
        const uint32_t work = is_ssm ? sb + S_WORK + wgu * S_WGB : sb + OFF_A;
        const uint32_t tbl = (is_ssm ? sb + (4 * wgu + 2 * pi) * TBL : sb + OFF_T) + c * TBL;
        conv_channel(tbl, work + c * SIG, is_ssm ? work + 2 * SIG + Y3B : sb + OFF_B, work + 2 * SIG, lds32f(tbl + TBL_SC), w, lane, 4 + wgu, res, 16 + 3 * (2 * pi + c));
        const float os = lds32f(tbl + TBL_SC + 8);
        if (c == 0) {
#pragma unroll
          for (int i = 0; i < 8; i++) keep[i] = pack_bf2(res[2 * i] * os, res[2 * i + 1] * os);
        } else {
          const int pair = !is_ssm ? b : (pi == 0 ? 112 + 3 * (b - NMLP) : (b < NMLP + 12 ? 172 + 3 * (b - NMLP) : 184 + 2 * (b - NMLP))) + wg;
          uint4* dst = g_s2 + ((size_t)(lane & 3) * 224 + pair) * 32 + w * 8 + (lane >> 2);
          const uint32_t tag = lds32(ms + M_EP) & 1;
#pragma unroll
          for (int nt = 0; nt < 4; nt++) {
            const uint32_t n0 = pack_bf2(res[4 * nt] * os, res[4 * nt + 1] * os), n1 = pack_bf2(res[4 * nt + 2] * os, res[4 * nt + 3] * os);
            st_b128(dst + nt * 4 * 224 * 32, tag, __byte_perm(keep[2 * nt], n0, 0x5410), __byte_perm(keep[2 * nt + 1], n1, 0x5410),
                    __byte_perm(keep[2 * nt], n0, 0x7632), __byte_perm(keep[2 * nt + 1], n1, 0x7632));
          }
        }
      }
      TSTAMP(8 + pi);
    }
    if (!is_ssm) {
      IDS
      const uint32_t tag = lds32(ms + M_EP) & 1;
      float pre[64];
#pragma unroll
      for (int i = 0; i < 64; i++) pre[i] = 0.f;
#pragma unroll 1
      for (int s = 0; s < 4; s++) recv_part<8, 128>(g_part + ((size_t)b * 6 + s) * 1024 + t, tag, pre);
      bar_sync(6, 128);
#pragma unroll
      for (int i = 0; i < 16; i++)
        sts128(sb + OFF_A + ((2 * (i >> 2) + (i & 1)) * 256 + ((i >> 1) & 1) * 128 + t) * 16, __float_as_uint(pre[4 * i]),
               __float_as_uint(pre[4 * i + 1]), __float_as_uint(pre[4 * i + 2]), __float_as_uint(pre[4 * i + 3]));
      bar_arrive(2, 384);
      TSTAMP(12);
    }
  } else {
    bar_arrive(1, 384);
    asm volatile("setmaxnreg.inc.sync.aligned.u32 192;");
    bar_sync(7, 384);
    uint32_t H[64];
    {
      float acc[128];
      float p0, q0, p1, q1;
      {
        IDS
        const int wgu = __shfl_sync(0xffffffffu, wg, 0);
        int sl = 0;
#pragma unroll 1
        for (int s = 0; s < 7; s++) {
          mbar_wait(bar0 + 8 * s, 0);
          const uint64_t da = mkdesc(sb + OFF_X + sl * 16384 + wgu * 8192, 16, 1024, 1);
          const uint64_t db = mkdesc(sb + OFF_W + sl * 32768, 8192, 1024, 1);
          wg_fence();
#pragma unroll
          for (int k = 0; k < 4; k++) wg_ss_bf16_n256(acc, da + 2 * k, db + 128 * k, (s | k) != 0);
          wg_commit();
          wg_wait<1>();
          const int pl = sl == 0 ? 2 : sl - 1;
          sl = sl == 2 ? 0 : sl + 1;
          if (s > 0 && lane == 0 && last_release(ms + M_REL + 4 * s)) {
            const uint32_t bx = bar0 + 8 * (s < 5 ? s + 2 : 14);
            mbar_expect(bar0 + 8 * (s + 2), s < 5 ? 49152 : 32768);
            if (s < 5) tma_3d(sb + OFF_W + pl * 32768, &tm_w1, 0, 64 * mod7(kc0 + s + 2), 4 * rk, bar0 + 8 * (s + 2));
            else tma_2d(sb + OFF_W + pl * 32768, &tm_w2, 64 * mod7(rk + s - 4), 256 * rk, bar0 + 8 * (s + 2));
            if (s == 6) mbar_expect(bx, 16384);
            if (s != 5) tma_2d(sb + OFF_X + pl * 16384, &tm_x, 64 * (s < 5 ? mod7(kc0 + s + 2) : rk), 128 * G, bx);
          }
        }
        TSTAMP(9);
        mbar_wait(bar0 + 8 * 15, 0);
        wg_fence();
        wg_ss_bf16_n256k(acc, mkdesc(sb + OFF_B + B_AX + wgu * 1024, 0, 128, 0), mkdesc(sb + OFF_B + B_BX, 4096, 128, 0), 1);
        wg_commit();
        wg_wait<1>();
        if (lane == 0 && last_release(ms + M_REL + 4 * 7)) {
#pragma unroll 1
          for (int c = 2; c < 4; c++) {
            mbar_expect(bar0 + 8 * (7 + c), 32768);
            tma_2d(sb + (c - 2) * OFF_X, &tm_w2, 64 * mod7(rk + 1 + c), 256 * rk, bar0 + 8 * (7 + c));
          }
        }
        bar_arrive(3, 384);
        const float r0 = lds32f(sb + OFF_B + B_R + (16 * (tid >> 5) + (lane >> 2)) * 4);
        const float r1 = lds32f(sb + OFF_B + B_R + (16 * (tid >> 5) + (lane >> 2) + 8) * 4);
        p0 = 0.7978845608028654f * r0; q0 = 0.0356774081363001f * r0 * r0 * r0;
        p1 = 0.7978845608028654f * r1; q1 = 0.0356774081363001f * r1 * r1 * r1;
      }
      wg_wait<0>();
      fence_regs<128>(acc);
      TSTAMP(2);
      float hq[4];
#pragma unroll
      for (int i = 0; i < 64; i++) {
        const float pp = (i & 1) ? p1 : p0, qq = (i & 1) ? q1 : q0;
        const float a = acc[2 * i], c = acc[2 * i + 1];
        const float ta = tanhf_(a * fmaf(a * a, qq, pp)), tc = tanhf_(c * fmaf(c * c, qq, pp));
        if (i >= 2) H[i - 2] = pack_bf2v(hq[(i & 1) * 2], hq[(i & 1) * 2 + 1]);
        hq[(i & 1) * 2] = fmaf(a, ta, a); hq[(i & 1) * 2 + 1] = fmaf(c, tc, c);
      }
      H[62] = pack_bf2v(hq[0], hq[1]); H[63] = pack_bf2v(hq[2], hq[3]);
    }
    TSTAMP(3);
    float accA[32], accB[32];
    const uint32_t tag = lds32(ms + M_EP) & 1;
    auto issue2 = [&](int c, float* acc) {
      const uint32_t base = sb + ((0x0213021u >> (4 * c)) & 3) * 32768;
      mbar_wait(bar0 + 8 * (7 + c), 0);
      const uint64_t db = mkdesc(base, 8192, 1024, 1);
      wg_fence();
#pragma unroll
      for (int k = 0; k < 16; k++) wg_rs_bf16_n64(acc, H[4 * k], H[4 * k + 1], H[4 * k + 2], H[4 * k + 3], db + 128 * k, k != 0);
      wg_commit();
    };
    auto process = [&](int s, float* acc) {
      wg_wait<1>();
      fence_regs<32>(acc);
      const int tid = opaque(tid0);
      if (s < 3 && (tid & 31) == 0 && last_release(ms + M_REL + 4 * (8 + s))) {
        mbar_expect(bar0 + 8 * (11 + s), 32768);
        tma_2d(sb + ((0x021u >> (4 * s)) & 3) * 32768, &tm_w2, 64 * mod7(mod7(rk + 5 + s)), 256 * rk, bar0 + 8 * (11 + s));
      }
      send_part(g_part + ((size_t)(G * 7 + mod7(rk + 1 + s)) * 6 + s) * 1024 + tid, tag, acc);
      TSTAMP(10 + s);
    };
    issue2(0, accA);
#pragma unroll
    for (int s = 0; s < 6; s += 2) {
      issue2(s + 1, accB);
      process(s, accA);
      issue2(s + 2, accA);
      process(s + 1, accB);
    }
    TSTAMP(4);
    IDS
    const int g = lane >> 2, tq = lane & 3;
    uint32_t sw[16];
    {
      const uint4* sp = g_s2 + ((size_t)G * 224 + 32 * rk + tq) * 32 + w * 8 + g;
#pragma unroll 1
      for (int it = 0; it < RETRY_MAX; it++) {
        uint32_t bad = 0;
#pragma unroll
        for (int i = 0; i < 8; i++) {
          const uint4 v = ld_b128(sp + i * 4 * 32);
          bad |= ((v.x ^ tag) & 1) << i;
          sw[2 * i] = wg ? v.z : v.x; sw[2 * i + 1] = wg ? v.w : v.y;
        }
        const unsigned m = __ballot_sync(0xffffffffu, bad);
        if (!m) break;
        if (lane == __ffs(m) - 1) poll_tag((const unsigned*)(sp + (__ffs(bad) - 1) * 4 * 32), tag);
        __syncwarp();
      }
    }
    TSTAMP(5);
    uint32_t b2w[8];
#pragma unroll
    for (int i = 0; i < 8; i++) b2w[i] = __ldg((const uint32_t*)(p.b2 + 64 * rk) + 4 * i + tq);
    wg_wait<0>();
    fence_regs<32>(accA);
    TSTAMP(6);
    bar_sync(2, 384);
#pragma unroll
    for (int i = 0; i < 8; i++) {
      const uint4 v = lds128(sb + OFF_A + (i * 256 + tid) * 16);
      accA[4 * i] += __uint_as_float(v.x); accA[4 * i + 1] += __uint_as_float(v.y);
      accA[4 * i + 2] += __uint_as_float(v.z); accA[4 * i + 3] += __uint_as_float(v.w);
    }
    mbar_wait(bar0 + 8 * 14, 0);
    const uint32_t xa = sb + OFF_X + 2 * 16384 + (16 * (tid >> 5) + (lane & 15)) * 128;
    uint32_t xw[16];
#pragma unroll
    for (int q = 0; q < 4; q++) ldsm4(xa + (((2 * q + (lane >> 4)) ^ (lane & 7)) << 4), xw[4 * q], xw[4 * q + 1], xw[4 * q + 2], xw[4 * q + 3]);
    const float r0 = 0.5f * lds32f(sb + OFF_B + B_R + (16 * (tid >> 5) + g) * 4);
    const float r1 = 0.5f * lds32f(sb + OFF_B + B_R + (16 * (tid >> 5) + g + 8) * 4);
#pragma unroll 1
    for (int s = 4; s < 6; s++) recv_part<4, 256>(g_part + ((size_t)b * 6 + s) * 1024 + tid, tag, accA);
    TSTAMP(7);
#pragma unroll
    for (int k = 0; k < 16; k++) {
      const float rr = (k & 1) ? r1 : r0;
      const float o0 = fmaf(accA[2 * k], rr, bf_lo(b2w[k >> 1])), o1 = fmaf(accA[2 * k + 1], rr, bf_hi(b2w[k >> 1]));
      const float g0 = o0 * rcpf_(1.f + ex2f(o0 * -1.4426950408889634f)), g1 = o1 * rcpf_(1.f + ex2f(o1 * -1.4426950408889634f));
      xw[k] = pack_bf2(fmaf(bf_lo(sw[k]), g0, bf_lo(xw[k])), fmaf(bf_hi(sw[k]), g1, bf_hi(xw[k])));
    }
#pragma unroll
    for (int q = 0; q < 4; q++) stsm4(xa + (((2 * q + (lane >> 4)) ^ (lane & 7)) << 4), xw[4 * q], xw[4 * q + 1], xw[4 * q + 2], xw[4 * q + 3]);
    fence_async();
    __syncwarp();
    if (lane == 0) {
      tma_store_2d(&tm_out, sb + OFF_X + 2 * 16384 + (tid >> 5) * 2048, 64 * rk, 128 * G + 16 * (tid >> 5));
      bulk_commit();
      bulk_wait0_read();
    }
    TSTAMP(8);
  }
}

typedef CUresult (*EncodeFn)(CUtensorMap*, CUtensorMapDataType, cuuint32_t, void*, const cuuint64_t*, const cuuint64_t*,
                             const cuuint32_t*, const cuuint32_t*, CUtensorMapInterleave, CUtensorMapSwizzle,
                             CUtensorMapL2promotion, CUtensorMapFloatOOBfill);

void make_map(EncodeFn fn, CUtensorMap* m, const void* ptr, int rank, const cuuint64_t* dims, const cuuint64_t* strides, const cuuint32_t* box) {
  const cuuint32_t es[3] = {1, 1, 1};
  fn(m, CU_TENSOR_MAP_DATA_TYPE_BFLOAT16, rank, const_cast<void*>(ptr), dims, strides, box, es, CU_TENSOR_MAP_INTERLEAVE_NONE,
     CU_TENSOR_MAP_SWIZZLE_128B, CU_TENSOR_MAP_L2_PROMOTION_L2_128B, CU_TENSOR_MAP_FLOAT_OOB_FILL_NONE);
}

}

extern "C" void kernel_launch(void* const* d_in, const int* in_sizes, int n_in, void* d_out, int out_size) {
  (void)in_sizes; (void)n_in; (void)out_size;
  void* fnp = nullptr;
  cudaDriverEntryPointQueryResult qr;
  cudaGetDriverEntryPoint("cuTensorMapEncodeTiled", &fnp, cudaEnableDefault, &qr);
  EncodeFn fn = (EncodeFn)fnp;
  Params p;
  p.x = (const __nv_bfloat16*)d_in[0];
  p.a_re = (const __nv_bfloat16*)d_in[1]; p.a_im = (const __nv_bfloat16*)d_in[2];
  p.b_re = (const __nv_bfloat16*)d_in[3]; p.b_im = (const __nv_bfloat16*)d_in[4];
  p.c_re = (const __nv_bfloat16*)d_in[5]; p.c_im = (const __nv_bfloat16*)d_in[6];
  p.log_dt = (const __nv_bfloat16*)d_in[7]; p.dskip = (const __nv_bfloat16*)d_in[8];
  p.w1 = (const __nv_bfloat16*)d_in[10]; p.b1 = (const __nv_bfloat16*)d_in[11];
  p.w2 = (const __nv_bfloat16*)d_in[12]; p.b2 = (const __nv_bfloat16*)d_in[13];
  CUtensorMap mx, mw1, mw2, mo;
  {
    const cuuint64_t dims[2] = {448, 2048}, str[1] = {896};
    const cuuint32_t box[2] = {64, 128}, boxo[2] = {64, 16};
    make_map(fn, &mx, p.x, 2, dims, str, box);
    make_map(fn, &mo, d_out, 2, dims, str, boxo);
  }
  {
    const cuuint64_t dims[3] = {64, 448, 28}, str[2] = {3584, 128};
    const cuuint32_t box[3] = {64, 64, 4};
    make_map(fn, &mw1, p.w1, 3, dims, str, box);
  }
  {
    const cuuint64_t dims[2] = {448, 1792}, str[1] = {896};
    const cuuint32_t box[2] = {64, 256};
    make_map(fn, &mw2, p.w2, 2, dims, str, box);
  }
  cudaFuncSetAttribute(fused_kernel, cudaFuncAttributeMaxDynamicSharedMemorySize, SMEM_BYTES);
  fused_kernel<<<NCTA, 384, SMEM_BYTES>>>(mx, mw1, mw2, mo, p);
}
```

```cpp
#include <cuda_runtime.h>
#include <cuda_bf16.h>
#include <cuda_fp16.h>
#include <cuda.h>
#include <stdint.h>

namespace {

constexpr int D_ = 448, NST = 256, F_ = 1792;
constexpr int NRK = 7, NMLP = 112, NCTA = 132;
constexpr int SPIN_MAX = 1 << 20, RETRY_MAX = 512;

__device__ uint4 g_xnT[224 * 512];
__device__ uint4 g_ax[2048];
__device__ float g_r[2048];
__device__ uint4 g_bx[7 * 512];
__device__ uint4 g_part[16 * 7 * 6 * 1024];
__device__ uint4 g_s2[16 * 224 * 32];
__device__ uint4 g_tbl[112 * 329];
__device__ unsigned g_cntA, g_cntT;
__device__ unsigned g_epoch;
#define TSTAMP(i)
#define TSINIT()
#define TSDUMP()
extern __shared__ __align__(1024) uint8_t smem_raw[];

constexpr int TBL_SC = 5248, TBL = 5264;
constexpr int TBL_C1 = 2624;
constexpr int SIG = 19584;
constexpr int SIG_U = 0, U_LBO = 656, SIG_V3 = 6272, SIG_V5 = 10368, SIG_V7 = 13440, SIG_V9 = 15488, SIG_V2 = 17536;
constexpr int Y2B = 6528, Y3B = 4352;
constexpr int KREC = 160, KSTG = 32 * KREC;
constexpr int OFF_W = 0, OFF_X = 98304, OFF_A = 147456, OFF_B = OFF_A + 8 * KSTG + 2560, OFF_T = OFF_B + 4 * KSTG;
constexpr int OFF_M = OFF_T + 15872;
constexpr int B_AX = Y2B, B_BX = B_AX + 2048, B_R = B_BX + 8192;
constexpr int M_BAR = 0, M_REL = 128, M_EP = 192, M_CSR = 256, M_END = 1280;
constexpr int SMEM_BYTES = OFF_M + M_END + 384;
constexpr int S_WORK = 63232, S_WGB = 2 * SIG + Y2B + Y3B;
static_assert(S_WORK + 3 * S_WGB <= OFF_M && SMEM_BYTES <= 232448, "smem");

struct Params {
  const __nv_bfloat16 *x, *a_re, *a_im, *b_re, *b_im, *c_re, *c_im, *log_dt, *dskip, *w1, *b1, *w2, *b2;
};

__device__ __forceinline__ int opaque(int x) { int v; asm volatile("mov.u32 %0, %1;" : "=r"(v) : "r"(x)); return v; }
__device__ __forceinline__ int rd_bid() { int v; asm volatile("mov.u32 %0, %%ctaid.x;" : "=r"(v)); return v; }
__device__ __forceinline__ uint32_t smem_u32(const void* p) { return (uint32_t)__cvta_generic_to_shared(p); }
__device__ __forceinline__ void mbar_init(uint32_t bar, int cnt) { asm volatile("mbarrier.init.shared::cta.b64 [%0], %1;" ::"r"(bar), "r"(cnt)); }
__device__ __forceinline__ void mbar_expect(uint32_t bar, uint32_t bytes) {
  asm volatile("mbarrier.arrive.expect_tx.shared::cta.b64 _, [%0], %1;" ::"r"(bar), "r"(bytes) : "memory");
}
__device__ __forceinline__ void mbar_wait(uint32_t bar, uint32_t parity) {
  uint32_t done = 0;
#pragma unroll 1
  for (int it = 0; it < SPIN_MAX; it++) {
    asm volatile("{.reg .pred p; mbarrier.try_wait.parity.shared::cta.b64 p, [%1], %2; selp.u32 %0,1,0,p;}"
                 : "=r"(done) : "r"(bar), "r"(parity) : "memory");
    if (done) break;
  }
}
__device__ __forceinline__ void tma_2d(uint32_t dst, const CUtensorMap* m, int c0, int c1, uint32_t bar) {
  asm volatile("cp.async.bulk.tensor.2d.shared::cluster.global.mbarrier::complete_tx::bytes [%0], [%1, {%3, %4}], [%2];"
               ::"r"(dst), "l"(m), "r"(bar), "r"(c0), "r"(c1) : "memory");
}
__device__ __forceinline__ void tma_3d(uint32_t dst, const CUtensorMap* m, int c0, int c1, int c2, uint32_t bar) {
  asm volatile("cp.async.bulk.tensor.3d.shared::cluster.global.mbarrier::complete_tx::bytes [%0], [%1, {%3, %4, %5}], [%2];"
               ::"r"(dst), "l"(m), "r"(bar), "r"(c0), "r"(c1), "r"(c2) : "memory");
}
__device__ __forceinline__ void tma_store_2d(const CUtensorMap* m, uint32_t src, int c0, int c1) {
  asm volatile("cp.async.bulk.tensor.2d.global.shared::cta.bulk_group [%0, {%2, %3}], [%1];"
               ::"l"(m), "r"(src), "r"(c0), "r"(c1) : "memory");
}
__device__ __forceinline__ void bulk_s2g(void* dst, uint32_t src, uint32_t bytes) {
  asm volatile("cp.async.bulk.global.shared::cta.bulk_group [%0], [%1], %2;" ::"l"(dst), "r"(src), "r"(bytes) : "memory");
}
__device__ __forceinline__ void bulk_g2s(uint32_t dst, const void* src, uint32_t bytes, uint32_t bar) {
  asm volatile("cp.async.bulk.shared::cluster.global.mbarrier::complete_tx::bytes [%0], [%1], %2, [%3];"
               ::"r"(dst), "l"(src), "r"(bytes), "r"(bar) : "memory");
}
__device__ __forceinline__ void bulk_commit() { asm volatile("cp.async.bulk.commit_group;" ::: "memory"); }
__device__ __forceinline__ void bulk_wait0() { asm volatile("cp.async.bulk.wait_group 0;" ::: "memory"); }
__device__ __forceinline__ void bulk_wait0_read() { asm volatile("cp.async.bulk.wait_group.read 0;" ::: "memory"); }
__device__ __forceinline__ void fence_async() { asm volatile("fence.proxy.async.shared::cta;" ::: "memory"); }
__device__ __forceinline__ void bar_sync(int id, int n) { asm volatile("bar.sync %0, %1;" ::"r"(id), "r"(n) : "memory"); }
__device__ __forceinline__ void bar_arrive(int id, int n) { asm volatile("bar.arrive %0, %1;" ::"r"(id), "r"(n) : "memory"); }
__device__ __forceinline__ void wg_fence() { asm volatile("wgmma.fence.sync.aligned;" ::: "memory"); }
__device__ __forceinline__ void wg_commit() { asm volatile("wgmma.commit_group.sync.aligned;" ::: "memory"); }
template <int N> __device__ __forceinline__ void wg_wait() { asm volatile("wgmma.wait_group.sync.aligned %0;" ::"n"(N) : "memory"); }
template <int N> __device__ __forceinline__ void fence_regs(float* d) {
#pragma unroll
  for (int i = 0; i < N; i++) asm volatile("" : "+f"(d[i])::"memory");
}
__device__ __forceinline__ uint64_t mkdesc(uint32_t addr, uint32_t lbo, uint32_t sbo, uint32_t sw) {
  return (uint64_t)((addr & 0x3FFFF) >> 4) | ((uint64_t)(lbo >> 4) << 16) | ((uint64_t)(sbo >> 4) << 32) | ((uint64_t)sw << 62);
}
__device__ __forceinline__ uint32_t lds32(uint32_t a) { uint32_t v; asm volatile("ld.shared.b32 %0, [%1];" : "=r"(v) : "r"(a) : "memory"); return v; }
__device__ __forceinline__ float lds32f(uint32_t a) { float v; asm volatile("ld.shared.f32 %0, [%1];" : "=f"(v) : "r"(a) : "memory"); return v; }
__device__ __forceinline__ float2 lds64f(uint32_t a) { float2 v; asm volatile("ld.shared.v2.f32 {%0,%1}, [%2];" : "=f"(v.x), "=f"(v.y) : "r"(a) : "memory"); return v; }
__device__ __forceinline__ uint4 lds128(uint32_t a) {
  uint4 v; asm volatile("ld.shared.v4.b32 {%0,%1,%2,%3}, [%4];" : "=r"(v.x), "=r"(v.y), "=r"(v.z), "=r"(v.w) : "r"(a) : "memory"); return v;
}
__device__ __forceinline__ void sts16(uint32_t a, uint16_t v) { asm volatile("st.shared.b16 [%0], %1;" ::"r"(a), "h"(v) : "memory"); }
__device__ __forceinline__ void sts32f(uint32_t a, float v) { asm volatile("st.shared.f32 [%0], %1;" ::"r"(a), "f"(v) : "memory"); }
__device__ __forceinline__ void sts64f(uint32_t a, float x, float y) { asm volatile("st.shared.v2.f32 [%0], {%1,%2};" ::"r"(a), "f"(x), "f"(y) : "memory"); }
__device__ __forceinline__ void sts128(uint32_t a, uint32_t x, uint32_t y, uint32_t z, uint32_t w) {
  asm volatile("st.shared.v4.b32 [%0], {%1,%2,%3,%4};" ::"r"(a), "r"(x), "r"(y), "r"(z), "r"(w) : "memory");
}
__device__ __forceinline__ void ldsm4(uint32_t a, uint32_t& r0, uint32_t& r1, uint32_t& r2, uint32_t& r3) {
  asm volatile("ldmatrix.sync.aligned.m8n8.x4.shared.b16 {%0,%1,%2,%3}, [%4];" : "=r"(r0), "=r"(r1), "=r"(r2), "=r"(r3) : "r"(a) : "memory");
}
__device__ __forceinline__ void ldsm4t(uint32_t a, uint32_t& r0, uint32_t& r1, uint32_t& r2, uint32_t& r3) {
  asm volatile("ldmatrix.sync.aligned.m8n8.x4.trans.shared.b16 {%0,%1,%2,%3}, [%4];" : "=r"(r0), "=r"(r1), "=r"(r2), "=r"(r3) : "r"(a) : "memory");
}
__device__ __forceinline__ void ldsm2t(uint32_t a, uint32_t& r0, uint32_t& r1) {
  asm volatile("ldmatrix.sync.aligned.m8n8.x2.trans.shared.b16 {%0,%1}, [%2];" : "=r"(r0), "=r"(r1) : "r"(a) : "memory");
}
__device__ __forceinline__ void stsm4(uint32_t a, uint32_t r0, uint32_t r1, uint32_t r2, uint32_t r3) {
  asm volatile("stmatrix.sync.aligned.m8n8.x4.shared.b16 [%0], {%1,%2,%3,%4};" ::"r"(a), "r"(r0), "r"(r1), "r"(r2), "r"(r3) : "memory");
}
__device__ __forceinline__ void mma_f16(float* c, uint32_t a0, uint32_t a1, uint32_t a2, uint32_t a3, uint32_t b0, uint32_t b1) {
  asm("mma.sync.aligned.m16n8k16.row.col.f32.f16.f16.f32 {%0,%1,%2,%3},{%4,%5,%6,%7},{%8,%9},{%0,%1,%2,%3};"
               : "+f"(c[0]), "+f"(c[1]), "+f"(c[2]), "+f"(c[3]) : "r"(a0), "r"(a1), "r"(a2), "r"(a3), "r"(b0), "r"(b1));
}
__device__ __forceinline__ uint4 ld_relaxed4(const void* p) {
  uint4 v; asm volatile("ld.relaxed.gpu.global.v4.b32 {%0,%1,%2,%3}, [%4];" : "=r"(v.x), "=r"(v.y), "=r"(v.z), "=r"(v.w) : "l"(p) : "memory"); return v;
}
__device__ __forceinline__ void st_relaxed2(void* p, uint32_t x, uint32_t y) {
  asm volatile("st.relaxed.gpu.global.v2.b32 [%0], {%1,%2};" ::"l"(p), "r"(x), "r"(y) : "memory");
}
__device__ __forceinline__ uint4 ld_b128(const void* p) {
  uint4 v;
  asm volatile("{.reg .b128 t; .reg .b64 a, c; ld.relaxed.gpu.global.b128 t, [%4]; mov.b128 {a, c}, t; mov.b64 {%0,%1}, a; mov.b64 {%2,%3}, c;}"
               : "=r"(v.x), "=r"(v.y), "=r"(v.z), "=r"(v.w) : "l"(p) : "memory");
  return v;
}
__device__ __forceinline__ void st_b128(void* p, uint32_t tag, uint32_t x, uint32_t y, uint32_t z, uint32_t w) {
  asm volatile("{.reg .b128 t; .reg .b64 a, c; mov.b64 a, {%1,%2}; mov.b64 c, {%3,%4}; mov.b128 t, {a, c}; st.relaxed.gpu.global.b128 [%0], t;}"
               ::"l"(p), "r"((x & ~1u) | tag), "r"(y), "r"(z), "r"(w) : "memory");
}
__device__ __forceinline__ unsigned ld_relaxed1(const unsigned* p) {
  unsigned v; asm volatile("ld.relaxed.gpu.global.u32 %0, [%1];" : "=r"(v) : "l"(p) : "memory"); return v;
}
__device__ __forceinline__ void red_release(unsigned* p) {
  asm volatile("red.release.gpu.global.add.u32 [%0], 1;" ::"l"(p) : "memory");
}
__device__ __forceinline__ void wait_count(const unsigned* p, unsigned target) {
#pragma unroll 1
  for (int it = 0; it < SPIN_MAX; it++) {
    if ((int)(ld_relaxed1(p) - target) >= 0) break;
    __nanosleep(40);
  }
  asm volatile("fence.acq_rel.gpu;" ::: "memory");
}
__device__ __forceinline__ uint32_t pack_h2(float lo, float hi) { uint32_t r; asm("cvt.rn.f16x2.f32 %0, %1, %2;" : "=r"(r) : "f"(hi), "f"(lo)); return r; }
__device__ __forceinline__ uint32_t pack_bf2(float lo, float hi) { uint32_t r; asm("cvt.rn.bf16x2.f32 %0, %1, %2;" : "=r"(r) : "f"(hi), "f"(lo)); return r; }
__device__ __forceinline__ uint32_t pack_bf2v(float lo, float hi) { uint32_t r; asm volatile("cvt.rn.bf16x2.f32 %0, %1, %2;" : "=r"(r) : "f"(hi), "f"(lo)); return r; }
__device__ __forceinline__ float bf_lo(uint32_t w) { return __uint_as_float(w << 16); }
__device__ __forceinline__ float bf_hi(uint32_t w) { return __uint_as_float(w & 0xffff0000u); }
__device__ __forceinline__ float rbf(float v) { return __bfloat162float(__float2bfloat16_rn(v)); }
__device__ __forceinline__ float2 h2f(uint32_t w) { return __half22float2(*reinterpret_cast<__half2*>(&w)); }
__device__ __forceinline__ float ex2f(float v) { float r; asm("ex2.approx.ftz.f32 %0, %1;" : "=f"(r) : "f"(v)); return r; }
__device__ __forceinline__ float rcpf_(float v) { float r; asm("rcp.approx.f32 %0, %1;" : "=f"(r) : "f"(v)); return r; }
__device__ __forceinline__ float sqrtf_(float v) { float r; asm("sqrt.approx.f32 %0, %1;" : "=f"(r) : "f"(v)); return r; }
__device__ __forceinline__ float tanhf_(float v) { float r; asm volatile("tanh.approx.f32 %0, %1;" : "=f"(r) : "f"(v)); return r; }

__device__ __forceinline__ void wg_ss_bf16_n256(float* d, uint64_t da, uint64_t db, int sc) {
  asm volatile("{.reg .pred p; setp.ne.b32 p, %130, 0;\n"
    "wgmma.mma_async.sync.aligned.m64n256k16.f32.bf16.bf16 {%0, %1, %2, %3, %4, %5, %6, %7, %8, %9, %10, %11, %12, %13, %14, %15, %16, %17, %18, %19, %20, %21, %22, %23, %24, %25, %26, %27, %28, %29, %30, %31, %32, %33, %34, %35, %36, %37, %38, %39, %40, %41, %42, %43, %44, %45, %46, %47, %48, %49, %50, %51, %52, %53, %54, %55, %56, %57, %58, %59, %60, %61, %62, %63, %64, %65, %66, %67, %68, %69, %70, %71, %72, %73, %74, %75, %76, %77, %78, %79, %80, %81, %82, %83, %84, %85, %86, %87, %88, %89, %90, %91, %92, %93, %94, %95, %96, %97, %98, %99, %100, %101, %102, %103, %104, %105, %106, %107, %108, %109, %110, %111, %112, %113, %114, %115, %116, %117, %118, %119, %120, %121, %122, %123, %124, %125, %126, %127}, %128, %129, p, 1, 1, 0, 1;}\n"
    : "+f"(d[0]), "+f"(d[1]), "+f"(d[2]), "+f"(d[3]), "+f"(d[4]), "+f"(d[5]), "+f"(d[6]), "+f"(d[7]), "+f"(d[8]), "+f"(d[9]), "+f"(d[10]), "+f"(d[11]), "+f"(d[12]), "+f"(d[13]), "+f"(d[14]), "+f"(d[15]), "+f"(d[16]), "+f"(d[17]), "+f"(d[18]), "+f"(d[19]), "+f"(d[20]), "+f"(d[21]), "+f"(d[22]), "+f"(d[23]), "+f"(d[24]), "+f"(d[25]), "+f"(d[26]), "+f"(d[27]), "+f"(d[28]), "+f"(d[29]), "+f"(d[30]), "+f"(d[31]), "+f"(d[32]), "+f"(d[33]), "+f"(d[34]), "+f"(d[35]), "+f"(d[36]), "+f"(d[37]), "+f"(d[38]), "+f"(d[39]), "+f"(d[40]), "+f"(d[41]), "+f"(d[42]), "+f"(d[43]), "+f"(d[44]), "+f"(d[45]), "+f"(d[46]), "+f"(d[47]), "+f"(d[48]), "+f"(d[49]), "+f"(d[50]), "+f"(d[51]), "+f"(d[52]), "+f"(d[53]), "+f"(d[54]), "+f"(d[55]), "+f"(d[56]), "+f"(d[57]), "+f"(d[58]), "+f"(d[59]), "+f"(d[60]), "+f"(d[61]), "+f"(d[62]), "+f"(d[63]), "+f"(d[64]), "+f"(d[65]), "+f"(d[66]), "+f"(d[67]), "+f"(d[68]), "+f"(d[69]), "+f"(d[70]), "+f"(d[71]), "+f"(d[72]), "+f"(d[73]), "+f"(d[74]), "+f"(d[75]), "+f"(d[76]), "+f"(d[77]), "+f"(d[78]), "+f"(d[79]), "+f"(d[80]), "+f"(d[81]), "+f"(d[82]), "+f"(d[83]), "+f"(d[84]), "+f"(d[85]), "+f"(d[86]), "+f"(d[87]), "+f"(d[88]), "+f"(d[89]), "+f"(d[90]), "+f"(d[91]), "+f"(d[92]), "+f"(d[93]), "+f"(d[94]), "+f"(d[95]), "+f"(d[96]), "+f"(d[97]), "+f"(d[98]), "+f"(d[99]), "+f"(d[100]), "+f"(d[101]), "+f"(d[102]), "+f"(d[103]), "+f"(d[104]), "+f"(d[105]), "+f"(d[106]), "+f"(d[107]), "+f"(d[108]), "+f"(d[109]), "+f"(d[110]), "+f"(d[111]), "+f"(d[112]), "+f"(d[113]), "+f"(d[114]), "+f"(d[115]), "+f"(d[116]), "+f"(d[117]), "+f"(d[118]), "+f"(d[119]), "+f"(d[120]), "+f"(d[121]), "+f"(d[122]), "+f"(d[123]), "+f"(d[124]), "+f"(d[125]), "+f"(d[126]), "+f"(d[127])
    : "l"(da), "l"(db), "r"(sc));
}

__device__ __forceinline__ void wg_ss_bf16_n256k(float* d, uint64_t da, uint64_t db, int sc) {
  asm volatile("{.reg .pred p; setp.ne.b32 p, %130, 0;\n"
    "wgmma.mma_async.sync.aligned.m64n256k16.f32.bf16.bf16 {%0, %1, %2, %3, %4, %5, %6, %7, %8, %9, %10, %11, %12, %13, %14, %15, %16, %17, %18, %19, %20, %21, %22, %23, %24, %25, %26, %27, %28, %29, %30, %31, %32, %33, %34, %35, %36, %37, %38, %39, %40, %41, %42, %43, %44, %45, %46, %47, %48, %49, %50, %51, %52, %53, %54, %55, %56, %57, %58, %59, %60, %61, %62, %63, %64, %65, %66, %67, %68, %69, %70, %71, %72, %73, %74, %75, %76, %77, %78, %79, %80, %81, %82, %83, %84, %85, %86, %87, %88, %89, %90, %91, %92, %93, %94, %95, %96, %97, %98, %99, %100, %101, %102, %103, %104, %105, %106, %107, %108, %109, %110, %111, %112, %113, %114, %115, %116, %117, %118, %119, %120, %121, %122, %123, %124, %125, %126, %127}, %128, %129, p, 1, 1, 0, 0;}\n"
    : "+f"(d[0]), "+f"(d[1]), "+f"(d[2]), "+f"(d[3]), "+f"(d[4]), "+f"(d[5]), "+f"(d[6]), "+f"(d[7]), "+f"(d[8]), "+f"(d[9]), "+f"(d[10]), "+f"(d[11]), "+f"(d[12]), "+f"(d[13]), "+f"(d[14]), "+f"(d[15]), "+f"(d[16]), "+f"(d[17]), "+f"(d[18]), "+f"(d[19]), "+f"(d[20]), "+f"(d[21]), "+f"(d[22]), "+f"(d[23]), "+f"(d[24]), "+f"(d[25]), "+f"(d[26]), "+f"(d[27]), "+f"(d[28]), "+f"(d[29]), "+f"(d[30]), "+f"(d[31]), "+f"(d[32]), "+f"(d[33]), "+f"(d[34]), "+f"(d[35]), "+f"(d[36]), "+f"(d[37]), "+f"(d[38]), "+f"(d[39]), "+f"(d[40]), "+f"(d[41]), "+f"(d[42]), "+f"(d[43]), "+f"(d[44]), "+f"(d[45]), "+f"(d[46]), "+f"(d[47]), "+f"(d[48]), "+f"(d[49]), "+f"(d[50]), "+f"(d[51]), "+f"(d[52]), "+f"(d[53]), "+f"(d[54]), "+f"(d[55]), "+f"(d[56]), "+f"(d[57]), "+f"(d[58]), "+f"(d[59]), "+f"(d[60]), "+f"(d[61]), "+f"(d[62]), "+f"(d[63]), "+f"(d[64]), "+f"(d[65]), "+f"(d[66]), "+f"(d[67]), "+f"(d[68]), "+f"(d[69]), "+f"(d[70]), "+f"(d[71]), "+f"(d[72]), "+f"(d[73]), "+f"(d[74]), "+f"(d[75]), "+f"(d[76]), "+f"(d[77]), "+f"(d[78]), "+f"(d[79]), "+f"(d[80]), "+f"(d[81]), "+f"(d[82]), "+f"(d[83]), "+f"(d[84]), "+f"(d[85]), "+f"(d[86]), "+f"(d[87]), "+f"(d[88]), "+f"(d[89]), "+f"(d[90]), "+f"(d[91]), "+f"(d[92]), "+f"(d[93]), "+f"(d[94]), "+f"(d[95]), "+f"(d[96]), "+f"(d[97]), "+f"(d[98]), "+f"(d[99]), "+f"(d[100]), "+f"(d[101]), "+f"(d[102]), "+f"(d[103]), "+f"(d[104]), "+f"(d[105]), "+f"(d[106]), "+f"(d[107]), "+f"(d[108]), "+f"(d[109]), "+f"(d[110]), "+f"(d[111]), "+f"(d[112]), "+f"(d[113]), "+f"(d[114]), "+f"(d[115]), "+f"(d[116]), "+f"(d[117]), "+f"(d[118]), "+f"(d[119]), "+f"(d[120]), "+f"(d[121]), "+f"(d[122]), "+f"(d[123]), "+f"(d[124]), "+f"(d[125]), "+f"(d[126]), "+f"(d[127])
    : "l"(da), "l"(db), "r"(sc));
}

__device__ __forceinline__ void wg_rs_bf16_n64(float* d, uint32_t a0, uint32_t a1, uint32_t a2, uint32_t a3, uint64_t db, int sc) {
  asm volatile("{.reg .pred p; setp.ne.b32 p, %37, 0;\n"
    "wgmma.mma_async.sync.aligned.m64n64k16.f32.bf16.bf16 {%0, %1, %2, %3, %4, %5, %6, %7, %8, %9, %10, %11, %12, %13, %14, %15, %16, %17, %18, %19, %20, %21, %22, %23, %24, %25, %26, %27, %28, %29, %30, %31}, {%32,%33,%34,%35}, %36, p, 1, 1, 1;}\n"
    : "+f"(d[0]), "+f"(d[1]), "+f"(d[2]), "+f"(d[3]), "+f"(d[4]), "+f"(d[5]), "+f"(d[6]), "+f"(d[7]), "+f"(d[8]), "+f"(d[9]), "+f"(d[10]), "+f"(d[11]), "+f"(d[12]), "+f"(d[13]), "+f"(d[14]), "+f"(d[15]), "+f"(d[16]), "+f"(d[17]), "+f"(d[18]), "+f"(d[19]), "+f"(d[20]), "+f"(d[21]), "+f"(d[22]), "+f"(d[23]), "+f"(d[24]), "+f"(d[25]), "+f"(d[26]), "+f"(d[27]), "+f"(d[28]), "+f"(d[29]), "+f"(d[30]), "+f"(d[31])
    : "r"(a0), "r"(a1), "r"(a2), "r"(a3), "l"(db), "r"(sc));
}

__device__ __forceinline__ void wg_rs_f16_n32k(float* d, uint32_t a0, uint32_t a1, uint32_t a2, uint32_t a3, uint64_t db, int sc) {
  asm volatile("{.reg .pred p; setp.ne.b32 p, %21, 0;\n"
    "wgmma.mma_async.sync.aligned.m64n32k16.f32.f16.f16 {%0, %1, %2, %3, %4, %5, %6, %7, %8, %9, %10, %11, %12, %13, %14, %15}, {%16,%17,%18,%19}, %20, p, 1, 1, 0;}\n"
    : "+f"(d[0]), "+f"(d[1]), "+f"(d[2]), "+f"(d[3]), "+f"(d[4]), "+f"(d[5]), "+f"(d[6]), "+f"(d[7]), "+f"(d[8]), "+f"(d[9]), "+f"(d[10]), "+f"(d[11]), "+f"(d[12]), "+f"(d[13]), "+f"(d[14]), "+f"(d[15])
    : "r"(a0), "r"(a1), "r"(a2), "r"(a3), "l"(db), "r"(sc));
}

__device__ __forceinline__ void wg_rs_f16_n24t(float* d, uint32_t a0, uint32_t a1, uint32_t a2, uint32_t a3, uint64_t db, int sc) {
  asm volatile("{.reg .pred p; setp.ne.b32 p, %17, 0;\n"
    "wgmma.mma_async.sync.aligned.m64n24k16.f32.f16.f16 {%0, %1, %2, %3, %4, %5, %6, %7, %8, %9, %10, %11}, {%12,%13,%14,%15}, %16, p, 1, 1, 1;}\n"
    : "+f"(d[0]), "+f"(d[1]), "+f"(d[2]), "+f"(d[3]), "+f"(d[4]), "+f"(d[5]), "+f"(d[6]), "+f"(d[7]), "+f"(d[8]), "+f"(d[9]), "+f"(d[10]), "+f"(d[11])
    : "r"(a0), "r"(a1), "r"(a2), "r"(a3), "l"(db), "r"(sc));
}

__device__ __forceinline__ void wg_rs_f16_n16t(float* d, uint32_t a0, uint32_t a1, uint32_t a2, uint32_t a3, uint64_t db, int sc) {
  asm volatile("{.reg .pred p; setp.ne.b32 p, %13, 0;\n"
    "wgmma.mma_async.sync.aligned.m64n16k16.f32.f16.f16 {%0, %1, %2, %3, %4, %5, %6, %7}, {%8,%9,%10,%11}, %12, p, 1, 1, 1;}\n"
    : "+f"(d[0]), "+f"(d[1]), "+f"(d[2]), "+f"(d[3]), "+f"(d[4]), "+f"(d[5]), "+f"(d[6]), "+f"(d[7])
    : "r"(a0), "r"(a1), "r"(a2), "r"(a3), "l"(db), "r"(sc));
}

struct cf { float x, y; };
__device__ __forceinline__ cf cmul(cf a, cf b) { cf r; r.x = fmaf(a.x, b.x, -a.y * b.y); r.y = fmaf(a.x, b.y, a.y * b.x); return r; }
__device__ __forceinline__ cf zpow(float rho2, float phi, float e) {
  const float m = ex2f(rho2 * e), ang = phi * e;
  cf r; r.x = m * __cosf(ang); r.y = m * __sinf(ang); return r;
}
__device__ __forceinline__ __half2 H2(uint32_t v) { return *reinterpret_cast<__half2*>(&v); }
__device__ __forceinline__ uint32_t U32(__half2 v) { return *reinterpret_cast<uint32_t*>(&v); }
__device__ __forceinline__ uint32_t hprod(uint32_t v, uint32_t r, uint32_t rr) {
  return U32(__hfma2(__high2half2(H2(v)), H2(rr), __hmul2(__low2half2(H2(v)), H2(r))));
}
__device__ __forceinline__ void hprod2(uint32_t re, uint32_t im, uint32_t r, uint32_t& ore, uint32_t& oim) {
  const __half2 rx = __low2half2(H2(r)), ry = __high2half2(H2(r));
  ore = U32(__hfma2(H2(re), rx, __hneg2(__hmul2(H2(im), ry))));
  oim = U32(__hfma2(H2(re), ry, __hmul2(H2(im), rx)));
}
__device__ __forceinline__ uint32_t rot90(uint32_t v) { return __byte_perm(v, 0, 0x1032) ^ 0x00008000u; }
__device__ __forceinline__ uint32_t hadd2u(uint32_t a, uint32_t b) { return U32(__hadd2(H2(a), H2(b))); }

struct KgIn { uint32_t cur[6], nxt[6]; uint16_t ldt, dk; };
__device__ __forceinline__ void kgen_load(const Params& p, int d, int wd0, int nw, int lane, KgIn& k) {
  const int off = d * (NST / 2) + 32 * wd0 + lane;
  const uint32_t* P[6] = {(const uint32_t*)p.a_re, (const uint32_t*)p.a_im, (const uint32_t*)p.b_re,
                          (const uint32_t*)p.b_im, (const uint32_t*)p.c_re, (const uint32_t*)p.c_im};
#pragma unroll
  for (int i = 0; i < 6; i++) { k.cur[i] = __ldg(P[i] + off); k.nxt[i] = __ldg(P[i] + off + 32 * (nw - 1)); }
  k.ldt = __ldg((const uint16_t*)p.log_dt + d); k.dk = __ldg((const uint16_t*)p.dskip + d);
}
__device__ __forceinline__ float pow2_floor(float v) { return __uint_as_float(__float_as_uint(fminf(fmaxf(v, 1e-30f), 1e30f)) & 0x7f800000u); }
__device__ __forceinline__ void kgen_mma(float* acc, const uint32_t (*A)[4], const uint32_t (*B)[6], int csrc) {
#pragma unroll
  for (int ks = 0; ks < 4; ks++) {
    const uint32_t rl = __shfl_sync(0xffffffffu, B[ks][4], csrc), rh = __shfl_sync(0xffffffffu, B[ks][5], csrc);
    const uint32_t rlr = rot90(rl), rhr = rot90(rh);
    mma_f16(acc + 0, A[ks][0], A[ks][1], A[ks][2], A[ks][3], B[ks][0], B[ks][1]);
    mma_f16(acc + 4, A[ks][0], A[ks][1], A[ks][2], A[ks][3], B[ks][2], B[ks][3]);
    mma_f16(acc + 8, A[ks][0], A[ks][1], A[ks][2], A[ks][3], B[ks][4], B[ks][5]);
    const uint32_t c0 = hprod(A[ks][0], rl, rlr), c1 = hprod(A[ks][1], rl, rlr);
    const uint32_t c2 = hprod(A[ks][2], rh, rhr), c3 = hprod(A[ks][3], rh, rhr);
    mma_f16(acc + 12, c0, c1, c2, c3, B[ks][0], B[ks][1]);
    mma_f16(acc + 16, c0, c1, c2, c3, B[ks][2], B[ks][3]);
    mma_f16(acc + 20, c0, c1, c2, c3, B[ks][4], B[ks][5]);
  }
}
__device__ __forceinline__ void kgen_warp(KgIn& k, int nw, uint32_t stg, uint32_t tbl, int lane) {
  float dl, dt, sc, inv_sc;
  {
    const uint32_t M = 0x7fff7fffu;
    uint32_t mx[2];
#pragma unroll
    for (int i = 0; i < 2; i++) {
      const uint32_t m = __vmaxu2(__vmaxu2(k.cur[2 + 2 * i] & M, k.cur[3 + 2 * i] & M), __vmaxu2(k.nxt[2 + 2 * i] & M, k.nxt[3 + 2 * i] & M));
      mx[i] = __reduce_max_sync(0xffffffffu, max(m << 16, m & 0xffff0000u));
    }
    dt = rbf(ex2f(bf_lo(k.ldt) * 1.4426950408889634f));
    sc = pow2_floor(0.125f * __uint_as_float(mx[0]) * __uint_as_float(mx[1]));
    inv_sc = rcpf_(sc);
    if (lane == 0) sts64f(tbl + TBL_SC + 8, dt, bf_lo(k.dk) * rcpf_(dt));
    dl = dt * 1.4426950408889634f;
  }
  const uint32_t st0 = stg + lane * KREC + (((lane >> 2) & 1) << 4), st1 = st0 ^ 16;
  const int mat = lane >> 3, rowi = lane & 7;
  const uint32_t ldB = stg + (4 * (mat & 1) + (rowi >> 1)) * KREC + ((((mat >> 1) * 2 + (rowi & 1)) << 4) ^ ((mat & 1) << 4));
  const uint32_t ldA = stg + (4 * (mat >> 1) + (rowi >> 1)) * KREC + ((((mat & 1) * 2 + (rowi & 1)) << 4) ^ ((mat >> 1) << 4)) + 96;
  const int csrc = 20 + (lane & 3);
  float acc[24];
  uint32_t B[4][6], A[4][4];
#pragma unroll
  for (int i = 0; i < 24; i++) { acc[i] = 0.f; B[i / 6][i % 6] = 0u; }
#pragma unroll
  for (int i = 0; i < 16; i++) A[i / 4][i % 4] = 0u;
#pragma unroll 1
  for (int it = 0; it < 2 * nw; it++) {
    const uint32_t sel = (it & 1) ? 0x3244u : 0x1044u;
    float v[6];
#pragma unroll
    for (int i = 0; i < 6; i++) { v[i] = __uint_as_float(__byte_perm(k.cur[i], 0, sel)); if (it == 1) k.cur[i] = k.nxt[i]; }
    const float rho2 = v[0] * dl, phi = v[1] * dt;
    const cf bb = {v[2] * inv_sc, v[3] * -inv_sc}, cc = {v[4], -v[5]};
    cf X[8];
    X[0] = cmul(cc, bb);
    const cf z1 = zpow(rho2, -phi, 1.f), z8 = zpow(rho2, phi, 8.f), z64 = zpow(rho2, phi, 64.f);
    const cf y1 = zpow(rho2, -phi, 256.f), y4 = zpow(rho2, -phi, 1024.f);
    kgen_mma(acc, A, B, csrc);
    const cf z2 = cmul(z1, z1);
    X[1] = cmul(X[0], z1);
#pragma unroll
    for (int j = 2; j < 8; j++) X[j] = cmul(X[j - 2], z2);
    const cf a0 = cmul(X[0], y1), a1 = cmul(X[2], y1), a2 = cmul(X[4], y1), a3 = cmul(X[6], y1);
    const cf a4 = cmul(a0, y1), a5 = cmul(a2, y1);
    const cf a6 = cmul(a4, y1), a7 = cmul(a5, y1);
    const cf v0 = cmul(X[0], y4), v1 = cmul(a0, y4), v2 = cmul(a4, y4), v3 = cmul(a6, y4), v4 = cmul(v0, y4);
    const cf f2 = cmul(z8, z8), f3 = cmul(f2, z8), f4 = cmul(f2, f2), f5 = cmul(f3, f2), f6 = cmul(f4, f2), f7 = cmul(f4, f3);
    const cf z128 = cmul(z64, z64);
    const uint32_t fr[4] = {pack_h2(1.f, z8.x), pack_h2(f2.x, f3.x), pack_h2(f4.x, f5.x), pack_h2(f6.x, f7.x)};
    const uint32_t fi[4] = {pack_h2(0.f, z8.y), pack_h2(f2.y, f3.y), pack_h2(f4.y, f5.y), pack_h2(f6.y, f7.y)};
    const uint32_t h64 = pack_h2(z64.x, z64.y);
    uint32_t gr[4], gi[4];
#pragma unroll
    for (int j = 0; j < 4; j++) hprod2(fr[j], fi[j], h64, gr[j], gi[j]);
    sts128(st0, pack_h2(X[0].x, X[1].x), pack_h2(X[2].x, X[3].x), pack_h2(X[4].x, X[5].x), pack_h2(X[6].x, X[7].x));
    sts128(st1, pack_h2(X[0].y, X[1].y), pack_h2(X[2].y, X[3].y), pack_h2(X[4].y, X[5].y), pack_h2(X[6].y, X[7].y));
    sts128(st0 + 96, fr[0], fr[1], fr[2], fr[3]);
    sts128(st1 + 96, fi[0], fi[1], fi[2], fi[3]);
    sts128(st0 + 128, gr[0], gr[1], gr[2], gr[3]);
    sts128(st1 + 128, gi[0], gi[1], gi[2], gi[3]);
    sts128(st0 + 32, pack_h2(a0.x, a1.x), pack_h2(a2.x, a3.x), pack_h2(a4.x, a5.x), pack_h2(a6.x, a7.x));
    sts128(st1 + 32, pack_h2(a0.y, a1.y), pack_h2(a2.y, a3.y), pack_h2(a4.y, a5.y), pack_h2(a6.y, a7.y));
    sts128(st0 + 64, pack_h2(v0.x, v1.x), pack_h2(v2.x, v3.x), pack_h2(v4.x, z128.x), h64);
    sts128(st1 + 64, pack_h2(v0.y, v1.y), pack_h2(v2.y, v3.y), pack_h2(v4.y, z128.y), h64);
    __syncwarp();
#pragma unroll
    for (int ks = 0; ks < 4; ks++) {
      ldsm2t(ldB + ks * 8 * KREC + 64, B[ks][4], B[ks][5]);
      ldsm4t(ldA + ks * 8 * KREC, A[ks][0], A[ks][1], A[ks][2], A[ks][3]);
      ldsm4t(ldB + ks * 8 * KREC, B[ks][0], B[ks][1], B[ks][2], B[ks][3]);
    }
  }
  kgen_mma(acc, A, B, csrc);
#pragma unroll
  for (int q = 0; q < 4; q++)
#pragma unroll
    for (int nt = 0; nt < 3; nt++) {
      const float* a = acc + 12 * (q >> 1) + 4 * nt + 2 * (q & 1);
      sts64f(stg + (q * 3 + nt) * 256 + lane * 8, a[0] * sc, a[1] * sc);
    }
  if (lane == 0) sts32f(stg + 3072, sc);
}

__device__ __forceinline__ void tput(uint32_t tbl, int X, uint32_t h) {
  sts16(tbl + 2 * (1296 - X), (uint16_t)h);
  sts16(tbl + TBL_C1 + 2 * (1297 - X), (uint16_t)h);
}
__device__ __forceinline__ void ktab_build(uint32_t src, bool four, int q, uint32_t tbl, int lane) {
  const int tq = lane & 3, r = 8 * q + (lane >> 2);
  float v[6];
  const float2 dd = lds64f(tbl + TBL_SC + 8);
  float sc = fmaxf(fmaxf(lds32f(src + 3072), lds32f(src + 3072 + KSTG)), pow2_floor(fabsf(dd.y) * (1.f / 4096.f)));
  if (four) sc = fmaxf(sc, fmaxf(lds32f(src + 3072 + 2 * KSTG), lds32f(src + 3072 + 3 * KSTG)));
  const float inv = rcpf_(sc);
  src += q * 768 + lane * 8;
#pragma unroll
  for (int nt = 0; nt < 3; nt++) {
    const float2 a = lds64f(src + nt * 256), c = lds64f(src + nt * 256 + KSTG);
    v[2 * nt] = a.x + c.x; v[2 * nt + 1] = a.y + c.y;
  }
  if (four) {
#pragma unroll
    for (int nt = 0; nt < 3; nt++) {
      const float2 a = lds64f(src + nt * 256 + 2 * KSTG), c = lds64f(src + nt * 256 + 3 * KSTG);
      v[2 * nt] += a.x + c.x; v[2 * nt + 1] += a.y + c.y;
    }
  }
  const bool first = (r == 0);
  if (first && tq == 0) { v[0] += dd.y; sts64f(tbl + TBL_SC, v[4] * inv, dd.x * sc); }
  const uint32_t h0 = pack_h2(v[0] * inv, v[1] * inv), h1 = pack_h2(v[2] * inv, v[3] * inv), h2 = pack_h2(v[4] * inv, v[5] * inv);
  tput(tbl, 64 + 8 * r + 2 * tq, h0);
  tput(tbl, 65 + 8 * r + 2 * tq, h0 >> 16);
  const bool lo = tq < 2;
  const int Xd = 320 + 8 * r + 4 * tq, k2 = 32 * (tq - 2) + r;
  tput(tbl, lo ? Xd + 2 : 720 + k2, h1 >> 16);
  const bool sp = first && tq == 2;
  const int Xa = lo ? Xd : (sp ? 576 : 911 + k2);
  tput(tbl, Xa, h1);
  if (lo || sp) {
    tput(tbl, Xa + 1, h1);
    if (Xa != 320) tput(tbl, Xa - 1, h1);
  }
  if (sp) { tput(tbl, 578, h1); tput(tbl, 1295, h2); }
  if (lo) {
    const int X3 = ((r & 1) ? 1104 : 1231) + 32 * tq + (r >> 1);
    tput(tbl, X3 == 1231 ? 975 : X3, h2);
    tput(tbl, X3 + 16, h2 >> 16);
  }
}

__device__ __forceinline__ void sig_windows(uint32_t sig, int t) {
  uint32_t U[20];
#pragma unroll
  for (int c = 0; c < 5; c++) {
    const int kap = 2 * t - 3 + c + 72;
    const uint4 v = lds128(sig + SIG_U + (kap & 7) * U_LBO + (kap >> 3) * 16);
    U[4 * c] = v.x; U[4 * c + 1] = v.y; U[4 * c + 2] = v.z; U[4 * c + 3] = v.w;
  }
  uint32_t O[19], A2[17], A4[17], V2[8], V5[8];
#pragma unroll
  for (int i = 3; i < 19; i++) O[i] = __byte_perm(U[i - 1], U[i], 0x5432);
#pragma unroll
  for (int i = 3; i < 17; i++) A2[i] = hadd2u(U[i], O[i]);
#pragma unroll
  for (int i = 4; i < 17; i++) A4[i] = hadd2u(A2[i], A2[i - 1]);
#pragma unroll
  for (int k = 0; k < 8; k++) { V2[k] = hadd2u(O[11 + k], U[10 + k]); V5[k] = hadd2u(A4[9 + k], U[7 + k]); }
#pragma unroll
  for (int h = 0; h < 2; h++) {
    sts128(sig + SIG_V3 + t * 32 + h * 16, hadd2u(V2[4 * h], O[10 + 4 * h]), hadd2u(V2[4 * h + 1], O[11 + 4 * h]),
           hadd2u(V2[4 * h + 2], O[12 + 4 * h]), hadd2u(V2[4 * h + 3], O[13 + 4 * h]));
    sts128(sig + SIG_V5 + t * 32 + h * 16, V5[4 * h], V5[4 * h + 1], V5[4 * h + 2], V5[4 * h + 3]);
  }
  if (t < 64) {
    uint32_t V7[8], V9[8];
#pragma unroll
    for (int k = 0; k < 8; k++) {
      V7[k] = hadd2u(V5[k], hadd2u(O[10 + k], O[7 + k]));
      V9[k] = hadd2u(hadd2u(A4[6 + k], A4[4 + k]), U[2 + k]);
    }
#pragma unroll
    for (int h = 0; h < 2; h++) {
      sts128(sig + SIG_V7 + h * 1024 + t * 16, V7[4 * h], V7[4 * h + 1], V7[4 * h + 2], V7[4 * h + 3]);
      sts128(sig + SIG_V9 + h * 1024 + t * 16, V9[4 * h], V9[4 * h + 1], V9[4 * h + 2], V9[4 * h + 3]);
      sts128(sig + SIG_V2 + h * 1024 + t * 16, V2[4 * h], V2[4 * h + 1], V2[4 * h + 2], V2[4 * h + 3]);
    }
  }
}

__device__ __forceinline__ void conv_channel(uint32_t tbl, uint32_t sig, uint32_t y2b, uint32_t y3b, float k1024,
                                             int w, int lane, int barid, float* res, int ts) {
  TSTAMP(ts);
  const int g = lane >> 2, tq = lane & 3;
  const uint32_t tb = tbl + ((g & 1) ? TBL_C1 + 2 : 0) + 2 * (1296 - (g - 2 * tq)) - 32 * w + 112;
  float a2[12], a3[8];
#pragma unroll
  for (int i = 0; i < 16; i++) res[i] = 0.f;
#pragma unroll
  for (int i = 0; i < 12; i++) a2[i] = 0.f;
#pragma unroll
  for (int q = 0; q < 4; q++) {
    const float2 f = h2f(lds32(sig + SIG_V2 + (q >> 1) * 1024 + (16 * w + 8 * (q & 1) + g) * 16 + tq * 4));
    a3[2 * q] = k1024 * f.x;
    a3[2 * q + 1] = k1024 * f.y;
  }
  const uint64_t dU = mkdesc(sig + SIG_U, U_LBO, 128, 0);
  const uint64_t dV = mkdesc(sig, 128, 1024, 0);
  fence_regs<16>(res); fence_regs<12>(a2); fence_regs<8>(a3);
  constexpr int LB = 2 * U_LBO / 16;
  uint32_t Rd[75], R2[2][17], R3[2][9];
  auto load_group = [&](int gi) {
    const int it = gi >> 1, hb = gi & 1;
    if (gi == 0) Rd[0] = lds32(tb - 128);
#pragma unroll
    for (int i = 1; i < (gi == 17 ? 7 : 5); i++) Rd[4 * gi + i] = lds32(tb - 128 - 16 * (4 * gi + i));
    if (gi < 16) {
      const int sg = it >> 2, n2 = gi & 7;
      if (n2 == 0) R2[sg][0] = lds32(tb - 1440 - 384 * sg);
      R2[sg][2 * n2 + 1] = lds32(tb - 1440 - 384 * sg - 16 * (2 * n2 + 1));
      R2[sg][2 * n2 + 2] = lds32(tb - 1440 - 384 * sg - 16 * (2 * n2 + 2));
      if (!hb) {
        const int n3 = it & 3;
        if (n3 == 0) R3[sg][0] = lds32(tb - 2208 - 256 * sg);
        R3[sg][2 * n3 + 1] = lds32(tb - 2208 - 256 * sg - 16 * (2 * n3 + 1));
        R3[sg][2 * n3 + 2] = lds32(tb - 2208 - 256 * sg - 16 * (2 * n3 + 2));
      }
    }
  };
  auto dense = [&](int n) {
    wg_rs_f16_n32k(res, Rd[2 * n + 1], Rd[2 * n + 2], Rd[2 * n], Rd[2 * n + 1], dU + ((3 - (n & 3)) * LB + 9 - (n >> 2)), 1);
  };
  load_group(0);
  load_group(1);
#pragma unroll
  for (int gi = 0; gi < 18; gi++) {
    const int it = gi >> 1, sg = it >> 2, n2 = gi & 7, n3 = it & 3;
    wg_fence();
    dense(2 * gi);
    if (gi < 16)
      wg_rs_f16_n24t(a2, R2[sg][2 * n2 + 1], R2[sg][2 * n2 + 2], R2[sg][2 * n2], R2[sg][2 * n2 + 1],
                     dV + ((SIG_V3 + 768) / 16 + 256 * sg - 16 * (n2 & 3) - 64 * (n2 >> 2)), 1);
    dense(2 * gi + 1);
    if (gi < 16 && !(gi & 1))
      wg_rs_f16_n16t(a3, R3[sg][2 * n3 + 1], R3[sg][2 * n3 + 2], R3[sg][2 * n3], R3[sg][2 * n3 + 1],
                     dV + ((SIG_V7 + 768) / 16 + 128 * sg - 16 * n3), 1);
    if (gi == 17) dense(36);
    wg_commit();
    if (gi < 16) { wg_wait<1>(); load_group(gi + 2); }
  }
  TSTAMP(ts + 1);
  wg_wait<2>();
  fence_regs<12>(a2); fence_regs<8>(a3);
  bar_sync(barid, 128);
  {
    const uint32_t o2 = y2b + (136 * w + 8 * g + 2 * tq) * 4, o3 = y3b + (272 * w + 16 * g + 2 * tq) * 4;
#pragma unroll
    for (int q = 0; q < 6; q++) sts64f(o2 + (544 * (q >> 1) + 64 * (q & 1)) * 4, a2[2 * q], a2[2 * q + 1]);
#pragma unroll
    for (int q = 0; q < 4; q++) sts64f(o3 + (8 * (q >> 1) + 136 * (q & 1)) * 4, a3[2 * q], a3[2 * q + 1]);
  }
  bar_sync(barid, 128);
  const uint32_t go = (136 * tq + 16 * w + g) * 4;
  float ex[12];
#pragma unroll
  for (int i = 0; i < 12; i++) {
    const int o = 544 * (i >> 2) + 64 * (i & 1) + 8 * ((i >> 1) & 1);
    ex[i] = lds32f(y2b + go + o * 4);
    if (i >= 4) ex[i] += lds32f(y3b + go + (o - 544) * 4);
  }
  wg_wait<0>();
  fence_regs<16>(res);
#pragma unroll
  for (int i = 0; i < 12; i++) res[4 + i] += ex[i];
  TSTAMP(ts + 2);
}

__device__ __forceinline__ void red16x2(float& a, float& c) {
#pragma unroll
  for (int o = 1; o < 16; o <<= 1) { a += __shfl_xor_sync(0xffffffffu, a, o); c += __shfl_xor_sync(0xffffffffu, c, o); }
}
__device__ __forceinline__ void ln_rows(uint32_t* u, int row, uint32_t stg_row, int lane) {
  const int j = lane & 15;
  const float piv = __shfl_sync(0xffffffffu, bf_lo(u[0]), lane & 16);
  float s0 = 0.f, s1 = 0.f, q0 = 0.f, q1 = 0.f;
#pragma unroll
  for (int i = 0; i < 14; i++) {
    const float a = bf_lo(u[i]) - piv, c = bf_hi(u[i]) - piv;
    s0 += a; s1 += c; q0 = fmaf(a, a, q0); q1 = fmaf(c, c, q1);
  }
  float s = s0 + s1, q = q0 + q1;
  red16x2(s, q);
  s *= (1.f / D_); q *= (1.f / D_);
  const __nv_bfloat16 m1b = __float2bfloat16_rn(s + piv);
  const __nv_bfloat162 m1v = __halves2bfloat162(m1b, m1b);
  const float den = rbf(sqrtf_(rbf(rbf(fmaxf(fmaf(-s, s, q), 0.f)) + 1e-5f)));
  const float rden = rcpf_(den);
  s0 = s1 = q0 = q1 = 0.f;
#pragma unroll
  for (int i = 0; i < 14; i++) {
    const __nv_bfloat162 cv = __hsub2(*reinterpret_cast<__nv_bfloat162*>(&u[i]), m1v);
    const uint32_t c = *reinterpret_cast<const uint32_t*>(&cv);
    const uint32_t n = pack_bf2(bf_lo(c) * rden, bf_hi(c) * rden);
    const float a = bf_lo(n), e = bf_hi(n);
    s0 += a; s1 += e; q0 = fmaf(a, a, q0); q1 = fmaf(e, e, q1);
    u[i] = pack_h2(a, e);
  }
#pragma unroll
  for (int i = 0; i < 7; i++)
    asm volatile("st.shared.v2.b32 [%0], {%1,%2};" ::"r"(stg_row + (j + 16 * i) * 8), "r"(u[2 * i]), "r"(u[2 * i + 1]) : "memory");
  s = s0 + s1; q = q0 + q1;
  red16x2(s, q);
  s *= (1.f / D_); q *= (1.f / D_);
  const float den2 = rbf(sqrtf_(rbf(rbf(fmaxf(fmaf(-s, s, q), 0.f)) + 1e-5f)));
  if (j == 0) {
    const float ir = den * den2, mu = fmaf(rbf(s), den, __bfloat162float(m1b));
    const float ih = rbf(ir), mh = rbf(mu);
    const uint32_t mm = pack_bf2(mh, mh);
    g_ax[row] = make_uint4(mm, pack_bf2(mu - mh, ih), mm, pack_bf2(mu - mh, ir - ih));
    g_r[row] = rcpf_(ir);
  }
}

__device__ __forceinline__ void poll_tag(const unsigned* p, uint32_t tag) {
#pragma unroll 1
  for (int it = 0; it < 4096; it++) {
    if (!((ld_relaxed1(p) ^ tag) & 1)) break;
    __nanosleep(32);
  }
}
template <int NV, int STRIDE>
__device__ __forceinline__ void recv_part(const uint4* src, uint32_t tag, float* pre) {
  uint4 v[NV];
#pragma unroll 1
  for (int it = 0; it < RETRY_MAX; it++) {
    uint32_t bad = 0;
#pragma unroll
    for (int q = 0; q < NV; q++) v[q] = ld_b128(src + q * STRIDE);
#pragma unroll
    for (int q = 0; q < NV; q++) bad |= v[q].x ^ tag;
    const unsigned m = __ballot_sync(0xffffffffu, bad & 1);
    if (!m) break;
    if ((threadIdx.x & 31) == __ffs(m) - 1) poll_tag((const unsigned*)(src + (NV - 1) * STRIDE), tag);
    __syncwarp();
  }
#pragma unroll
  for (int q = 0; q < NV; q++) {
    const uint32_t u[4] = {v[q].x, v[q].y, v[q].z, v[q].w};
#pragma unroll
    for (int k = 0; k < 4; k++) { pre[8 * q + 2 * k] += bf_lo(u[k]); pre[8 * q + 2 * k + 1] += bf_hi(u[k]); }
  }
}
__device__ __forceinline__ void send_part(uint4* dst, uint32_t tag, const float* a) {
#pragma unroll
  for (int q = 0; q < 4; q++)
    st_b128(dst + q * 256, tag, pack_bf2(a[8 * q], a[8 * q + 1]), pack_bf2(a[8 * q + 2], a[8 * q + 3]),
            pack_bf2(a[8 * q + 4], a[8 * q + 5]), pack_bf2(a[8 * q + 6], a[8 * q + 7]));
}
__device__ __forceinline__ bool last_release(uint32_t cnt) {
  unsigned old;
  asm volatile("atom.relaxed.cta.shared.inc.u32 %0, [%1], 7;" : "=r"(old) : "r"(cnt) : "memory");
  return old == 7;
}
__device__ __forceinline__ int mod7(int v) { return v >= 7 ? v - 7 : v; }

#define IDS const int tid = opaque(tid0), lane = tid & 31, t = tid & 127, wg = tid >> 7, w = (tid >> 5) & 3; \
            (void)lane; (void)t; (void)wg; (void)w;

__global__ void __launch_bounds__(384, 1)
fused_kernel(const __grid_constant__ CUtensorMap tm_x, const __grid_constant__ CUtensorMap tm_w1,
             const __grid_constant__ CUtensorMap tm_w2, const __grid_constant__ CUtensorMap tm_out, const Params p) {
  const uint32_t sb = smem_u32(smem_raw);
  const uint32_t ms = sb + OFF_M;
  const uint32_t bar0 = ms + M_BAR;
  const int tid0 = threadIdx.x;
  const int b = blockIdx.x;
  const bool is_ssm = b >= NMLP;
  const int G = b / NRK, rk = b - G * NRK;
  const int kc0 = (G + rk) % 7;
  TSINIT();
  TSTAMP(0);
  {
    IDS
    if (wg == 2 && w == 0) {
      if (lane < 16) { mbar_init(bar0 + 8 * lane, 1); asm volatile("st.shared.b32 [%0], 0;" ::"r"(ms + M_REL + 4 * lane) : "memory"); }
      fence_async();
      if (lane < 3 && !is_ssm) {
        const int kc = mod7(kc0 + lane);
        mbar_expect(bar0 + 8 * lane, 49152);
        tma_2d(sb + OFF_X + lane * 16384, &tm_x, 64 * kc, 128 * G, bar0 + 8 * lane);
        tma_3d(sb + OFF_W + lane * 32768, &tm_w1, 0, 64 * kc, 4 * rk, bar0 + 8 * lane);
      }
    }
    TSTAMP(28);
    unsigned ep = 0;
    if (tid == 256 + 32) ep = *(volatile unsigned*)&g_epoch;
    uint4 ld[7];
    const int rl = 2 * (tid >> 5) + (lane >> 4);
    if (wg < 2) {
      const uint2* xr = (const uint2*)(p.x + (size_t)(16 * (b & 127) + rl) * D_) + (lane & 15);
#pragma unroll
      for (int i = 0; i < 7; i++) { const uint2 v = __ldg(xr + 16 * i); ld[i].x = v.x; ld[i].y = v.y; }
    } else {
      const uint4* wr = (const uint4*)(p.w1 + (size_t)(112 * (b & 3) + (t >> 3)) * F_ + 64 * (is_ssm ? 0 : b >> 2)) + (t & 7);
#pragma unroll
      for (int i = 0; i < 7; i++) ld[i] = __ldg(wr + (size_t)i * 16 * (F_ / 8));
    }
    KgIn kin;
    {
      const int d = is_ssm ? 2 * (112 + 3 * (b - NMLP) + wg) + (w >> 1) : (wg < 2 ? 2 * b + wg : 336 + b);
      kgen_load(p, d, is_ssm ? 2 * (w & 1) : w, is_ssm ? 2 : 1, lane, kin);
    }
    const uint32_t tbl = is_ssm ? sb + (4 * wg + (w >> 1)) * TBL : sb + OFF_T + wg * TBL;
#pragma unroll 1
    for (int i = is_ssm ? t & 63 : t; i < TBL_SC / 16; i += is_ssm ? 64 : 128) sts128(tbl + i * 16, 0u, 0u, 0u, 0u);
    const uint32_t lns = is_ssm ? sb + S_WORK + 2 * S_WGB : sb + OFF_B;
    TSTAMP(31);
    if (wg < 2) {
      uint32_t u[14];
#pragma unroll
      for (int i = 0; i < 7; i++) { u[2 * i] = ld[i].x; u[2 * i + 1] = ld[i].y; }
      ln_rows(u, 16 * (b & 127) + rl, lns + ((rl & 1) | ((rl >> 2) << 1) | ((rl & 2) << 2)) * 912, lane);
      bar_arrive(7, 384);
    } else {
      const float b1v = __bfloat162float(p.b1[64 * (is_ssm ? 0 : b >> 2) + (t & 63)]);
      float cs[8];
#pragma unroll
      for (int k = 0; k < 8; k++) cs[k] = 0.f;
#pragma unroll
      for (int i = 0; i < 7; i++) {
        const uint32_t uu[4] = {ld[i].x, ld[i].y, ld[i].z, ld[i].w};
#pragma unroll
        for (int k = 0; k < 4; k++) { cs[2 * k] += bf_lo(uu[k]); cs[2 * k + 1] += bf_hi(uu[k]); }
      }
#pragma unroll
      for (int st = 0; st < 2; st++) {
        const int n = 4 >> st;
        const bool up = (lane >> (4 - st)) & 1;
#pragma unroll
        for (int k = 0; k < n; k++) {
          const float give = up ? cs[k] : cs[k + n], keep = up ? cs[k + n] : cs[k];
          cs[k] = keep + __shfl_xor_sync(0xffffffffu, give, 16 >> st);
        }
      }
      sts64f(ms + M_CSR + (w * 64 + (lane & 7) * 8 + (lane >> 3) * 2) * 4, cs[0], cs[1]);
      if (t == 32) asm volatile("st.shared.b32 [%0], %1;" ::"r"(ms + M_EP), "r"(ep + 1) : "memory");
      bar_sync(7, 384);
      const uint32_t la = lns + (lane & 15) * 912 + (lane >> 4) * 16 + w * 224;
      uint2* dst = (uint2*)(g_xnT + (size_t)(56 * w + (lane >> 3)) * 512 + 4 * b) + (lane & 7);
      uint32_t r[28];
#pragma unroll
      for (int k = 0; k < 7; k++) ldsm4t(la + k * 32, r[4 * k], r[4 * k + 1], r[4 * k + 2], r[4 * k + 3]);
      const uint32_t tag = lds32(ms + M_EP) & 1;
      if (b < 128) {
#pragma unroll
        for (int k = 0; k < 14; k++) st_relaxed2(dst + k * 4096, (r[2 * k] & ~1u) | tag, (r[2 * k + 1] & ~1u) | tag);
      }
      if (t < 64 && !is_ssm) {
        const uint32_t a = ms + M_CSR + t * 4;
        const float c = -((lds32f(a) + lds32f(a + 256)) + (lds32f(a + 512) + lds32f(a + 768)));
        const float ch = rbf(c);
        uint2* dx = (uint2*)(g_bx + (b >> 4) * 512 + ((b >> 1) & 1) * 256 + ((b >> 2) & 3) * 64 + t) + (b & 1);
        *dx = make_uint2(pack_bf2(ch, c - ch), pack_bf2(ch, (b & 2) ? 0.f : b1v));
      }
      bar_sync(6, 128);
    }
    TSTAMP(29);
    const uint32_t stg = is_ssm ? sb + S_WORK + wg * S_WGB + w * KSTG : sb + (wg < 2 ? OFF_A + 4 * wg * KSTG : OFF_B) + w * KSTG;
    kgen_warp(kin, is_ssm ? 2 : 1, stg, tbl, lane);
  }
  TSTAMP(1);
  __syncthreads();

  if (is_ssm || __shfl_sync(0xffffffffu, tid0 >> 7, 0) == 2) {
    asm volatile("setmaxnreg.dec.sync.aligned.u32 136;");
    {
      IDS
      if (tid == 256 + 96) red_release(&g_cntA);
      if (t == 0 && !is_ssm)
        asm volatile("cp.async.bulk.prefetch.L2.global [%0], %1;" ::"l"(p.w2 + (size_t)(256 * rk + 16 * G) * D_), "r"(16 * D_ * 2) : "memory");
#pragma unroll 1
      for (int c = is_ssm ? 1 : 2; c >= 0; c--) {
        const uint32_t src = is_ssm ? sb + S_WORK + wg * S_WGB + 2 * c * KSTG : sb + (c < 2 ? OFF_A + 4 * c * KSTG : OFF_B);
        ktab_build(src, !is_ssm, w, (is_ssm ? sb + 4 * wg * TBL : sb + OFF_T) + c * TBL, lane);
        if (c == 2) {
          fence_async();
          bar_sync(6, 128);
          if (t == 96) { bulk_s2g(g_tbl + b * (TBL / 16), sb + OFF_T + 2 * TBL, TBL); bulk_commit(); }
        }
      }
      if (t == 96 && !is_ssm) {
        const unsigned ep1 = lds32(ms + M_EP);
        wait_count(&g_cntA, ep1 * NCTA);
        if (b == 0) *(volatile unsigned*)&g_epoch = ep1;
        asm volatile("fence.proxy.async;" ::: "memory");
        mbar_expect(bar0 + 8 * 15, 2048 + 8192 + 512);
        bulk_g2s(sb + OFF_B + B_AX, g_ax + 128 * G, 2048, bar0 + 8 * 15);
        bulk_g2s(sb + OFF_B + B_BX, g_bx + 512 * rk, 8192, bar0 + 8 * 15);
        bulk_g2s(sb + OFF_B + B_R, g_r + 128 * G, 512, bar0 + 8 * 15);
        bulk_wait0();
        red_release(&g_cntT);
      }
      bar_sync(4 + wg, 128);
    }
    TSTAMP(3);
#pragma unroll 1
    for (int pi = 0; pi < 2; pi++) {
      {
        IDS
        if (pi == 1 && (!is_ssm || (b >= NMLP + 12 && wg == 2))) break;
        const unsigned ep1 = lds32(ms + M_EP);
        const int pair = !is_ssm ? b : (pi == 0 ? 112 + 3 * (b - NMLP) : (b < NMLP + 12 ? 172 + 3 * (b - NMLP) : 184 + 2 * (b - NMLP))) + wg;
        const uint32_t work = is_ssm ? sb + S_WORK + wg * S_WGB : sb + OFF_A;
        if (pi == 1 && t == 96) {
          wait_count(&g_cntT, ep1 * NMLP);
          asm volatile("fence.proxy.async;" ::: "memory");
          mbar_expect(bar0 + 8 * wg, 2 * TBL);
          bulk_g2s(sb + (4 * wg + 2) * TBL, g_tbl + (2 * pair - 336) * (TBL / 16), 2 * TBL, bar0 + 8 * wg);
        }
        const uint32_t z = work + SIG_V3 - 1024 + (t >> 6) * 4096 + (t & 63) * 16;
        sts128(z, 0u, 0u, 0u, 0u); sts128(z + SIG, 0u, 0u, 0u, 0u);
        if (t < 72) {
          const uint32_t zu = work + SIG_U + (t & 7) * U_LBO + (t >> 3) * 16;
          sts128(zu, 0u, 0u, 0u, 0u); sts128(zu + SIG, 0u, 0u, 0u, 0u);
        }
        const uint4* src = g_xnT + (size_t)pair * 512 + t;
        uint4 v[4];
#pragma unroll 1
        for (int it = 0; it < RETRY_MAX; it++) {
#pragma unroll
          for (int q = 0; q < 4; q++) v[q] = ld_relaxed4(src + q * 128);
          uint32_t bad = 0;
#pragma unroll
          for (int q = 0; q < 4; q++) bad |= (((v[q].x ^ ep1) | (v[q].y ^ ep1) | (v[q].z ^ ep1) | (v[q].w ^ ep1)) & 1) << q;
          const unsigned m = __ballot_sync(0xffffffffu, bad);
          if (!m) break;
          if (lane == __ffs(m) - 1) poll_tag((const unsigned*)(src + (__ffs(bad) - 1) * 128) + 3, ep1);
          __syncwarp();
        }
        TSTAMP(5);
        const uint32_t a = work + ((t >> 1) & 1) * SIG + SIG_U + (2 * ((t >> 2) & 3) + (t & 1)) * U_LBO + ((t >> 4) + 9) * 16;
#pragma unroll
        for (int q = 0; q < 4; q++) sts128(a + q * 128, v[q].x & ~1u, v[q].y & ~1u, v[q].z & ~1u, v[q].w & ~1u);
        bar_sync(4 + wg, 128);
#pragma unroll 1
        for (int k = w; k < 6; k += 4) sig_windows(work + (k & 1) * SIG, (k >> 1) * 32 + lane);
        fence_async();
        if (pi == 1) mbar_wait(bar0 + 8 * wg, 0);
        TSTAMP(6);
        bar_sync(4 + wg, 128);
        TSTAMP(7);
      }
      uint32_t keep[8];
      float res[16];
#pragma unroll 1
      for (int c = 0; c < 2; c++) {
        IDS
        const int wgu = __shfl_sync(0xffffffffu, wg, 0);
        const uint32_t work = is_ssm ? sb + S_WORK + wgu * S_WGB : sb + OFF_A;
        const uint32_t tbl = (is_ssm ? sb + (4 * wgu + 2 * pi) * TBL : sb + OFF_T) + c * TBL;
        conv_channel(tbl, work + c * SIG, is_ssm ? work + 2 * SIG + Y3B : sb + OFF_B, work + 2 * SIG, lds32f(tbl + TBL_SC), w, lane, 4 + wgu, res, 16 + 3 * (2 * pi + c));
        const float os = lds32f(tbl + TBL_SC + 4);
        if (c == 0) {
#pragma unroll
          for (int i = 0; i < 8; i++) keep[i] = pack_bf2(res[2 * i] * os, res[2 * i + 1] * os);
        } else {
          const int pair = !is_ssm ? b : (pi == 0 ? 112 + 3 * (b - NMLP) : (b < NMLP + 12 ? 172 + 3 * (b - NMLP) : 184 + 2 * (b - NMLP))) + wg;
          uint4* dst = g_s2 + ((size_t)(lane & 3) * 224 + pair) * 32 + w * 8 + (lane >> 2);
          const uint32_t tag = lds32(ms + M_EP) & 1;
#pragma unroll
          for (int nt = 0; nt < 4; nt++) {
            const uint32_t n0 = pack_bf2(res[4 * nt] * os, res[4 * nt + 1] * os), n1 = pack_bf2(res[4 * nt + 2] * os, res[4 * nt + 3] * os);
            st_b128(dst + nt * 4 * 224 * 32, tag, __byte_perm(keep[2 * nt], n0, 0x5410), __byte_perm(keep[2 * nt + 1], n1, 0x5410),
                    __byte_perm(keep[2 * nt], n0, 0x7632), __byte_perm(keep[2 * nt + 1], n1, 0x7632));
          }
        }
      }
      TSTAMP(8 + pi);
    }
    if (!is_ssm) {
      IDS
      const uint32_t tag = lds32(ms + M_EP) & 1;
      float pre[64];
#pragma unroll
      for (int i = 0; i < 64; i++) pre[i] = 0.f;
#pragma unroll 1
      for (int s = 0; s < 4; s++) recv_part<8, 128>(g_part + ((size_t)b * 6 + s) * 1024 + t, tag, pre);
      bar_sync(6, 128);
#pragma unroll
      for (int i = 0; i < 16; i++)
        sts128(sb + OFF_A + ((2 * (i >> 2) + (i & 1)) * 256 + ((i >> 1) & 1) * 128 + t) * 16, __float_as_uint(pre[4 * i]),
               __float_as_uint(pre[4 * i + 1]), __float_as_uint(pre[4 * i + 2]), __float_as_uint(pre[4 * i + 3]));
      bar_arrive(2, 384);
      TSTAMP(12);
    }
    TSDUMP();
  } else {
    bar_arrive(1, 384);
    asm volatile("setmaxnreg.inc.sync.aligned.u32 192;");
    bar_sync(7, 384);
    uint32_t H[64];
    {
      float acc[128];
      float p0, q0, p1, q1;
      {
        IDS
        const int wgu = __shfl_sync(0xffffffffu, wg, 0);
        int sl = 0;
#pragma unroll 1
        for (int s = 0; s < 7; s++) {
          mbar_wait(bar0 + 8 * s, 0);
          const uint64_t da = mkdesc(sb + OFF_X + sl * 16384 + wgu * 8192, 16, 1024, 1);
          const uint64_t db = mkdesc(sb + OFF_W + sl * 32768, 8192, 1024, 1);
          wg_fence();
#pragma unroll
          for (int k = 0; k < 4; k++) wg_ss_bf16_n256(acc, da + 2 * k, db + 128 * k, (s | k) != 0);
          wg_commit();
          wg_wait<1>();
          const int pl = sl == 0 ? 2 : sl - 1;
          sl = sl == 2 ? 0 : sl + 1;
          if (s > 0 && lane == 0 && last_release(ms + M_REL + 4 * s)) {
            const uint32_t bx = bar0 + 8 * (s < 5 ? s + 2 : 14);
            mbar_expect(bar0 + 8 * (s + 2), s < 5 ? 49152 : 32768);
            if (s < 5) tma_3d(sb + OFF_W + pl * 32768, &tm_w1, 0, 64 * mod7(kc0 + s + 2), 4 * rk, bar0 + 8 * (s + 2));
            else tma_2d(sb + OFF_W + pl * 32768, &tm_w2, 64 * mod7(rk + s - 4), 256 * rk, bar0 + 8 * (s + 2));
            if (s == 6) mbar_expect(bx, 16384);
            if (s != 5) tma_2d(sb + OFF_X + pl * 16384, &tm_x, 64 * (s < 5 ? mod7(kc0 + s + 2) : rk), 128 * G, bx);
          }
        }
        TSTAMP(9);
        mbar_wait(bar0 + 8 * 15, 0);
        wg_fence();
        wg_ss_bf16_n256k(acc, mkdesc(sb + OFF_B + B_AX + wgu * 1024, 0, 128, 0), mkdesc(sb + OFF_B + B_BX, 4096, 128, 0), 1);
        wg_commit();
        wg_wait<1>();
        if (lane == 0 && last_release(ms + M_REL + 4 * 7)) {
#pragma unroll 1
          for (int c = 2; c < 4; c++) {
            mbar_expect(bar0 + 8 * (7 + c), 32768);
            tma_2d(sb + (c - 2) * OFF_X, &tm_w2, 64 * mod7(rk + 1 + c), 256 * rk, bar0 + 8 * (7 + c));
          }
        }
        const float r0 = lds32f(sb + OFF_B + B_R + (16 * (tid >> 5) + (lane >> 2)) * 4);
        const float r1 = lds32f(sb + OFF_B + B_R + (16 * (tid >> 5) + (lane >> 2) + 8) * 4);
        p0 = 0.7978845608028654f * r0; q0 = 0.0356774081363001f * r0 * r0 * r0;
        p1 = 0.7978845608028654f * r1; q1 = 0.0356774081363001f * r1 * r1 * r1;
      }
      wg_wait<0>();
      fence_regs<128>(acc);
      TSTAMP(2);
      float hq[4];
#pragma unroll
      for (int i = 0; i < 64; i++) {
        const float pp = (i & 1) ? p1 : p0, qq = (i & 1) ? q1 : q0;
        const float a = acc[2 * i], c = acc[2 * i + 1];
        const float ta = tanhf_(a * fmaf(a * a, qq, pp)), tc = tanhf_(c * fmaf(c * c, qq, pp));
        if (i >= 2) H[i - 2] = pack_bf2v(hq[(i & 1) * 2], hq[(i & 1) * 2 + 1]);
        hq[(i & 1) * 2] = fmaf(a, ta, a); hq[(i & 1) * 2 + 1] = fmaf(c, tc, c);
      }
      H[62] = pack_bf2v(hq[0], hq[1]); H[63] = pack_bf2v(hq[2], hq[3]);
    }
    TSTAMP(3);
    float accA[32], accB[32];
    const uint32_t tag = lds32(ms + M_EP) & 1;
    auto issue2 = [&](int c, float* acc) {
      const uint32_t base = sb + ((0x0213021u >> (4 * c)) & 3) * 32768;
      mbar_wait(bar0 + 8 * (7 + c), 0);
      const uint64_t db = mkdesc(base, 8192, 1024, 1);
      wg_fence();
#pragma unroll
      for (int k = 0; k < 16; k++) wg_rs_bf16_n64(acc, H[4 * k], H[4 * k + 1], H[4 * k + 2], H[4 * k + 3], db + 128 * k, k != 0);
      wg_commit();
    };
    auto process = [&](int s, float* acc) {
      wg_wait<1>();
      fence_regs<32>(acc);
      const int tid = opaque(tid0);
      if (s < 3 && (tid & 31) == 0 && last_release(ms + M_REL + 4 * (8 + s))) {
        mbar_expect(bar0 + 8 * (11 + s), 32768);
        tma_2d(sb + ((0x021u >> (4 * s)) & 3) * 32768, &tm_w2, 64 * mod7(mod7(rk + 5 + s)), 256 * rk, bar0 + 8 * (11 + s));
      }
      send_part(g_part + ((size_t)(G * 7 + mod7(rk + 1 + s)) * 6 + s) * 1024 + tid, tag, acc);
      TSTAMP(10 + s);
    };
    issue2(0, accA);
#pragma unroll
    for (int s = 0; s < 6; s += 2) {
      issue2(s + 1, accB);
      process(s, accA);
      issue2(s + 2, accA);
      process(s + 1, accB);
    }
    TSTAMP(4);
    IDS
    const int g = lane >> 2, tq = lane & 3;
    uint32_t sw[16];
    {
      const uint4* sp = g_s2 + ((size_t)G * 224 + 32 * rk + tq) * 32 + w * 8 + g;
#pragma unroll 1
      for (int it = 0; it < RETRY_MAX; it++) {
        uint32_t bad = 0;
#pragma unroll
        for (int i = 0; i < 8; i++) {
          const uint4 v = ld_b128(sp + i * 4 * 32);
          bad |= ((v.x ^ tag) & 1) << i;
          sw[2 * i] = wg ? v.z : v.x; sw[2 * i + 1] = wg ? v.w : v.y;
        }
        const unsigned m = __ballot_sync(0xffffffffu, bad);
        if (!m) break;
        if (lane == __ffs(m) - 1) poll_tag((const unsigned*)(sp + (__ffs(bad) - 1) * 4 * 32), tag);
        __syncwarp();
      }
    }
    TSTAMP(5);
    uint32_t b2w[8];
#pragma unroll
    for (int i = 0; i < 8; i++) b2w[i] = __ldg((const uint32_t*)(p.b2 + 64 * rk) + 4 * i + tq);
    wg_wait<0>();
    fence_regs<32>(accA);
    TSTAMP(6);
    bar_sync(2, 384);
#pragma unroll
    for (int i = 0; i < 8; i++) {
      const uint4 v = lds128(sb + OFF_A + (i * 256 + tid) * 16);
      accA[4 * i] += __uint_as_float(v.x); accA[4 * i + 1] += __uint_as_float(v.y);
      accA[4 * i + 2] += __uint_as_float(v.z); accA[4 * i + 3] += __uint_as_float(v.w);
    }
    mbar_wait(bar0 + 8 * 14, 0);
    const uint32_t xa = sb + OFF_X + 2 * 16384 + (16 * (tid >> 5) + (lane & 15)) * 128;
    uint32_t xw[16];
#pragma unroll
    for (int q = 0; q < 4; q++) ldsm4(xa + (((2 * q + (lane >> 4)) ^ (lane & 7)) << 4), xw[4 * q], xw[4 * q + 1], xw[4 * q + 2], xw[4 * q + 3]);
    const float r0 = 0.5f * lds32f(sb + OFF_B + B_R + (16 * (tid >> 5) + g) * 4);
    const float r1 = 0.5f * lds32f(sb + OFF_B + B_R + (16 * (tid >> 5) + g + 8) * 4);
#pragma unroll 1
    for (int s = 4; s < 6; s++) recv_part<4, 256>(g_part + ((size_t)b * 6 + s) * 1024 + tid, tag, accA);
    TSTAMP(7);
#pragma unroll
    for (int k = 0; k < 16; k++) {
      const float rr = (k & 1) ? r1 : r0;
      const float o0 = fmaf(accA[2 * k], rr, bf_lo(b2w[k >> 1])), o1 = fmaf(accA[2 * k + 1], rr, bf_hi(b2w[k >> 1]));
      const float g0 = o0 * rcpf_(1.f + ex2f(o0 * -1.4426950408889634f)), g1 = o1 * rcpf_(1.f + ex2f(o1 * -1.4426950408889634f));
      xw[k] = pack_bf2(fmaf(bf_lo(sw[k]), g0, bf_lo(xw[k])), fmaf(bf_hi(sw[k]), g1, bf_hi(xw[k])));
    }
#pragma unroll
    for (int q = 0; q < 4; q++) stsm4(xa + (((2 * q + (lane >> 4)) ^ (lane & 7)) << 4), xw[4 * q], xw[4 * q + 1], xw[4 * q + 2], xw[4 * q + 3]);
    fence_async();
    __syncwarp();
    if (lane == 0) {
      tma_store_2d(&tm_out, sb + OFF_X + 2 * 16384 + (tid >> 5) * 2048, 64 * rk, 128 * G + 16 * (tid >> 5));
      bulk_commit();
      bulk_wait0_read();
    }
    TSTAMP(8);
    TSDUMP();
  }
}

typedef CUresult (*EncodeFn)(CUtensorMap*, CUtensorMapDataType, cuuint32_t, void*, const cuuint64_t*, const cuuint64_t*,
                             const cuuint32_t*, const cuuint32_t*, CUtensorMapInterleave, CUtensorMapSwizzle,
                             CUtensorMapL2promotion, CUtensorMapFloatOOBfill);

void make_map(EncodeFn fn, CUtensorMap* m, const void* ptr, int rank, const cuuint64_t* dims, const cuuint64_t* strides, const cuuint32_t* box) {
  const cuuint32_t es[3] = {1, 1, 1};
  fn(m, CU_TENSOR_MAP_DATA_TYPE_BFLOAT16, rank, const_cast<void*>(ptr), dims, strides, box, es, CU_TENSOR_MAP_INTERLEAVE_NONE,
     CU_TENSOR_MAP_SWIZZLE_128B, CU_TENSOR_MAP_L2_PROMOTION_L2_128B, CU_TENSOR_MAP_FLOAT_OOB_FILL_NONE);
}

}

extern "C" void kernel_launch(void* const* d_in, const int* in_sizes, int n_in, void* d_out, int out_size) {
  (void)in_sizes; (void)n_in; (void)out_size;
  void* fnp = nullptr;
  cudaDriverEntryPointQueryResult qr;
  cudaGetDriverEntryPoint("cuTensorMapEncodeTiled", &fnp, cudaEnableDefault, &qr);
  EncodeFn fn = (EncodeFn)fnp;
  Params p;
  p.x = (const __nv_bfloat16*)d_in[0];
  p.a_re = (const __nv_bfloat16*)d_in[1]; p.a_im = (const __nv_bfloat16*)d_in[2];
  p.b_re = (const __nv_bfloat16*)d_in[3]; p.b_im = (const __nv_bfloat16*)d_in[4];
  p.c_re = (const __nv_bfloat16*)d_in[5]; p.c_im = (const __nv_bfloat16*)d_in[6];
  p.log_dt = (const __nv_bfloat16*)d_in[7]; p.dskip = (const __nv_bfloat16*)d_in[8];
  p.w1 = (const __nv_bfloat16*)d_in[10]; p.b1 = (const __nv_bfloat16*)d_in[11];
  p.w2 = (const __nv_bfloat16*)d_in[12]; p.b2 = (const __nv_bfloat16*)d_in[13];
  CUtensorMap mx, mw1, mw2, mo;
  {
    const cuuint64_t dims[2] = {448, 2048}, str[1] = {896};
    const cuuint32_t box[2] = {64, 128}, boxo[2] = {64, 16};
    make_map(fn, &mx, p.x, 2, dims, str, box);
    make_map(fn, &mo, d_out, 2, dims, str, boxo);
  }
  {
    const cuuint64_t dims[3] = {64, 448, 28}, str[2] = {3584, 128};
    const cuuint32_t box[3] = {64, 64, 4};
    make_map(fn, &mw1, p.w1, 3, dims, str, box);
  }
  {
    const cuuint64_t dims[2] = {448, 1792}, str[1] = {896};
    const cuuint32_t box[2] = {64, 256};
    make_map(fn, &mw2, p.w2, 2, dims, str, box);
  }
  cudaFuncSetAttribute(fused_kernel, cudaFuncAttributeMaxDynamicSharedMemorySize, SMEM_BYTES);
  fused_kernel<<<NCTA, 384, SMEM_BYTES>>>(mx, mw1, mw2, mo, p);
}
```

```cpp
#include <cuda_runtime.h>
#include <cuda_bf16.h>
#include <cuda_fp16.h>
#include <cuda.h>
#include <stdint.h>

namespace {

constexpr int D_ = 448, NST = 256, F_ = 1792;
constexpr int NRK = 7, NMLP = 112, NCTA = 132;
constexpr int SPIN_MAX = 1 << 20, RETRY_MAX = 512;

struct Scratch {
  unsigned cntA, pad0[31], cntT, pad1[31], epoch, pad2[63];
  float r[2048];
  uint4 ax[2048];
  uint4 bx[7 * 512];
  uint4 tbl[112 * 329];
  uint4 xnT[224 * 512];
  uint4 s2[16 * 224 * 32];
  uint4 part[16 * 7 * 6 * 1024];
};
__device__ Scratch g_scr;
#define TSTAMP(i)
#define TSINIT()
#define TSDUMP()
extern __shared__ __align__(1024) uint8_t smem_raw[];

constexpr int TBL_SC = 5248, TBL = 5264;
constexpr int TBL_C1 = 2624;
constexpr int SIG = 19584;
constexpr int SIG_U = 0, U_LBO = 656, SIG_V3 = 6272, SIG_V5 = 10368, SIG_V7 = 13440, SIG_V9 = 15488, SIG_V2 = 17536;
constexpr int Y2B = 6528, Y3B = 4352;
constexpr int KREC = 160, KSTG = 32 * KREC;
constexpr int OFF_W = 0, OFF_X = 98304, OFF_A = 147456, OFF_B = OFF_A + 8 * KSTG + 2560, OFF_T = OFF_B + 4 * KSTG;
constexpr int OFF_M = OFF_T + 15872;
constexpr int B_AX = Y2B, B_BX = B_AX + 2048, B_R = B_BX + 8192;
constexpr int M_BAR = 0, M_REL = 128, M_EP = 192, M_CSR = 256, M_END = 1280;
constexpr int SMEM_BYTES = OFF_M + M_END + 384;
constexpr int S_WORK = 63232, S_WGB = 2 * SIG + Y2B + Y3B;
static_assert(S_WORK + 3 * S_WGB <= OFF_M && SMEM_BYTES <= 232448, "smem");

struct Params {
  const __nv_bfloat16 *x, *a_re, *a_im, *b_re, *b_im, *c_re, *c_im, *log_dt, *dskip, *w1, *b1, *w2, *b2;
  Scratch* s;
};

__device__ __forceinline__ int opaque(int x) { int v; asm volatile("mov.u32 %0, %1;" : "=r"(v) : "r"(x)); return v; }
__device__ __forceinline__ int rd_bid() { int v; asm volatile("mov.u32 %0, %%ctaid.x;" : "=r"(v)); return v; }
__device__ __forceinline__ uint32_t smem_u32(const void* p) { return (uint32_t)__cvta_generic_to_shared(p); }
__device__ __forceinline__ void mbar_init(uint32_t bar, int cnt) { asm volatile("mbarrier.init.shared::cta.b64 [%0], %1;" ::"r"(bar), "r"(cnt)); }
__device__ __forceinline__ void mbar_expect(uint32_t bar, uint32_t bytes) {
  asm volatile("mbarrier.arrive.expect_tx.shared::cta.b64 _, [%0], %1;" ::"r"(bar), "r"(bytes) : "memory");
}
__device__ __forceinline__ void mbar_wait(uint32_t bar, uint32_t parity) {
  uint32_t done = 0;
#pragma unroll 1
  for (int it = 0; it < SPIN_MAX; it++) {
    asm volatile("{.reg .pred p; mbarrier.try_wait.parity.shared::cta.b64 p, [%1], %2; selp.u32 %0,1,0,p;}"
                 : "=r"(done) : "r"(bar), "r"(parity) : "memory");
    if (done) break;
  }
}
__device__ __forceinline__ void tma_2d(uint32_t dst, const CUtensorMap* m, int c0, int c1, uint32_t bar) {
  asm volatile("cp.async.bulk.tensor.2d.shared::cluster.global.mbarrier::complete_tx::bytes [%0], [%1, {%3, %4}], [%2];"
               ::"r"(dst), "l"(m), "r"(bar), "r"(c0), "r"(c1) : "memory");
}
__device__ __forceinline__ void tma_3d(uint32_t dst, const CUtensorMap* m, int c0, int c1, int c2, uint32_t bar) {
  asm volatile("cp.async.bulk.tensor.3d.shared::cluster.global.mbarrier::complete_tx::bytes [%0], [%1, {%3, %4, %5}], [%2];"
               ::"r"(dst), "l"(m), "r"(bar), "r"(c0), "r"(c1), "r"(c2) : "memory");
}
__device__ __forceinline__ void tma_store_2d(const CUtensorMap* m, uint32_t src, int c0, int c1) {
  asm volatile("cp.async.bulk.tensor.2d.global.shared::cta.bulk_group [%0, {%2, %3}], [%1];"
               ::"l"(m), "r"(src), "r"(c0), "r"(c1) : "memory");
}
__device__ __forceinline__ void bulk_s2g(void* dst, uint32_t src, uint32_t bytes) {
  asm volatile("cp.async.bulk.global.shared::cta.bulk_group [%0], [%1], %2;" ::"l"(dst), "r"(src), "r"(bytes) : "memory");
}
__device__ __forceinline__ void bulk_g2s(uint32_t dst, const void* src, uint32_t bytes, uint32_t bar) {
  asm volatile("cp.async.bulk.shared::cluster.global.mbarrier::complete_tx::bytes [%0], [%1], %2, [%3];"
               ::"r"(dst), "l"(src), "r"(bytes), "r"(bar) : "memory");
}
__device__ __forceinline__ void bulk_commit() { asm volatile("cp.async.bulk.commit_group;" ::: "memory"); }
__device__ __forceinline__ void bulk_wait0() { asm volatile("cp.async.bulk.wait_group 0;" ::: "memory"); }
__device__ __forceinline__ void bulk_wait0_read() { asm volatile("cp.async.bulk.wait_group.read 0;" ::: "memory"); }
__device__ __forceinline__ void fence_async() { asm volatile("fence.proxy.async.shared::cta;" ::: "memory"); }
__device__ __forceinline__ void bar_sync(int id, int n) { asm volatile("bar.sync %0, %1;" ::"r"(id), "r"(n) : "memory"); }
__device__ __forceinline__ void bar_arrive(int id, int n) { asm volatile("bar.arrive %0, %1;" ::"r"(id), "r"(n) : "memory"); }
__device__ __forceinline__ void wg_fence() { asm volatile("wgmma.fence.sync.aligned;" ::: "memory"); }
__device__ __forceinline__ void wg_commit() { asm volatile("wgmma.commit_group.sync.aligned;" ::: "memory"); }
template <int N> __device__ __forceinline__ void wg_wait() { asm volatile("wgmma.wait_group.sync.aligned %0;" ::"n"(N) : "memory"); }
template <int N> __device__ __forceinline__ void fence_regs(float* d) {
#pragma unroll
  for (int i = 0; i < N; i++) asm volatile("" : "+f"(d[i])::"memory");
}
__device__ __forceinline__ uint64_t mkdesc(uint32_t addr, uint32_t lbo, uint32_t sbo, uint32_t sw) {
  return (uint64_t)((addr & 0x3FFFF) >> 4) | ((uint64_t)(lbo >> 4) << 16) | ((uint64_t)(sbo >> 4) << 32) | ((uint64_t)sw << 62);
}
__device__ __forceinline__ uint32_t lds32(uint32_t a) { uint32_t v; asm volatile("ld.shared.b32 %0, [%1];" : "=r"(v) : "r"(a) : "memory"); return v; }
__device__ __forceinline__ float lds32f(uint32_t a) { float v; asm volatile("ld.shared.f32 %0, [%1];" : "=f"(v) : "r"(a) : "memory"); return v; }
__device__ __forceinline__ float2 lds64f(uint32_t a) { float2 v; asm volatile("ld.shared.v2.f32 {%0,%1}, [%2];" : "=f"(v.x), "=f"(v.y) : "r"(a) : "memory"); return v; }
__device__ __forceinline__ uint4 lds128(uint32_t a) {
  uint4 v; asm volatile("ld.shared.v4.b32 {%0,%1,%2,%3}, [%4];" : "=r"(v.x), "=r"(v.y), "=r"(v.z), "=r"(v.w) : "r"(a) : "memory"); return v;
}
__device__ __forceinline__ void sts16(uint32_t a, uint16_t v) { asm volatile("st.shared.b16 [%0], %1;" ::"r"(a), "h"(v) : "memory"); }
__device__ __forceinline__ void sts32f(uint32_t a, float v) { asm volatile("st.shared.f32 [%0], %1;" ::"r"(a), "f"(v) : "memory"); }
__device__ __forceinline__ void sts64f(uint32_t a, float x, float y) { asm volatile("st.shared.v2.f32 [%0], {%1,%2};" ::"r"(a), "f"(x), "f"(y) : "memory"); }
__device__ __forceinline__ void sts128(uint32_t a, uint32_t x, uint32_t y, uint32_t z, uint32_t w) {
  asm volatile("st.shared.v4.b32 [%0], {%1,%2,%3,%4};" ::"r"(a), "r"(x), "r"(y), "r"(z), "r"(w) : "memory");
}
__device__ __forceinline__ void ldsm4(uint32_t a, uint32_t& r0, uint32_t& r1, uint32_t& r2, uint32_t& r3) {
  asm volatile("ldmatrix.sync.aligned.m8n8.x4.shared.b16 {%0,%1,%2,%3}, [%4];" : "=r"(r0), "=r"(r1), "=r"(r2), "=r"(r3) : "r"(a) : "memory");
}
__device__ __forceinline__ void ldsm4t(uint32_t a, uint32_t& r0, uint32_t& r1, uint32_t& r2, uint32_t& r3) {
  asm volatile("ldmatrix.sync.aligned.m8n8.x4.trans.shared.b16 {%0,%1,%2,%3}, [%4];" : "=r"(r0), "=r"(r1), "=r"(r2), "=r"(r3) : "r"(a) : "memory");
}
__device__ __forceinline__ void ldsm2t(uint32_t a, uint32_t& r0, uint32_t& r1) {
  asm volatile("ldmatrix.sync.aligned.m8n8.x2.trans.shared.b16 {%0,%1}, [%2];" : "=r"(r0), "=r"(r1) : "r"(a) : "memory");
}
__device__ __forceinline__ void stsm4(uint32_t a, uint32_t r0, uint32_t r1, uint32_t r2, uint32_t r3) {
  asm volatile("stmatrix.sync.aligned.m8n8.x4.shared.b16 [%0], {%1,%2,%3,%4};" ::"r"(a), "r"(r0), "r"(r1), "r"(r2), "r"(r3) : "memory");
}
__device__ __forceinline__ void mma_f16(float* c, uint32_t a0, uint32_t a1, uint32_t a2, uint32_t a3, uint32_t b0, uint32_t b1) {
  asm("mma.sync.aligned.m16n8k16.row.col.f32.f16.f16.f32 {%0,%1,%2,%3},{%4,%5,%6,%7},{%8,%9},{%0,%1,%2,%3};"
               : "+f"(c[0]), "+f"(c[1]), "+f"(c[2]), "+f"(c[3]) : "r"(a0), "r"(a1), "r"(a2), "r"(a3), "r"(b0), "r"(b1));
}
__device__ __forceinline__ uint4 ld_relaxed4(const void* p) {
  uint4 v; asm volatile("ld.relaxed.gpu.global.v4.b32 {%0,%1,%2,%3}, [%4];" : "=r"(v.x), "=r"(v.y), "=r"(v.z), "=r"(v.w) : "l"(p) : "memory"); return v;
}
__device__ __forceinline__ void st_relaxed2(void* p, uint32_t x, uint32_t y) {
  asm volatile("st.relaxed.gpu.global.v2.b32 [%0], {%1,%2};" ::"l"(p), "r"(x), "r"(y) : "memory");
}
__device__ __forceinline__ uint4 ld_b128(const void* p) {
  uint4 v;
  asm volatile("{.reg .b128 t; .reg .b64 a, c; ld.relaxed.gpu.global.b128 t, [%4]; mov.b128 {a, c}, t; mov.b64 {%0,%1}, a; mov.b64 {%2,%3}, c;}"
               : "=r"(v.x), "=r"(v.y), "=r"(v.z), "=r"(v.w) : "l"(p) : "memory");
  return v;
}
__device__ __forceinline__ void st_b128(void* p, uint32_t tag, uint32_t x, uint32_t y, uint32_t z, uint32_t w) {
  asm volatile("{.reg .b128 t; .reg .b64 a, c; mov.b64 a, {%1,%2}; mov.b64 c, {%3,%4}; mov.b128 t, {a, c}; st.relaxed.gpu.global.b128 [%0], t;}"
               ::"l"(p), "r"((x & ~1u) | tag), "r"(y), "r"(z), "r"(w) : "memory");
}
__device__ __forceinline__ unsigned ld_relaxed1(const unsigned* p) {
  unsigned v; asm volatile("ld.relaxed.gpu.global.u32 %0, [%1];" : "=r"(v) : "l"(p) : "memory"); return v;
}
__device__ __forceinline__ void red_release(unsigned* p) {
  asm volatile("red.release.gpu.global.add.u32 [%0], 1;" ::"l"(p) : "memory");
}
__device__ __forceinline__ void wait_count(const unsigned* p, unsigned target) {
#pragma unroll 1
  for (int it = 0; it < SPIN_MAX; it++) {
    if ((int)(ld_relaxed1(p) - target) >= 0) break;
    __nanosleep(40);
  }
  asm volatile("fence.acq_rel.gpu;" ::: "memory");
}
__device__ __forceinline__ uint32_t pack_h2(float lo, float hi) { uint32_t r; asm("cvt.rn.f16x2.f32 %0, %1, %2;" : "=r"(r) : "f"(hi), "f"(lo)); return r; }
__device__ __forceinline__ uint32_t pack_bf2(float lo, float hi) { uint32_t r; asm("cvt.rn.bf16x2.f32 %0, %1, %2;" : "=r"(r) : "f"(hi), "f"(lo)); return r; }
__device__ __forceinline__ uint32_t pack_bf2v(float lo, float hi) { uint32_t r; asm volatile("cvt.rn.bf16x2.f32 %0, %1, %2;" : "=r"(r) : "f"(hi), "f"(lo)); return r; }
__device__ __forceinline__ float bf_lo(uint32_t w) { return __uint_as_float(w << 16); }
__device__ __forceinline__ float bf_hi(uint32_t w) { return __uint_as_float(w & 0xffff0000u); }
__device__ __forceinline__ float rbf(float v) { return __bfloat162float(__float2bfloat16_rn(v)); }
__device__ __forceinline__ float2 h2f(uint32_t w) { return __half22float2(*reinterpret_cast<__half2*>(&w)); }
__device__ __forceinline__ float ex2f(float v) { float r; asm("ex2.approx.ftz.f32 %0, %1;" : "=f"(r) : "f"(v)); return r; }
__device__ __forceinline__ float rcpf_(float v) { float r; asm("rcp.approx.f32 %0, %1;" : "=f"(r) : "f"(v)); return r; }
__device__ __forceinline__ float sqrtf_(float v) { float r; asm("sqrt.approx.f32 %0, %1;" : "=f"(r) : "f"(v)); return r; }
__device__ __forceinline__ float tanhf_(float v) { float r; asm volatile("tanh.approx.f32 %0, %1;" : "=f"(r) : "f"(v)); return r; }

__device__ __forceinline__ void wg_ss_bf16_n256(float* d, uint64_t da, uint64_t db, int sc) {
  asm volatile("{.reg .pred p; setp.ne.b32 p, %130, 0;\n"
    "wgmma.mma_async.sync.aligned.m64n256k16.f32.bf16.bf16 {%0, %1, %2, %3, %4, %5, %6, %7, %8, %9, %10, %11, %12, %13, %14, %15, %16, %17, %18, %19, %20, %21, %22, %23, %24, %25, %26, %27, %28, %29, %30, %31, %32, %33, %34, %35, %36, %37, %38, %39, %40, %41, %42, %43, %44, %45, %46, %47, %48, %49, %50, %51, %52, %53, %54, %55, %56, %57, %58, %59, %60, %61, %62, %63, %64, %65, %66, %67, %68, %69, %70, %71, %72, %73, %74, %75, %76, %77, %78, %79, %80, %81, %82, %83, %84, %85, %86, %87, %88, %89, %90, %91, %92, %93, %94, %95, %96, %97, %98, %99, %100, %101, %102, %103, %104, %105, %106, %107, %108, %109, %110, %111, %112, %113, %114, %115, %116, %117, %118, %119, %120, %121, %122, %123, %124, %125, %126, %127}, %128, %129, p, 1, 1, 0, 1;}\n"
    : "+f"(d[0]), "+f"(d[1]), "+f"(d[2]), "+f"(d[3]), "+f"(d[4]), "+f"(d[5]), "+f"(d[6]), "+f"(d[7]), "+f"(d[8]), "+f"(d[9]), "+f"(d[10]), "+f"(d[11]), "+f"(d[12]), "+f"(d[13]), "+f"(d[14]), "+f"(d[15]), "+f"(d[16]), "+f"(d[17]), "+f"(d[18]), "+f"(d[19]), "+f"(d[20]), "+f"(d[21]), "+f"(d[22]), "+f"(d[23]), "+f"(d[24]), "+f"(d[25]), "+f"(d[26]), "+f"(d[27]), "+f"(d[28]), "+f"(d[29]), "+f"(d[30]), "+f"(d[31]), "+f"(d[32]), "+f"(d[33]), "+f"(d[34]), "+f"(d[35]), "+f"(d[36]), "+f"(d[37]), "+f"(d[38]), "+f"(d[39]), "+f"(d[40]), "+f"(d[41]), "+f"(d[42]), "+f"(d[43]), "+f"(d[44]), "+f"(d[45]), "+f"(d[46]), "+f"(d[47]), "+f"(d[48]), "+f"(d[49]), "+f"(d[50]), "+f"(d[51]), "+f"(d[52]), "+f"(d[53]), "+f"(d[54]), "+f"(d[55]), "+f"(d[56]), "+f"(d[57]), "+f"(d[58]), "+f"(d[59]), "+f"(d[60]), "+f"(d[61]), "+f"(d[62]), "+f"(d[63]), "+f"(d[64]), "+f"(d[65]), "+f"(d[66]), "+f"(d[67]), "+f"(d[68]), "+f"(d[69]), "+f"(d[70]), "+f"(d[71]), "+f"(d[72]), "+f"(d[73]), "+f"(d[74]), "+f"(d[75]), "+f"(d[76]), "+f"(d[77]), "+f"(d[78]), "+f"(d[79]), "+f"(d[80]), "+f"(d[81]), "+f"(d[82]), "+f"(d[83]), "+f"(d[84]), "+f"(d[85]), "+f"(d[86]), "+f"(d[87]), "+f"(d[88]), "+f"(d[89]), "+f"(d[90]), "+f"(d[91]), "+f"(d[92]), "+f"(d[93]), "+f"(d[94]), "+f"(d[95]), "+f"(d[96]), "+f"(d[97]), "+f"(d[98]), "+f"(d[99]), "+f"(d[100]), "+f"(d[101]), "+f"(d[102]), "+f"(d[103]), "+f"(d[104]), "+f"(d[105]), "+f"(d[106]), "+f"(d[107]), "+f"(d[108]), "+f"(d[109]), "+f"(d[110]), "+f"(d[111]), "+f"(d[112]), "+f"(d[113]), "+f"(d[114]), "+f"(d[115]), "+f"(d[116]), "+f"(d[117]), "+f"(d[118]), "+f"(d[119]), "+f"(d[120]), "+f"(d[121]), "+f"(d[122]), "+f"(d[123]), "+f"(d[124]), "+f"(d[125]), "+f"(d[126]), "+f"(d[127])
    : "l"(da), "l"(db), "r"(sc));
}

__device__ __forceinline__ void wg_ss_bf16_n256k(float* d, uint64_t da, uint64_t db, int sc) {
  asm volatile("{.reg .pred p; setp.ne.b32 p, %130, 0;\n"
    "wgmma.mma_async.sync.aligned.m64n256k16.f32.bf16.bf16 {%0, %1, %2, %3, %4, %5, %6, %7, %8, %9, %10, %11, %12, %13, %14, %15, %16, %17, %18, %19, %20, %21, %22, %23, %24, %25, %26, %27, %28, %29, %30, %31, %32, %33, %34, %35, %36, %37, %38, %39, %40, %41, %42, %43, %44, %45, %46, %47, %48, %49, %50, %51, %52, %53, %54, %55, %56, %57, %58, %59, %60, %61, %62, %63, %64, %65, %66, %67, %68, %69, %70, %71, %72, %73, %74, %75, %76, %77, %78, %79, %80, %81, %82, %83, %84, %85, %86, %87, %88, %89, %90, %91, %92, %93, %94, %95, %96, %97, %98, %99, %100, %101, %102, %103, %104, %105, %106, %107, %108, %109, %110, %111, %112, %113, %114, %115, %116, %117, %118, %119, %120, %121, %122, %123, %124, %125, %126, %127}, %128, %129, p, 1, 1, 0, 0;}\n"
    : "+f"(d[0]), "+f"(d[1]), "+f"(d[2]), "+f"(d[3]), "+f"(d[4]), "+f"(d[5]), "+f"(d[6]), "+f"(d[7]), "+f"(d[8]), "+f"(d[9]), "+f"(d[10]), "+f"(d[11]), "+f"(d[12]), "+f"(d[13]), "+f"(d[14]), "+f"(d[15]), "+f"(d[16]), "+f"(d[17]), "+f"(d[18]), "+f"(d[19]), "+f"(d[20]), "+f"(d[21]), "+f"(d[22]), "+f"(d[23]), "+f"(d[24]), "+f"(d[25]), "+f"(d[26]), "+f"(d[27]), "+f"(d[28]), "+f"(d[29]), "+f"(d[30]), "+f"(d[31]), "+f"(d[32]), "+f"(d[33]), "+f"(d[34]), "+f"(d[35]), "+f"(d[36]), "+f"(d[37]), "+f"(d[38]), "+f"(d[39]), "+f"(d[40]), "+f"(d[41]), "+f"(d[42]), "+f"(d[43]), "+f"(d[44]), "+f"(d[45]), "+f"(d[46]), "+f"(d[47]), "+f"(d[48]), "+f"(d[49]), "+f"(d[50]), "+f"(d[51]), "+f"(d[52]), "+f"(d[53]), "+f"(d[54]), "+f"(d[55]), "+f"(d[56]), "+f"(d[57]), "+f"(d[58]), "+f"(d[59]), "+f"(d[60]), "+f"(d[61]), "+f"(d[62]), "+f"(d[63]), "+f"(d[64]), "+f"(d[65]), "+f"(d[66]), "+f"(d[67]), "+f"(d[68]), "+f"(d[69]), "+f"(d[70]), "+f"(d[71]), "+f"(d[72]), "+f"(d[73]), "+f"(d[74]), "+f"(d[75]), "+f"(d[76]), "+f"(d[77]), "+f"(d[78]), "+f"(d[79]), "+f"(d[80]), "+f"(d[81]), "+f"(d[82]), "+f"(d[83]), "+f"(d[84]), "+f"(d[85]), "+f"(d[86]), "+f"(d[87]), "+f"(d[88]), "+f"(d[89]), "+f"(d[90]), "+f"(d[91]), "+f"(d[92]), "+f"(d[93]), "+f"(d[94]), "+f"(d[95]), "+f"(d[96]), "+f"(d[97]), "+f"(d[98]), "+f"(d[99]), "+f"(d[100]), "+f"(d[101]), "+f"(d[102]), "+f"(d[103]), "+f"(d[104]), "+f"(d[105]), "+f"(d[106]), "+f"(d[107]), "+f"(d[108]), "+f"(d[109]), "+f"(d[110]), "+f"(d[111]), "+f"(d[112]), "+f"(d[113]), "+f"(d[114]), "+f"(d[115]), "+f"(d[116]), "+f"(d[117]), "+f"(d[118]), "+f"(d[119]), "+f"(d[120]), "+f"(d[121]), "+f"(d[122]), "+f"(d[123]), "+f"(d[124]), "+f"(d[125]), "+f"(d[126]), "+f"(d[127])
    : "l"(da), "l"(db), "r"(sc));
}

__device__ __forceinline__ void wg_rs_bf16_n64(float* d, uint32_t a0, uint32_t a1, uint32_t a2, uint32_t a3, uint64_t db, int sc) {
  asm volatile("{.reg .pred p; setp.ne.b32 p, %37, 0;\n"
    "wgmma.mma_async.sync.aligned.m64n64k16.f32.bf16.bf16 {%0, %1, %2, %3, %4, %5, %6, %7, %8, %9, %10, %11, %12, %13, %14, %15, %16, %17, %18, %19, %20, %21, %22, %23, %24, %25, %26, %27, %28, %29, %30, %31}, {%32,%33,%34,%35}, %36, p, 1, 1, 1;}\n"
    : "+f"(d[0]), "+f"(d[1]), "+f"(d[2]), "+f"(d[3]), "+f"(d[4]), "+f"(d[5]), "+f"(d[6]), "+f"(d[7]), "+f"(d[8]), "+f"(d[9]), "+f"(d[10]), "+f"(d[11]), "+f"(d[12]), "+f"(d[13]), "+f"(d[14]), "+f"(d[15]), "+f"(d[16]), "+f"(d[17]), "+f"(d[18]), "+f"(d[19]), "+f"(d[20]), "+f"(d[21]), "+f"(d[22]), "+f"(d[23]), "+f"(d[24]), "+f"(d[25]), "+f"(d[26]), "+f"(d[27]), "+f"(d[28]), "+f"(d[29]), "+f"(d[30]), "+f"(d[31])
    : "r"(a0), "r"(a1), "r"(a2), "r"(a3), "l"(db), "r"(sc));
}

__device__ __forceinline__ void wg_rs_f16_n32k(float* d, uint32_t a0, uint32_t a1, uint32_t a2, uint32_t a3, uint64_t db, int sc) {
  asm volatile("{.reg .pred p; setp.ne.b32 p, %21, 0;\n"
    "wgmma.mma_async.sync.aligned.m64n32k16.f32.f16.f16 {%0, %1, %2, %3, %4, %5, %6, %7, %8, %9, %10, %11, %12, %13, %14, %15}, {%16,%17,%18,%19}, %20, p, 1, 1, 0;}\n"
    : "+f"(d[0]), "+f"(d[1]), "+f"(d[2]), "+f"(d[3]), "+f"(d[4]), "+f"(d[5]), "+f"(d[6]), "+f"(d[7]), "+f"(d[8]), "+f"(d[9]), "+f"(d[10]), "+f"(d[11]), "+f"(d[12]), "+f"(d[13]), "+f"(d[14]), "+f"(d[15])
    : "r"(a0), "r"(a1), "r"(a2), "r"(a3), "l"(db), "r"(sc));
}

__device__ __forceinline__ void wg_rs_f16_n24t(float* d, uint32_t a0, uint32_t a1, uint32_t a2, uint32_t a3, uint64_t db, int sc) {
  asm volatile("{.reg .pred p; setp.ne.b32 p, %17, 0;\n"
    "wgmma.mma_async.sync.aligned.m64n24k16.f32.f16.f16 {%0, %1, %2, %3, %4, %5, %6, %7, %8, %9, %10, %11}, {%12,%13,%14,%15}, %16, p, 1, 1, 1;}\n"
    : "+f"(d[0]), "+f"(d[1]), "+f"(d[2]), "+f"(d[3]), "+f"(d[4]), "+f"(d[5]), "+f"(d[6]), "+f"(d[7]), "+f"(d[8]), "+f"(d[9]), "+f"(d[10]), "+f"(d[11])
    : "r"(a0), "r"(a1), "r"(a2), "r"(a3), "l"(db), "r"(sc));
}

__device__ __forceinline__ void wg_rs_f16_n16t(float* d, uint32_t a0, uint32_t a1, uint32_t a2, uint32_t a3, uint64_t db, int sc) {
  asm volatile("{.reg .pred p; setp.ne.b32 p, %13, 0;\n"
    "wgmma.mma_async.sync.aligned.m64n16k16.f32.f16.f16 {%0, %1, %2, %3, %4, %5, %6, %7}, {%8,%9,%10,%11}, %12, p, 1, 1, 1;}\n"
    : "+f"(d[0]), "+f"(d[1]), "+f"(d[2]), "+f"(d[3]), "+f"(d[4]), "+f"(d[5]), "+f"(d[6]), "+f"(d[7])
    : "r"(a0), "r"(a1), "r"(a2), "r"(a3), "l"(db), "r"(sc));
}

struct cf { float x, y; };
__device__ __forceinline__ cf cmul(cf a, cf b) { cf r; r.x = fmaf(a.x, b.x, -a.y * b.y); r.y = fmaf(a.x, b.y, a.y * b.x); return r; }
__device__ __forceinline__ cf zpow(float rho2, float phi, float e) {
  const float m = ex2f(rho2 * e), ang = phi * e;
  cf r; r.x = m * __cosf(ang); r.y = m * __sinf(ang); return r;
}
__device__ __forceinline__ __half2 H2(uint32_t v) { return *reinterpret_cast<__half2*>(&v); }
__device__ __forceinline__ uint32_t U32(__half2 v) { return *reinterpret_cast<uint32_t*>(&v); }
__device__ __forceinline__ uint32_t hprod(uint32_t v, uint32_t r, uint32_t rr) {
  return U32(__hfma2(__high2half2(H2(v)), H2(rr), __hmul2(__low2half2(H2(v)), H2(r))));
}
__device__ __forceinline__ void hprod2(uint32_t re, uint32_t im, uint32_t r, uint32_t& ore, uint32_t& oim) {
  const __half2 rx = __low2half2(H2(r)), ry = __high2half2(H2(r));
  ore = U32(__hfma2(H2(re), rx, __hneg2(__hmul2(H2(im), ry))));
  oim = U32(__hfma2(H2(re), ry, __hmul2(H2(im), rx)));
}
__device__ __forceinline__ uint32_t rot90(uint32_t v) { return __byte_perm(v, 0, 0x1032) ^ 0x00008000u; }
__device__ __forceinline__ uint32_t hadd2u(uint32_t a, uint32_t b) { return U32(__hadd2(H2(a), H2(b))); }

struct KgIn { uint32_t cur[6], nxt[6]; uint16_t ldt, dk; };
__device__ __forceinline__ void kgen_load(const Params& p, int d, int wd0, int nw, int lane, KgIn& k) {
  const int off = d * (NST / 2) + 32 * wd0 + lane;
  const uint32_t* P[6] = {(const uint32_t*)p.a_re, (const uint32_t*)p.a_im, (const uint32_t*)p.b_re,
                          (const uint32_t*)p.b_im, (const uint32_t*)p.c_re, (const uint32_t*)p.c_im};
#pragma unroll
  for (int i = 0; i < 6; i++) { k.cur[i] = __ldg(P[i] + off); k.nxt[i] = __ldg(P[i] + off + 32 * (nw - 1)); }
  k.ldt = __ldg((const uint16_t*)p.log_dt + d); k.dk = __ldg((const uint16_t*)p.dskip + d);
}
__device__ __forceinline__ float pow2_floor(float v) { return __uint_as_float(__float_as_uint(fminf(fmaxf(v, 1e-30f), 1e30f)) & 0x7f800000u); }
__device__ __forceinline__ void kgen_mma(float* acc, const uint32_t (*A)[4], const uint32_t (*B)[6], int csrc) {
#pragma unroll
  for (int ks = 0; ks < 4; ks++) {
    const uint32_t rl = __shfl_sync(0xffffffffu, B[ks][4], csrc), rh = __shfl_sync(0xffffffffu, B[ks][5], csrc);
    const uint32_t rlr = rot90(rl), rhr = rot90(rh);
    mma_f16(acc + 0, A[ks][0], A[ks][1], A[ks][2], A[ks][3], B[ks][0], B[ks][1]);
    mma_f16(acc + 4, A[ks][0], A[ks][1], A[ks][2], A[ks][3], B[ks][2], B[ks][3]);
    mma_f16(acc + 8, A[ks][0], A[ks][1], A[ks][2], A[ks][3], B[ks][4], B[ks][5]);
    const uint32_t c0 = hprod(A[ks][0], rl, rlr), c1 = hprod(A[ks][1], rl, rlr);
    const uint32_t c2 = hprod(A[ks][2], rh, rhr), c3 = hprod(A[ks][3], rh, rhr);
    mma_f16(acc + 12, c0, c1, c2, c3, B[ks][0], B[ks][1]);
    mma_f16(acc + 16, c0, c1, c2, c3, B[ks][2], B[ks][3]);
    mma_f16(acc + 20, c0, c1, c2, c3, B[ks][4], B[ks][5]);
  }
}
__device__ __forceinline__ void kgen_warp(KgIn& k, int nw, uint32_t stg, uint32_t tbl, int lane) {
  float dl, dt, sc, inv_sc;
  {
    const uint32_t M = 0x7fff7fffu;
    uint32_t mx[2];
#pragma unroll
    for (int i = 0; i < 2; i++) {
      const uint32_t m = __vmaxu2(__vmaxu2(k.cur[2 + 2 * i] & M, k.cur[3 + 2 * i] & M), __vmaxu2(k.nxt[2 + 2 * i] & M, k.nxt[3 + 2 * i] & M));
      mx[i] = __reduce_max_sync(0xffffffffu, max(m << 16, m & 0xffff0000u));
    }
    dt = rbf(ex2f(bf_lo(k.ldt) * 1.4426950408889634f));
    sc = pow2_floor(0.125f * __uint_as_float(mx[0]) * __uint_as_float(mx[1]));
    inv_sc = rcpf_(sc);
    if (lane == 0) sts64f(tbl + TBL_SC + 8, dt, bf_lo(k.dk) * rcpf_(dt));
    dl = dt * 1.4426950408889634f;
  }
  const uint32_t st0 = stg + lane * KREC + (((lane >> 2) & 1) << 4), st1 = st0 ^ 16;
  const int mat = lane >> 3, rowi = lane & 7;
  const uint32_t ldB = stg + (4 * (mat & 1) + (rowi >> 1)) * KREC + ((((mat >> 1) * 2 + (rowi & 1)) << 4) ^ ((mat & 1) << 4));
  const uint32_t ldA = stg + (4 * (mat >> 1) + (rowi >> 1)) * KREC + ((((mat & 1) * 2 + (rowi & 1)) << 4) ^ ((mat >> 1) << 4)) + 96;
  const int csrc = 20 + (lane & 3);
  float acc[24];
  uint32_t B[4][6], A[4][4];
#pragma unroll
  for (int i = 0; i < 24; i++) { acc[i] = 0.f; B[i / 6][i % 6] = 0u; }
#pragma unroll
  for (int i = 0; i < 16; i++) A[i / 4][i % 4] = 0u;
#pragma unroll 1
  for (int it = 0; it < 2 * nw; it++) {
    const uint32_t sel = (it & 1) ? 0x3244u : 0x1044u;
    float v[6];
#pragma unroll
    for (int i = 0; i < 6; i++) { v[i] = __uint_as_float(__byte_perm(k.cur[i], 0, sel)); if (it == 1) k.cur[i] = k.nxt[i]; }
    const float rho2 = v[0] * dl, phi = v[1] * dt;
    const cf bb = {v[2] * inv_sc, v[3] * -inv_sc}, cc = {v[4], -v[5]};
    cf X[8];
    X[0] = cmul(cc, bb);
    const cf z1 = zpow(rho2, -phi, 1.f), z8 = zpow(rho2, phi, 8.f), z64 = zpow(rho2, phi, 64.f);
    const cf y1 = zpow(rho2, -phi, 256.f), y4 = zpow(rho2, -phi, 1024.f);
    kgen_mma(acc, A, B, csrc);
    const cf z2 = cmul(z1, z1);
    X[1] = cmul(X[0], z1);
#pragma unroll
    for (int j = 2; j < 8; j++) X[j] = cmul(X[j - 2], z2);
    const cf a0 = cmul(X[0], y1), a1 = cmul(X[2], y1), a2 = cmul(X[4], y1), a3 = cmul(X[6], y1);
    const cf a4 = cmul(a0, y1), a5 = cmul(a2, y1);
    const cf a6 = cmul(a4, y1), a7 = cmul(a5, y1);
    const cf v0 = cmul(X[0], y4), v1 = cmul(a0, y4), v2 = cmul(a4, y4), v3 = cmul(a6, y4), v4 = cmul(v0, y4);
    const cf f2 = cmul(z8, z8), f3 = cmul(f2, z8), f4 = cmul(f2, f2), f5 = cmul(f3, f2), f6 = cmul(f4, f2), f7 = cmul(f4, f3);
    const cf z128 = cmul(z64, z64);
    const uint32_t fr[4] = {pack_h2(1.f, z8.x), pack_h2(f2.x, f3.x), pack_h2(f4.x, f5.x), pack_h2(f6.x, f7.x)};
    const uint32_t fi[4] = {pack_h2(0.f, z8.y), pack_h2(f2.y, f3.y), pack_h2(f4.y, f5.y), pack_h2(f6.y, f7.y)};
    const uint32_t h64 = pack_h2(z64.x, z64.y);
    uint32_t gr[4], gi[4];
#pragma unroll
    for (int j = 0; j < 4; j++) hprod2(fr[j], fi[j], h64, gr[j], gi[j]);
    sts128(st0, pack_h2(X[0].x, X[1].x), pack_h2(X[2].x, X[3].x), pack_h2(X[4].x, X[5].x), pack_h2(X[6].x, X[7].x));
    sts128(st1, pack_h2(X[0].y, X[1].y), pack_h2(X[2].y, X[3].y), pack_h2(X[4].y, X[5].y), pack_h2(X[6].y, X[7].y));
    sts128(st0 + 96, fr[0], fr[1], fr[2], fr[3]);
    sts128(st1 + 96, fi[0], fi[1], fi[2], fi[3]);
    sts128(st0 + 128, gr[0], gr[1], gr[2], gr[3]);
    sts128(st1 + 128, gi[0], gi[1], gi[2], gi[3]);
    sts128(st0 + 32, pack_h2(a0.x, a1.x), pack_h2(a2.x, a3.x), pack_h2(a4.x, a5.x), pack_h2(a6.x, a7.x));
    sts128(st1 + 32, pack_h2(a0.y, a1.y), pack_h2(a2.y, a3.y), pack_h2(a4.y, a5.y), pack_h2(a6.y, a7.y));
    sts128(st0 + 64, pack_h2(v0.x, v1.x), pack_h2(v2.x, v3.x), pack_h2(v4.x, z128.x), h64);
    sts128(st1 + 64, pack_h2(v0.y, v1.y), pack_h2(v2.y, v3.y), pack_h2(v4.y, z128.y), h64);
    __syncwarp();
#pragma unroll
    for (int ks = 0; ks < 4; ks++) {
      ldsm2t(ldB + ks * 8 * KREC + 64, B[ks][4], B[ks][5]);
      ldsm4t(ldA + ks * 8 * KREC, A[ks][0], A[ks][1], A[ks][2], A[ks][3]);
      ldsm4t(ldB + ks * 8 * KREC, B[ks][0], B[ks][1], B[ks][2], B[ks][3]);
    }
  }
  kgen_mma(acc, A, B, csrc);
#pragma unroll
  for (int q = 0; q < 4; q++)
#pragma unroll
    for (int nt = 0; nt < 3; nt++) {
      const float* a = acc + 12 * (q >> 1) + 4 * nt + 2 * (q & 1);
      sts64f(stg + (q * 3 + nt) * 256 + lane * 8, a[0] * sc, a[1] * sc);
    }
  if (lane == 0) sts32f(stg + 3072, sc);
}

__device__ __forceinline__ void tput(uint32_t tbl, int X, uint32_t h) {
  sts16(tbl + 2 * (1296 - X), (uint16_t)h);
  sts16(tbl + TBL_C1 + 2 * (1297 - X), (uint16_t)h);
}
__device__ __forceinline__ void ktab_build(uint32_t src, bool four, int q, uint32_t tbl, int lane) {
  const int tq = lane & 3, r = 8 * q + (lane >> 2);
  float v[6];
  const float2 dd = lds64f(tbl + TBL_SC + 8);
  float sc = fmaxf(fmaxf(lds32f(src + 3072), lds32f(src + 3072 + KSTG)), pow2_floor(fabsf(dd.y) * (1.f / 4096.f)));
  if (four) sc = fmaxf(sc, fmaxf(lds32f(src + 3072 + 2 * KSTG), lds32f(src + 3072 + 3 * KSTG)));
  const float inv = rcpf_(sc);
  src += q * 768 + lane * 8;
#pragma unroll
  for (int nt = 0; nt < 3; nt++) {
    const float2 a = lds64f(src + nt * 256), c = lds64f(src + nt * 256 + KSTG);
    v[2 * nt] = a.x + c.x; v[2 * nt + 1] = a.y + c.y;
  }
  if (four) {
#pragma unroll
    for (int nt = 0; nt < 3; nt++) {
      const float2 a = lds64f(src + nt * 256 + 2 * KSTG), c = lds64f(src + nt * 256 + 3 * KSTG);
      v[2 * nt] += a.x + c.x; v[2 * nt + 1] += a.y + c.y;
    }
  }
  const bool first = (r == 0);
  if (first && tq == 0) { v[0] += dd.y; sts64f(tbl + TBL_SC, v[4] * inv, dd.x * sc); }
  const uint32_t h0 = pack_h2(v[0] * inv, v[1] * inv), h1 = pack_h2(v[2] * inv, v[3] * inv), h2 = pack_h2(v[4] * inv, v[5] * inv);
  tput(tbl, 64 + 8 * r + 2 * tq, h0);
  tput(tbl, 65 + 8 * r + 2 * tq, h0 >> 16);
  const bool lo = tq < 2;
  const int Xd = 320 + 8 * r + 4 * tq, k2 = 32 * (tq - 2) + r;
  tput(tbl, lo ? Xd + 2 : 720 + k2, h1 >> 16);
  const bool sp = first && tq == 2;
  const int Xa = lo ? Xd : (sp ? 576 : 911 + k2);
  tput(tbl, Xa, h1);
  if (lo || sp) {
    tput(tbl, Xa + 1, h1);
    if (Xa != 320) tput(tbl, Xa - 1, h1);
  }
  if (sp) { tput(tbl, 578, h1); tput(tbl, 1295, h2); }
  if (lo) {
    const int X3 = ((r & 1) ? 1104 : 1231) + 32 * tq + (r >> 1);
    tput(tbl, X3 == 1231 ? 975 : X3, h2);
    tput(tbl, X3 + 16, h2 >> 16);
  }
}

__device__ __forceinline__ void sig_windows(uint32_t sig, int t) {
  uint32_t U[20];
#pragma unroll
  for (int c = 0; c < 5; c++) {
    const int kap = 2 * t - 3 + c + 72;
    const uint4 v = lds128(sig + SIG_U + (kap & 7) * U_LBO + (kap >> 3) * 16);
    U[4 * c] = v.x; U[4 * c + 1] = v.y; U[4 * c + 2] = v.z; U[4 * c + 3] = v.w;
  }
  uint32_t O[19], A2[17], A4[17], V2[8], V5[8];
#pragma unroll
  for (int i = 3; i < 19; i++) O[i] = __byte_perm(U[i - 1], U[i], 0x5432);
#pragma unroll
  for (int i = 3; i < 17; i++) A2[i] = hadd2u(U[i], O[i]);
#pragma unroll
  for (int i = 4; i < 17; i++) A4[i] = hadd2u(A2[i], A2[i - 1]);
#pragma unroll
  for (int k = 0; k < 8; k++) { V2[k] = hadd2u(O[11 + k], U[10 + k]); V5[k] = hadd2u(A4[9 + k], U[7 + k]); }
#pragma unroll
  for (int h = 0; h < 2; h++) {
    sts128(sig + SIG_V3 + t * 32 + h * 16, hadd2u(V2[4 * h], O[10 + 4 * h]), hadd2u(V2[4 * h + 1], O[11 + 4 * h]),
           hadd2u(V2[4 * h + 2], O[12 + 4 * h]), hadd2u(V2[4 * h + 3], O[13 + 4 * h]));
    sts128(sig + SIG_V5 + t * 32 + h * 16, V5[4 * h], V5[4 * h + 1], V5[4 * h + 2], V5[4 * h + 3]);
  }
  if (t < 64) {
    uint32_t V7[8], V9[8];
#pragma unroll
    for (int k = 0; k < 8; k++) {
      V7[k] = hadd2u(V5[k], hadd2u(O[10 + k], O[7 + k]));
      V9[k] = hadd2u(hadd2u(A4[6 + k], A4[4 + k]), U[2 + k]);
    }
#pragma unroll
    for (int h = 0; h < 2; h++) {
      sts128(sig + SIG_V7 + h * 1024 + t * 16, V7[4 * h], V7[4 * h + 1], V7[4 * h + 2], V7[4 * h + 3]);
      sts128(sig + SIG_V9 + h * 1024 + t * 16, V9[4 * h], V9[4 * h + 1], V9[4 * h + 2], V9[4 * h + 3]);
      sts128(sig + SIG_V2 + h * 1024 + t * 16, V2[4 * h], V2[4 * h + 1], V2[4 * h + 2], V2[4 * h + 3]);
    }
  }
}

__device__ __forceinline__ void conv_channel(uint32_t tbl, uint32_t sig, uint32_t y2b, uint32_t y3b, float k1024,
                                             int w, int lane, int barid, float* res, int ts) {
  TSTAMP(ts);
  const int g = lane >> 2, tq = lane & 3;
  const uint32_t tb = tbl + ((g & 1) ? TBL_C1 + 2 : 0) + 2 * (1296 - (g - 2 * tq)) - 32 * w + 112;
  float a2[12], a3[8];
#pragma unroll
  for (int i = 0; i < 16; i++) res[i] = 0.f;
#pragma unroll
  for (int i = 0; i < 12; i++) a2[i] = 0.f;
#pragma unroll
  for (int q = 0; q < 4; q++) {
    const float2 f = h2f(lds32(sig + SIG_V2 + (q >> 1) * 1024 + (16 * w + 8 * (q & 1) + g) * 16 + tq * 4));
    a3[2 * q] = k1024 * f.x;
    a3[2 * q + 1] = k1024 * f.y;
  }
  const uint64_t dU = mkdesc(sig + SIG_U, U_LBO, 128, 0);
  const uint64_t dV = mkdesc(sig, 128, 1024, 0);
  fence_regs<16>(res); fence_regs<12>(a2); fence_regs<8>(a3);
  constexpr int LB = 2 * U_LBO / 16;
  uint32_t Rd[75], R2[2][17], R3[2][9];
  auto load_group = [&](int gi) {
    const int it = gi >> 1, hb = gi & 1;
    if (gi == 0) Rd[0] = lds32(tb - 128);
#pragma unroll
    for (int i = 1; i < (gi == 17 ? 7 : 5); i++) Rd[4 * gi + i] = lds32(tb - 128 - 16 * (4 * gi + i));
    if (gi < 16) {
      const int sg = it >> 2, n2 = gi & 7;
      if (n2 == 0) R2[sg][0] = lds32(tb - 1440 - 384 * sg);
      R2[sg][2 * n2 + 1] = lds32(tb - 1440 - 384 * sg - 16 * (2 * n2 + 1));
      R2[sg][2 * n2 + 2] = lds32(tb - 1440 - 384 * sg - 16 * (2 * n2 + 2));
      if (!hb) {
        const int n3 = it & 3;
        if (n3 == 0) R3[sg][0] = lds32(tb - 2208 - 256 * sg);
        R3[sg][2 * n3 + 1] = lds32(tb - 2208 - 256 * sg - 16 * (2 * n3 + 1));
        R3[sg][2 * n3 + 2] = lds32(tb - 2208 - 256 * sg - 16 * (2 * n3 + 2));
      }
    }
  };
  auto dense = [&](int n) {
    wg_rs_f16_n32k(res, Rd[2 * n + 1], Rd[2 * n + 2], Rd[2 * n], Rd[2 * n + 1], dU + ((3 - (n & 3)) * LB + 9 - (n >> 2)), 1);
  };
  load_group(0);
  load_group(1);
#pragma unroll
  for (int gi = 0; gi < 18; gi++) {
    const int it = gi >> 1, sg = it >> 2, n2 = gi & 7, n3 = it & 3;
    wg_fence();
    dense(2 * gi);
    if (gi < 16)
      wg_rs_f16_n24t(a2, R2[sg][2 * n2 + 1], R2[sg][2 * n2 + 2], R2[sg][2 * n2], R2[sg][2 * n2 + 1],
                     dV + ((SIG_V3 + 768) / 16 + 256 * sg - 16 * (n2 & 3) - 64 * (n2 >> 2)), 1);
    dense(2 * gi + 1);
    if (gi < 16 && !(gi & 1))
      wg_rs_f16_n16t(a3, R3[sg][2 * n3 + 1], R3[sg][2 * n3 + 2], R3[sg][2 * n3], R3[sg][2 * n3 + 1],
                     dV + ((SIG_V7 + 768) / 16 + 128 * sg - 16 * n3), 1);
    if (gi == 17) dense(36);
    wg_commit();
    if (gi < 16) { wg_wait<1>(); load_group(gi + 2); }
  }
  TSTAMP(ts + 1);
  wg_wait<2>();
  fence_regs<12>(a2); fence_regs<8>(a3);
  bar_sync(barid, 128);
  {
    const uint32_t o2 = y2b + (136 * w + 8 * g + 2 * tq) * 4, o3 = y3b + (272 * w + 16 * g + 2 * tq) * 4;
#pragma unroll
    for (int q = 0; q < 6; q++) sts64f(o2 + (544 * (q >> 1) + 64 * (q & 1)) * 4, a2[2 * q], a2[2 * q + 1]);
#pragma unroll
    for (int q = 0; q < 4; q++) sts64f(o3 + (8 * (q >> 1) + 136 * (q & 1)) * 4, a3[2 * q], a3[2 * q + 1]);
  }
  bar_sync(barid, 128);
  const uint32_t go = (136 * tq + 16 * w + g) * 4;
  float ex[12];
#pragma unroll
  for (int i = 0; i < 12; i++) {
    const int o = 544 * (i >> 2) + 64 * (i & 1) + 8 * ((i >> 1) & 1);
    ex[i] = lds32f(y2b + go + o * 4);
    if (i >= 4) ex[i] += lds32f(y3b + go + (o - 544) * 4);
  }
  wg_wait<0>();
  fence_regs<16>(res);
#pragma unroll
  for (int i = 0; i < 12; i++) res[4 + i] += ex[i];
  TSTAMP(ts + 2);
}

__device__ __forceinline__ void red16x2(float& a, float& c) {
#pragma unroll
  for (int o = 1; o < 16; o <<= 1) { a += __shfl_xor_sync(0xffffffffu, a, o); c += __shfl_xor_sync(0xffffffffu, c, o); }
}
__device__ __forceinline__ void ln_rows(Scratch* sc, uint32_t* u, int row, uint32_t stg_row, int lane) {
  const int j = lane & 15;
  const float piv = __shfl_sync(0xffffffffu, bf_lo(u[0]), lane & 16);
  float s0 = 0.f, s1 = 0.f, q0 = 0.f, q1 = 0.f;
#pragma unroll
  for (int i = 0; i < 14; i++) {
    const float a = bf_lo(u[i]) - piv, c = bf_hi(u[i]) - piv;
    s0 += a; s1 += c; q0 = fmaf(a, a, q0); q1 = fmaf(c, c, q1);
  }
  float s = s0 + s1, q = q0 + q1;
  red16x2(s, q);
  s *= (1.f / D_); q *= (1.f / D_);
  const __nv_bfloat16 m1b = __float2bfloat16_rn(s + piv);
  const __nv_bfloat162 m1v = __halves2bfloat162(m1b, m1b);
  const float den = rbf(sqrtf_(rbf(rbf(fmaxf(fmaf(-s, s, q), 0.f)) + 1e-5f)));
  const float rden = rcpf_(den);
  s0 = s1 = q0 = q1 = 0.f;
#pragma unroll
  for (int i = 0; i < 14; i++) {
    const __nv_bfloat162 cv = __hsub2(*reinterpret_cast<__nv_bfloat162*>(&u[i]), m1v);
    const uint32_t c = *reinterpret_cast<const uint32_t*>(&cv);
    const uint32_t n = pack_bf2(bf_lo(c) * rden, bf_hi(c) * rden);
    const float a = bf_lo(n), e = bf_hi(n);
    s0 += a; s1 += e; q0 = fmaf(a, a, q0); q1 = fmaf(e, e, q1);
    u[i] = pack_h2(a, e);
  }
#pragma unroll
  for (int i = 0; i < 7; i++)
    asm volatile("st.shared.v2.b32 [%0], {%1,%2};" ::"r"(stg_row + (j + 16 * i) * 8), "r"(u[2 * i]), "r"(u[2 * i + 1]) : "memory");
  s = s0 + s1; q = q0 + q1;
  red16x2(s, q);
  s *= (1.f / D_); q *= (1.f / D_);
  const float den2 = rbf(sqrtf_(rbf(rbf(fmaxf(fmaf(-s, s, q), 0.f)) + 1e-5f)));
  if (j == 0) {
    const float ir = den * den2, mu = fmaf(rbf(s), den, __bfloat162float(m1b));
    const float ih = rbf(ir), mh = rbf(mu);
    const uint32_t mm = pack_bf2(mh, mh);
    sc->ax[row] = make_uint4(mm, pack_bf2(mu - mh, ih), mm, pack_bf2(mu - mh, ir - ih));
    sc->r[row] = rcpf_(ir);
  }
}

__device__ __forceinline__ void poll_tag(const unsigned* p, uint32_t tag) {
#pragma unroll 1
  for (int it = 0; it < 4096; it++) {
    if (!((ld_relaxed1(p) ^ tag) & 1)) break;
    __nanosleep(32);
  }
}
template <int NV, int STRIDE>
__device__ __forceinline__ void recv_part(const uint4* src, uint32_t tag, float* pre) {
  uint4 v[NV];
#pragma unroll 1
  for (int it = 0; it < RETRY_MAX; it++) {
    uint32_t bad = 0;
#pragma unroll
    for (int q = 0; q < NV; q++) v[q] = ld_b128(src + q * STRIDE);
#pragma unroll
    for (int q = 0; q < NV; q++) bad |= v[q].x ^ tag;
    const unsigned m = __ballot_sync(0xffffffffu, bad & 1);
    if (!m) break;
    if ((threadIdx.x & 31) == __ffs(m) - 1) poll_tag((const unsigned*)(src + (NV - 1) * STRIDE), tag);
    __syncwarp();
  }
#pragma unroll
  for (int q = 0; q < NV; q++) {
    const uint32_t u[4] = {v[q].x, v[q].y, v[q].z, v[q].w};
#pragma unroll
    for (int k = 0; k < 4; k++) { pre[8 * q + 2 * k] += bf_lo(u[k]); pre[8 * q + 2 * k + 1] += bf_hi(u[k]); }
  }
}
__device__ __forceinline__ void send_part(uint4* dst, uint32_t tag, const float* a) {
#pragma unroll
  for (int q = 0; q < 4; q++)
    st_b128(dst + q * 256, tag, pack_bf2(a[8 * q], a[8 * q + 1]), pack_bf2(a[8 * q + 2], a[8 * q + 3]),
            pack_bf2(a[8 * q + 4], a[8 * q + 5]), pack_bf2(a[8 * q + 6], a[8 * q + 7]));
}
__device__ __forceinline__ bool last_release(uint32_t cnt) {
  unsigned old;
  asm volatile("atom.relaxed.cta.shared.inc.u32 %0, [%1], 7;" : "=r"(old) : "r"(cnt) : "memory");
  return old == 7;
}
__device__ __forceinline__ int mod7(int v) { return v >= 7 ? v - 7 : v; }

#define IDS const int tid = opaque(tid0), lane = tid & 31, t = tid & 127, wg = tid >> 7, w = (tid >> 5) & 3; \
            (void)lane; (void)t; (void)wg; (void)w;

__global__ void __launch_bounds__(384, 1)
fused_kernel(const Params p, const __grid_constant__ CUtensorMap tm_x, const __grid_constant__ CUtensorMap tm_w1,
             const __grid_constant__ CUtensorMap tm_w2, const __grid_constant__ CUtensorMap tm_out) {
  const uint32_t sb = smem_u32(smem_raw);
  const uint32_t ms = sb + OFF_M;
  const uint32_t bar0 = ms + M_BAR;
  const int tid0 = threadIdx.x;
  const int b = blockIdx.x;
  const bool is_ssm = b >= NMLP;
  const int G = b / NRK, rk = b - G * NRK;
  const int kc0 = (G + rk) % 7;
  TSINIT();
  TSTAMP(0);
  {
    IDS
    if (t == 0 || tid == 32) {
      const int i = __shfl_sync(1u, tid == 32 ? 3 : wg, 0);
      mbar_init(bar0 + 8 * i, 1);
      asm volatile("fence.mbarrier_init.release.cluster;" ::: "memory");
      if (i < 3 && !is_ssm) {
        const int kc = mod7(kc0 + i);
        mbar_expect(bar0 + 8 * i, 49152);
        tma_2d(sb + OFF_X + i * 16384, &tm_x, 64 * kc, 128 * G, bar0 + 8 * i);
        tma_3d(sb + OFF_W + i * 32768, &tm_w1, 0, 64 * kc, 4 * rk, bar0 + 8 * i);
      }
    }
    if (tid >= 64 && tid < 80) asm volatile("st.shared.b32 [%0], 0;" ::"r"(ms + M_REL + 4 * lane) : "memory");
    TSTAMP(28);
    unsigned ep = 0;
    if (tid == 256 + 32) ep = *(volatile unsigned*)&p.s->epoch;
    uint4 ld[7];
    const int rl = 2 * (tid >> 5) + (lane >> 4);
    if (wg < 2) {
      const uint2* xr = (const uint2*)(p.x + (size_t)(16 * (b & 127) + rl) * D_) + (lane & 15);
#pragma unroll
      for (int i = 0; i < 7; i++) { const uint2 v = __ldg(xr + 16 * i); ld[i].x = v.x; ld[i].y = v.y; }
    } else {
      const uint4* wr = (const uint4*)(p.w1 + (size_t)(112 * (b & 3) + (t >> 3)) * F_ + 64 * (is_ssm ? 0 : b >> 2)) + (t & 7);
#pragma unroll
      for (int i = 0; i < 7; i++) ld[i] = __ldg(wr + (size_t)i * 16 * (F_ / 8));
    }
    KgIn kin;
    {
      const int d = is_ssm ? 2 * (112 + 3 * (b - NMLP) + wg) + (w >> 1) : (wg < 2 ? 2 * b + wg : 336 + b);
      kgen_load(p, d, is_ssm ? 2 * (w & 1) : w, is_ssm ? 2 : 1, lane, kin);
    }
    const uint32_t tbl = is_ssm ? sb + (4 * wg + (w >> 1)) * TBL : sb + OFF_T + wg * TBL;
#pragma unroll 1
    for (int i = is_ssm ? t & 63 : t; i < TBL_SC / 16; i += is_ssm ? 64 : 128) sts128(tbl + i * 16, 0u, 0u, 0u, 0u);
    const uint32_t lns = is_ssm ? sb + S_WORK + 2 * S_WGB : sb + OFF_B;
    TSTAMP(31);
    if (wg < 2) {
      uint32_t u[14];
#pragma unroll
      for (int i = 0; i < 7; i++) { u[2 * i] = ld[i].x; u[2 * i + 1] = ld[i].y; }
      ln_rows(p.s, u, 16 * (b & 127) + rl, lns + ((rl & 1) | ((rl >> 2) << 1) | ((rl & 2) << 2)) * 912, lane);
      bar_arrive(7, 384);
    } else {
      const float b1v = __bfloat162float(p.b1[64 * (is_ssm ? 0 : b >> 2) + (t & 63)]);
      float cs[8];
#pragma unroll
      for (int k = 0; k < 8; k++) cs[k] = 0.f;
#pragma unroll
      for (int i = 0; i < 7; i++) {
        const uint32_t uu[4] = {ld[i].x, ld[i].y, ld[i].z, ld[i].w};
#pragma unroll
        for (int k = 0; k < 4; k++) { cs[2 * k] += bf_lo(uu[k]); cs[2 * k + 1] += bf_hi(uu[k]); }
      }
#pragma unroll
      for (int st = 0; st < 2; st++) {
        const int n = 4 >> st;
        const bool up = (lane >> (4 - st)) & 1;
#pragma unroll
        for (int k = 0; k < n; k++) {
          const float give = up ? cs[k] : cs[k + n], keep = up ? cs[k + n] : cs[k];
          cs[k] = keep + __shfl_xor_sync(0xffffffffu, give, 16 >> st);
        }
      }
      sts64f(ms + M_CSR + (w * 64 + (lane & 7) * 8 + (lane >> 3) * 2) * 4, cs[0], cs[1]);
      if (t == 32) asm volatile("st.shared.b32 [%0], %1;" ::"r"(ms + M_EP), "r"(ep + 1) : "memory");
      bar_sync(7, 384);
      const uint32_t la = lns + (lane & 15) * 912 + (lane >> 4) * 16 + w * 224;
      uint2* dst = (uint2*)(p.s->xnT + (size_t)(56 * w + (lane >> 3)) * 512 + 4 * b) + (lane & 7);
      uint32_t r[28];
#pragma unroll
      for (int k = 0; k < 7; k++) ldsm4t(la + k * 32, r[4 * k], r[4 * k + 1], r[4 * k + 2], r[4 * k + 3]);
      const uint32_t tag = lds32(ms + M_EP) & 1;
      if (b < 128) {
#pragma unroll
        for (int k = 0; k < 14; k++) st_relaxed2(dst + k * 4096, (r[2 * k] & ~1u) | tag, (r[2 * k + 1] & ~1u) | tag);
      }
      if (t < 64 && !is_ssm) {
        const uint32_t a = ms + M_CSR + t * 4;
        const float c = -((lds32f(a) + lds32f(a + 256)) + (lds32f(a + 512) + lds32f(a + 768)));
        const float ch = rbf(c);
        uint2* dx = (uint2*)(p.s->bx + (b >> 4) * 512 + ((b >> 1) & 1) * 256 + ((b >> 2) & 3) * 64 + t) + (b & 1);
        *dx = make_uint2(pack_bf2(ch, c - ch), pack_bf2(ch, (b & 2) ? 0.f : b1v));
      }
      bar_sync(6, 128);
    }
    TSTAMP(29);
    const uint32_t stg = is_ssm ? sb + S_WORK + wg * S_WGB + w * KSTG : sb + (wg < 2 ? OFF_A + 4 * wg * KSTG : OFF_B) + w * KSTG;
    kgen_warp(kin, is_ssm ? 2 : 1, stg, tbl, lane);
  }
  TSTAMP(1);
  uint4 v[4];
  {
    IDS
    bar_sync(4 + wg, 128);
    if (is_ssm || wg == 2) {
      const uint4* src = p.s->xnT + (size_t)(is_ssm ? 112 + 3 * (b - NMLP) + wg : b) * 512 + t;
#pragma unroll
      for (int q = 0; q < 4; q++) v[q] = ld_relaxed4(src + q * 128);
    }
#pragma unroll 1
    for (int c = is_ssm ? 1 : 0; c >= 0; c--) {
      const uint32_t src = is_ssm ? sb + S_WORK + wg * S_WGB + 2 * c * KSTG : sb + (wg < 2 ? OFF_A + 4 * wg * KSTG : OFF_B);
      ktab_build(src, !is_ssm, w, is_ssm ? sb + (4 * wg + c) * TBL : sb + OFF_T + wg * TBL, lane);
    }
    fence_async();
  }
  TSTAMP(2);
  __syncthreads();

  if (is_ssm || __shfl_sync(0xffffffffu, tid0 >> 7, 0) == 2) {
    asm volatile("setmaxnreg.dec.sync.aligned.u32 136;");
#pragma unroll 1
    for (int pi = opaque(0); ; pi++) {
      {
        IDS
        const unsigned ep1 = lds32(ms + M_EP);
        const int pair = !is_ssm ? b : (pi == 0 ? 112 + 3 * (b - NMLP) : (b < NMLP + 12 ? 172 + 3 * (b - NMLP) : 184 + 2 * (b - NMLP))) + wg;
        const uint32_t work = is_ssm ? sb + S_WORK + wg * S_WGB : sb + OFF_A;
        if (pi == 1 && t == 96) {
          wait_count(&p.s->cntT, ep1 * NMLP);
          asm volatile("fence.proxy.async;" ::: "memory");
          mbar_expect(bar0 + 8 * wg, 2 * TBL);
          bulk_g2s(sb + (4 * wg + 2) * TBL, p.s->tbl + (2 * pair - 336) * (TBL / 16), 2 * TBL, bar0 + 8 * wg);
        }
        const uint32_t z = work + SIG_V3 - 1024 + (t >> 6) * 4096 + (t & 63) * 16;
        sts128(z, 0u, 0u, 0u, 0u); sts128(z + SIG, 0u, 0u, 0u, 0u);
        if (t < 72) {
          const uint32_t zu = work + SIG_U + (t & 7) * U_LBO + (t >> 3) * 16;
          sts128(zu, 0u, 0u, 0u, 0u); sts128(zu + SIG, 0u, 0u, 0u, 0u);
        }
        const uint4* src = p.s->xnT + (size_t)pair * 512 + t;
#pragma unroll 1
        for (int it = 0; it < RETRY_MAX; it++) {
          uint32_t bad = 0;
#pragma unroll
          for (int q = 0; q < 4; q++) bad |= (((v[q].x ^ ep1) | (v[q].y ^ ep1) | (v[q].z ^ ep1) | (v[q].w ^ ep1)) & 1) << q;
          const unsigned m = __ballot_sync(0xffffffffu, bad);
          if (!m) break;
          if (lane == __ffs(m) - 1) poll_tag((const unsigned*)(src + (__ffs(bad) - 1) * 128) + 3, ep1);
          __syncwarp();
#pragma unroll
          for (int q = 0; q < 4; q++) v[q] = ld_relaxed4(src + q * 128);
        }
        TSTAMP(5);
        const uint32_t a = work + ((t >> 1) & 1) * SIG + SIG_U + (2 * ((t >> 2) & 3) + (t & 1)) * U_LBO + ((t >> 4) + 9) * 16;
#pragma unroll
        for (int q = 0; q < 4; q++) sts128(a + q * 128, v[q].x & ~1u, v[q].y & ~1u, v[q].z & ~1u, v[q].w & ~1u);
        bar_sync(4 + wg, 128);
#pragma unroll 1
        for (int k = w; k < 6; k += 4) sig_windows(work + (k & 1) * SIG, (k >> 1) * 32 + lane);
        fence_async();
        if (pi == 0 && tid == 256 + 96) {
          red_release(&p.s->cntA);
          if (!is_ssm) {
            bulk_s2g(p.s->tbl + b * (TBL / 16), sb + OFF_T + 2 * TBL, TBL);
            bulk_commit();
            asm volatile("cp.async.bulk.prefetch.L2.global [%0], %1;" ::"l"(p.w2 + (size_t)(256 * rk + 16 * G) * D_), "r"(16 * D_ * 2) : "memory");
            wait_count(&p.s->cntA, ep1 * NCTA);
            if (b == 0) *(volatile unsigned*)&p.s->epoch = ep1;
            asm volatile("fence.proxy.async;" ::: "memory");
            mbar_expect(bar0 + 8 * 3, 2048 + 8192 + 512);
            bulk_g2s(sb + OFF_B + B_AX, p.s->ax + 128 * G, 2048, bar0 + 8 * 3);
            bulk_g2s(sb + OFF_B + B_BX, p.s->bx + 512 * rk, 8192, bar0 + 8 * 3);
            bulk_g2s(sb + OFF_B + B_R, p.s->r + 128 * G, 512, bar0 + 8 * 3);
            bulk_wait0();
            red_release(&p.s->cntT);
          }
        }
        if (pi == 1) mbar_wait(bar0 + 8 * wg, 0);
        TSTAMP(6);
        bar_sync(is_ssm ? 4 + wg : 3, is_ssm ? 128 : 384);
        TSTAMP(7);
      }
      uint32_t keep[8];
      float res[16];
#pragma unroll 1
      for (int c = 0; c < 2; c++) {
        IDS
        const int wgu = __shfl_sync(0xffffffffu, wg, 0);
        const uint32_t work = is_ssm ? sb + S_WORK + wgu * S_WGB : sb + OFF_A;
        const uint32_t tbl = (is_ssm ? sb + (4 * wgu + 2 * pi) * TBL : sb + OFF_T) + c * TBL;
        conv_channel(tbl, work + c * SIG, is_ssm ? work + 2 * SIG + Y3B : sb + OFF_B, work + 2 * SIG, lds32f(tbl + TBL_SC), w, lane, 4 + wgu, res, 16 + 3 * (2 * pi + c));
        const float os = lds32f(tbl + TBL_SC + 4);
        if (c == 0) {
#pragma unroll
          for (int i = 0; i < 8; i++) keep[i] = pack_bf2(res[2 * i] * os, res[2 * i + 1] * os);
        } else {
          const int pair = !is_ssm ? b : (pi == 0 ? 112 + 3 * (b - NMLP) : (b < NMLP + 12 ? 172 + 3 * (b - NMLP) : 184 + 2 * (b - NMLP))) + wg;
          uint4* dst = p.s->s2 + ((size_t)(lane & 3) * 224 + pair) * 32 + w * 8 + (lane >> 2);
          const uint32_t tag = lds32(ms + M_EP) & 1;
#pragma unroll
          for (int nt = 0; nt < 4; nt++) {
            const uint32_t n0 = pack_bf2(res[4 * nt] * os, res[4 * nt + 1] * os), n1 = pack_bf2(res[4 * nt + 2] * os, res[4 * nt + 3] * os);
            st_b128(dst + nt * 4 * 224 * 32, tag, __byte_perm(keep[2 * nt], n0, 0x5410), __byte_perm(keep[2 * nt + 1], n1, 0x5410),
                    __byte_perm(keep[2 * nt], n0, 0x7632), __byte_perm(keep[2 * nt + 1], n1, 0x7632));
          }
        }
      }
      TSTAMP(8 + pi);
      {
        IDS
        if (pi == 1 || !is_ssm || (b >= NMLP + 12 && wg == 2)) break;
        const uint4* src = p.s->xnT + (size_t)((b < NMLP + 12 ? 172 + 3 * (b - NMLP) : 184 + 2 * (b - NMLP)) + wg) * 512 + t;
#pragma unroll
        for (int q = 0; q < 4; q++) v[q] = ld_relaxed4(src + q * 128);
      }
    }
    if (!is_ssm) {
      IDS
      const uint32_t tag = lds32(ms + M_EP) & 1;
      float pre[64];
#pragma unroll
      for (int i = 0; i < 64; i++) pre[i] = 0.f;
#pragma unroll 1
      for (int s = 0; s < 4; s++) recv_part<8, 128>(p.s->part + ((size_t)b * 6 + s) * 1024 + t, tag, pre);
      bar_sync(6, 128);
#pragma unroll
      for (int i = 0; i < 16; i++)
        sts128(sb + OFF_A + ((2 * (i >> 2) + (i & 1)) * 256 + ((i >> 1) & 1) * 128 + t) * 16, __float_as_uint(pre[4 * i]),
               __float_as_uint(pre[4 * i + 1]), __float_as_uint(pre[4 * i + 2]), __float_as_uint(pre[4 * i + 3]));
      bar_arrive(2, 384);
      TSTAMP(12);
    }
    TSDUMP();
  } else {
    bar_arrive(1, 384);
    asm volatile("setmaxnreg.inc.sync.aligned.u32 192;");
    bar_sync(7, 384);
    uint32_t H[64];
    {
      float acc[128];
      float p0, q0, p1, q1;
      {
        IDS
        const int wgu = __shfl_sync(0xffffffffu, wg, 0);
        int sl = 0;
#pragma unroll 1
        for (int s = 0; s < 7; s++) {
          mbar_wait(bar0 + 8 * sl, (s >= 3 && s < 6));
          const uint64_t da = mkdesc(sb + OFF_X + sl * 16384 + wgu * 8192, 16, 1024, 1);
          const uint64_t db = mkdesc(sb + OFF_W + sl * 32768, 8192, 1024, 1);
          wg_fence();
#pragma unroll
          for (int k = 0; k < 4; k++) wg_ss_bf16_n256(acc, da + 2 * k, db + 128 * k, (s | k) != 0);
          wg_commit();
          wg_wait<1>();
          const int pl = sl == 0 ? 2 : sl - 1;
          sl = sl == 2 ? 0 : sl + 1;
          if (s > 0 && lane == 0 && last_release(ms + M_REL + 4 * s)) {
            mbar_expect(bar0 + 8 * pl, s == 5 ? 32768 : 49152);
            if (s < 5) tma_3d(sb + OFF_W + pl * 32768, &tm_w1, 0, 64 * mod7(kc0 + s + 2), 4 * rk, bar0 + 8 * pl);
            else tma_2d(sb + OFF_W + pl * 32768, &tm_w2, 64 * mod7(rk + s - 4), 256 * rk, bar0 + 8 * pl);
            if (s != 5) tma_2d(sb + OFF_X + pl * 16384, &tm_x, 64 * (s < 5 ? mod7(kc0 + s + 2) : rk), 128 * G, bar0 + 8 * pl);
          }
        }
        TSTAMP(9);
        mbar_wait(bar0 + 8 * 3, 0);
        wg_fence();
        wg_ss_bf16_n256k(acc, mkdesc(sb + OFF_B + B_AX + wgu * 1024, 0, 128, 0), mkdesc(sb + OFF_B + B_BX, 4096, 128, 0), 1);
        wg_commit();
        wg_wait<1>();
        if (lane == 0 && last_release(ms + M_REL + 4 * 7)) {
          mbar_expect(bar0, 65536);
#pragma unroll 1
          for (int c = 2; c < 4; c++) tma_2d(sb + (c - 2) * OFF_X, &tm_w2, 64 * mod7(rk + 1 + c), 256 * rk, bar0);
        }
        bar_arrive(3, 384);
        const float r0 = lds32f(sb + OFF_B + B_R + (16 * (tid >> 5) + (lane >> 2)) * 4);
        const float r1 = lds32f(sb + OFF_B + B_R + (16 * (tid >> 5) + (lane >> 2) + 8) * 4);
        p0 = 0.7978845608028654f * r0; q0 = 0.0356774081363001f * r0 * r0 * r0;
        p1 = 0.7978845608028654f * r1; q1 = 0.0356774081363001f * r1 * r1 * r1;
      }
      wg_wait<0>();
      fence_regs<128>(acc);
      TSTAMP(16);
      float hq[4];
#pragma unroll
      for (int i = 0; i < 64; i++) {
        const float pp = (i & 1) ? p1 : p0, qq = (i & 1) ? q1 : q0;
        const float a = acc[2 * i], c = acc[2 * i + 1];
        const float ta = tanhf_(a * fmaf(a * a, qq, pp)), tc = tanhf_(c * fmaf(c * c, qq, pp));
        if (i >= 2) H[i - 2] = pack_bf2v(hq[(i & 1) * 2], hq[(i & 1) * 2 + 1]);
        hq[(i & 1) * 2] = fmaf(a, ta, a); hq[(i & 1) * 2 + 1] = fmaf(c, tc, c);
      }
      H[62] = pack_bf2v(hq[0], hq[1]); H[63] = pack_bf2v(hq[2], hq[3]);
    }
    TSTAMP(3);
    float accA[32], accB[32];
    const uint32_t tag = lds32(ms + M_EP) & 1;
    auto issue2 = [&](int c, float* acc) {
      const uint32_t base = sb + ((0x0213021u >> (4 * c)) & 3) * 32768;
      if (c != 3) mbar_wait(bar0 + 8 * ((0x0210021u >> (4 * c)) & 3), (0x34 >> c) & 1);
      const uint64_t db = mkdesc(base, 8192, 1024, 1);
      wg_fence();
#pragma unroll
      for (int k = 0; k < 16; k++) wg_rs_bf16_n64(acc, H[4 * k], H[4 * k + 1], H[4 * k + 2], H[4 * k + 3], db + 128 * k, k != 0);
      wg_commit();
    };
    auto process = [&](int s, float* acc) {
      wg_wait<1>();
      fence_regs<32>(acc);
      const int tid = opaque(tid0);
      if (s < 3 && (tid & 31) == 0 && last_release(ms + M_REL + 4 * (8 + s))) {
        const int sl = (0x021u >> (4 * s)) & 3;
        mbar_expect(bar0 + 8 * sl, 32768);
        tma_2d(sb + sl * 32768, &tm_w2, 64 * mod7(mod7(rk + 5 + s)), 256 * rk, bar0 + 8 * sl);
      }
      send_part(p.s->part + ((size_t)(G * 7 + mod7(rk + 1 + s)) * 6 + s) * 1024 + tid, tag, acc);
      TSTAMP(10 + s);
    };
    issue2(0, accA);
#pragma unroll
    for (int s = 0; s < 6; s += 2) {
      issue2(s + 1, accB);
      process(s, accA);
      issue2(s + 2, accA);
      process(s + 1, accB);
    }
    TSTAMP(4);
    IDS
    const int g = lane >> 2, tq = lane & 3;
    uint32_t sw[16];
    {
      const uint4* sp = p.s->s2 + ((size_t)G * 224 + 32 * rk + tq) * 32 + w * 8 + g;
#pragma unroll 1
      for (int it = 0; it < RETRY_MAX; it++) {
        uint32_t bad = 0;
#pragma unroll
        for (int i = 0; i < 8; i++) {
          const uint4 v = ld_b128(sp + i * 4 * 32);
          bad |= ((v.x ^ tag) & 1) << i;
          sw[2 * i] = wg ? v.z : v.x; sw[2 * i + 1] = wg ? v.w : v.y;
        }
        const unsigned m = __ballot_sync(0xffffffffu, bad);
        if (!m) break;
        if (lane == __ffs(m) - 1) poll_tag((const unsigned*)(sp + (__ffs(bad) - 1) * 4 * 32), tag);
        __syncwarp();
      }
    }
    TSTAMP(5);
    uint32_t b2w[8];
#pragma unroll
    for (int i = 0; i < 8; i++) b2w[i] = __ldg((const uint32_t*)(p.b2 + 64 * rk) + 4 * i + tq);
    wg_wait<0>();
    fence_regs<32>(accA);
    TSTAMP(6);
    bar_sync(2, 384);
#pragma unroll
    for (int i = 0; i < 8; i++) {
      const uint4 v = lds128(sb + OFF_A + (i * 256 + tid) * 16);
      accA[4 * i] += __uint_as_float(v.x); accA[4 * i + 1] += __uint_as_float(v.y);
      accA[4 * i + 2] += __uint_as_float(v.z); accA[4 * i + 3] += __uint_as_float(v.w);
    }
    const uint32_t xa = sb + OFF_X + 2 * 16384 + (16 * (tid >> 5) + (lane & 15)) * 128;
    uint32_t xw[16];
#pragma unroll
    for (int q = 0; q < 4; q++) ldsm4(xa + (((2 * q + (lane >> 4)) ^ (lane & 7)) << 4), xw[4 * q], xw[4 * q + 1], xw[4 * q + 2], xw[4 * q + 3]);
    const float r0 = 0.5f * lds32f(sb + OFF_B + B_R + (16 * (tid >> 5) + g) * 4);
    const float r1 = 0.5f * lds32f(sb + OFF_B + B_R + (16 * (tid >> 5) + g + 8) * 4);
#pragma unroll 1
    for (int s = 4; s < 6; s++) recv_part<4, 256>(p.s->part + ((size_t)b * 6 + s) * 1024 + tid, tag, accA);
    TSTAMP(7);
#pragma unroll
    for (int k = 0; k < 16; k++) {
      const float rr = (k & 1) ? r1 : r0;
      const float o0 = fmaf(accA[2 * k], rr, bf_lo(b2w[k >> 1])), o1 = fmaf(accA[2 * k + 1], rr, bf_hi(b2w[k >> 1]));
      const float g0 = o0 * rcpf_(1.f + ex2f(o0 * -1.4426950408889634f)), g1 = o1 * rcpf_(1.f + ex2f(o1 * -1.4426950408889634f));
      xw[k] = pack_bf2(fmaf(bf_lo(sw[k]), g0, bf_lo(xw[k])), fmaf(bf_hi(sw[k]), g1, bf_hi(xw[k])));
    }
#pragma unroll
    for (int q = 0; q < 4; q++) stsm4(xa + (((2 * q + (lane >> 4)) ^ (lane & 7)) << 4), xw[4 * q], xw[4 * q + 1], xw[4 * q + 2], xw[4 * q + 3]);
    fence_async();
    __syncwarp();
    if (lane == 0) {
      tma_store_2d(&tm_out, sb + OFF_X + 2 * 16384 + (tid >> 5) * 2048, 64 * rk, 128 * G + 16 * (tid >> 5));
      bulk_commit();
      bulk_wait0_read();
    }
    TSTAMP(8);
    TSDUMP();
  }
}

typedef CUresult (*EncodeFn)(CUtensorMap*, CUtensorMapDataType, cuuint32_t, void*, const cuuint64_t*, const cuuint64_t*,
                             const cuuint32_t*, const cuuint32_t*, CUtensorMapInterleave, CUtensorMapSwizzle,
                             CUtensorMapL2promotion, CUtensorMapFloatOOBfill);

void make_map(EncodeFn fn, CUtensorMap* m, const void* ptr, int rank, const cuuint64_t* dims, const cuuint64_t* strides, const cuuint32_t* box) {
  const cuuint32_t es[3] = {1, 1, 1};
  fn(m, CU_TENSOR_MAP_DATA_TYPE_BFLOAT16, rank, const_cast<void*>(ptr), dims, strides, box, es, CU_TENSOR_MAP_INTERLEAVE_NONE,
     CU_TENSOR_MAP_SWIZZLE_128B, CU_TENSOR_MAP_L2_PROMOTION_L2_128B, CU_TENSOR_MAP_FLOAT_OOB_FILL_NONE);
}

}

extern "C" void kernel_launch(void* const* d_in, const int* in_sizes, int n_in, void* d_out, int out_size) {
  (void)in_sizes; (void)n_in; (void)out_size;
  void* fnp = nullptr;
  cudaDriverEntryPointQueryResult qr;
  cudaGetDriverEntryPoint("cuTensorMapEncodeTiled", &fnp, cudaEnableDefault, &qr);
  EncodeFn fn = (EncodeFn)fnp;
  Params p;
  p.x = (const __nv_bfloat16*)d_in[0];
  p.a_re = (const __nv_bfloat16*)d_in[1]; p.a_im = (const __nv_bfloat16*)d_in[2];
  p.b_re = (const __nv_bfloat16*)d_in[3]; p.b_im = (const __nv_bfloat16*)d_in[4];
  p.c_re = (const __nv_bfloat16*)d_in[5]; p.c_im = (const __nv_bfloat16*)d_in[6];
  p.log_dt = (const __nv_bfloat16*)d_in[7]; p.dskip = (const __nv_bfloat16*)d_in[8];
  p.w1 = (const __nv_bfloat16*)d_in[10]; p.b1 = (const __nv_bfloat16*)d_in[11];
  p.w2 = (const __nv_bfloat16*)d_in[12]; p.b2 = (const __nv_bfloat16*)d_in[13];
  void* sp = nullptr;
  cudaGetSymbolAddress(&sp, g_scr);
  p.s = (Scratch*)sp;
  CUtensorMap mx, mw1, mw2, mo;
  {
    const cuuint64_t dims[2] = {448, 2048}, str[1] = {896};
    const cuuint32_t box[2] = {64, 128}, boxo[2] = {64, 16};
    make_map(fn, &mx, p.x, 2, dims, str, box);
    make_map(fn, &mo, d_out, 2, dims, str, boxo);
  }
  {
    const cuuint64_t dims[3] = {64, 448, 28}, str[2] = {3584, 128};
    const cuuint32_t box[3] = {64, 64, 4};
    make_map(fn, &mw1, p.w1, 3, dims, str, box);
  }
  {
    const cuuint64_t dims[2] = {448, 1792}, str[1] = {896};
    const cuuint32_t box[2] = {64, 256};
    make_map(fn, &mw2, p.w2, 2, dims, str, box);
  }
  cudaFuncSetAttribute(fused_kernel, cudaFuncAttributeMaxDynamicSharedMemorySize, SMEM_BYTES);
  fused_kernel<<<NCTA, 384, SMEM_BYTES>>>(p, mx, mw1, mw2, mo);
}
```

```cpp
#include <cuda_runtime.h>
#include <cuda_bf16.h>
#include <cuda_fp16.h>
#include <cuda.h>
#include <stdint.h>

namespace {

constexpr int D_ = 448, NST = 256, F_ = 1792;
constexpr int NRK = 7, NMLP = 112, NCTA = 132;
constexpr int SPIN_MAX = 1 << 20, RETRY_MAX = 512;

struct Scratch {
  unsigned cntA, pad0[31], cntT, pad1[31], epoch, pad2[63];
  uint4 ax[2048];
  uint4 bx[7 * 512];
  uint4 tbl[112 * 329];
  uint4 xnT[224 * 512];
  uint4 s2[16 * 224 * 32];
  uint4 part[16 * 7 * 6 * 1024];
};
__device__ Scratch g_scr;
#define TSTAMP(i)
#define TSINIT()
#define TSDUMP()
extern __shared__ __align__(1024) uint8_t smem_raw[];

constexpr int TBL_SC = 5248, TBL = 5264;
constexpr int TBL_C1 = 2624;
constexpr int SIG = 19584;
constexpr int SIG_U = 0, U_LBO = 656, SIG_V3 = 6272, SIG_V5 = 10368, SIG_V7 = 13440, SIG_V9 = 15488, SIG_V2 = 17536;
constexpr int Y2B = 6528, Y3B = 4352;
constexpr int KREC = 160, KSTG = 32 * KREC;
constexpr int OFF_W = 0, OFF_X = 98304, OFF_A = 147456, OFF_B = OFF_A + 8 * KSTG + 2560, OFF_T = OFF_B + 4 * KSTG;
constexpr int OFF_M = OFF_T + 15872;
constexpr int B_AX = Y2B, B_BX = B_AX + 2048;
constexpr int M_BAR = 0, M_REL = 128, M_EP = 192, M_CSR = 256, M_LT = 1280, M_END = 1536;
constexpr int SMEM_BYTES = OFF_M + M_END + 384;
constexpr int S_WORK = 63232, S_WGB = 2 * SIG + Y2B + Y3B;
static_assert(S_WORK + 3 * S_WGB <= OFF_M && SMEM_BYTES <= 232448, "smem");

struct Params {
  const __nv_bfloat16 *x, *a_re, *a_im, *b_re, *b_im, *c_re, *c_im, *log_dt, *dskip, *w1, *b1, *w2, *b2;
  Scratch* s;
};

__device__ __forceinline__ int opaque(int x) { int v; asm volatile("mov.u32 %0, %1;" : "=r"(v) : "r"(x)); return v; }
__device__ __forceinline__ int rd_bid() { int v; asm volatile("mov.u32 %0, %%ctaid.x;" : "=r"(v)); return v; }
__device__ __forceinline__ uint32_t smem_u32(const void* p) { return (uint32_t)__cvta_generic_to_shared(p); }
__device__ __forceinline__ void mbar_init(uint32_t bar, int cnt) { asm volatile("mbarrier.init.shared::cta.b64 [%0], %1;" ::"r"(bar), "r"(cnt)); }
__device__ __forceinline__ void mbar_expect(uint32_t bar, uint32_t bytes) {
  asm volatile("mbarrier.arrive.expect_tx.shared::cta.b64 _, [%0], %1;" ::"r"(bar), "r"(bytes) : "memory");
}
__device__ __forceinline__ void mbar_wait(uint32_t bar, uint32_t parity) {
  uint32_t done = 0;
#pragma unroll 1
  for (int it = 0; it < SPIN_MAX; it++) {
    asm volatile("{.reg .pred p; mbarrier.try_wait.parity.shared::cta.b64 p, [%1], %2; selp.u32 %0,1,0,p;}"
                 : "=r"(done) : "r"(bar), "r"(parity) : "memory");
    if (done) break;
  }
}
__device__ __forceinline__ void tma_2d(uint32_t dst, const CUtensorMap* m, int c0, int c1, uint32_t bar) {
  asm volatile("cp.async.bulk.tensor.2d.shared::cluster.global.mbarrier::complete_tx::bytes [%0], [%1, {%3, %4}], [%2];"
               ::"r"(dst), "l"(m), "r"(bar), "r"(c0), "r"(c1) : "memory");
}
__device__ __forceinline__ void tma_3d(uint32_t dst, const CUtensorMap* m, int c0, int c1, int c2, uint32_t bar) {
  asm volatile("cp.async.bulk.tensor.3d.shared::cluster.global.mbarrier::complete_tx::bytes [%0], [%1, {%3, %4, %5}], [%2];"
               ::"r"(dst), "l"(m), "r"(bar), "r"(c0), "r"(c1), "r"(c2) : "memory");
}
__device__ __forceinline__ void tma_store_2d(const CUtensorMap* m, uint32_t src, int c0, int c1) {
  asm volatile("cp.async.bulk.tensor.2d.global.shared::cta.bulk_group [%0, {%2, %3}], [%1];"
               ::"l"(m), "r"(src), "r"(c0), "r"(c1) : "memory");
}
__device__ __forceinline__ void bulk_s2g(void* dst, uint32_t src, uint32_t bytes) {
  asm volatile("cp.async.bulk.global.shared::cta.bulk_group [%0], [%1], %2;" ::"l"(dst), "r"(src), "r"(bytes) : "memory");
}
__device__ __forceinline__ void bulk_g2s(uint32_t dst, const void* src, uint32_t bytes, uint32_t bar) {
  asm volatile("cp.async.bulk.shared::cluster.global.mbarrier::complete_tx::bytes [%0], [%1], %2, [%3];"
               ::"r"(dst), "l"(src), "r"(bytes), "r"(bar) : "memory");
}
__device__ __forceinline__ void bulk_commit() { asm volatile("cp.async.bulk.commit_group;" ::: "memory"); }
__device__ __forceinline__ void bulk_wait0() { asm volatile("cp.async.bulk.wait_group 0;" ::: "memory"); }
__device__ __forceinline__ void bulk_wait0_read() { asm volatile("cp.async.bulk.wait_group.read 0;" ::: "memory"); }
__device__ __forceinline__ void fence_async() { asm volatile("fence.proxy.async.shared::cta;" ::: "memory"); }
__device__ __forceinline__ void bar_sync(int id, int n) { asm volatile("bar.sync %0, %1;" ::"r"(id), "r"(n) : "memory"); }
__device__ __forceinline__ void bar_arrive(int id, int n) { asm volatile("bar.arrive %0, %1;" ::"r"(id), "r"(n) : "memory"); }
__device__ __forceinline__ void wg_fence() { asm volatile("wgmma.fence.sync.aligned;" ::: "memory"); }
__device__ __forceinline__ void wg_commit() { asm volatile("wgmma.commit_group.sync.aligned;" ::: "memory"); }
template <int N> __device__ __forceinline__ void wg_wait() { asm volatile("wgmma.wait_group.sync.aligned %0;" ::"n"(N) : "memory"); }
template <int N> __device__ __forceinline__ void fence_regs(float* d) {
#pragma unroll
  for (int i = 0; i < N; i++) asm volatile("" : "+f"(d[i])::"memory");
}
__device__ __forceinline__ uint64_t mkdesc(uint32_t addr, uint32_t lbo, uint32_t sbo, uint32_t sw) {
  return (uint64_t)((addr & 0x3FFFF) >> 4) | ((uint64_t)(lbo >> 4) << 16) | ((uint64_t)(sbo >> 4) << 32) | ((uint64_t)sw << 62);
}
__device__ __forceinline__ uint32_t lds32(uint32_t a) { uint32_t v; asm volatile("ld.shared.b32 %0, [%1];" : "=r"(v) : "r"(a) : "memory"); return v; }
__device__ __forceinline__ float lds32f(uint32_t a) { float v; asm volatile("ld.shared.f32 %0, [%1];" : "=f"(v) : "r"(a) : "memory"); return v; }
__device__ __forceinline__ float2 lds64f(uint32_t a) { float2 v; asm volatile("ld.shared.v2.f32 {%0,%1}, [%2];" : "=f"(v.x), "=f"(v.y) : "r"(a) : "memory"); return v; }
__device__ __forceinline__ uint4 lds128(uint32_t a) {
  uint4 v; asm volatile("ld.shared.v4.b32 {%0,%1,%2,%3}, [%4];" : "=r"(v.x), "=r"(v.y), "=r"(v.z), "=r"(v.w) : "r"(a) : "memory"); return v;
}
__device__ __forceinline__ void sts16(uint32_t a, uint16_t v) { asm volatile("st.shared.b16 [%0], %1;" ::"r"(a), "h"(v) : "memory"); }
__device__ __forceinline__ void sts32f(uint32_t a, float v) { asm volatile("st.shared.f32 [%0], %1;" ::"r"(a), "f"(v) : "memory"); }
__device__ __forceinline__ void sts64f(uint32_t a, float x, float y) { asm volatile("st.shared.v2.f32 [%0], {%1,%2};" ::"r"(a), "f"(x), "f"(y) : "memory"); }
__device__ __forceinline__ void sts128(uint32_t a, uint32_t x, uint32_t y, uint32_t z, uint32_t w) {
  asm volatile("st.shared.v4.b32 [%0], {%1,%2,%3,%4};" ::"r"(a), "r"(x), "r"(y), "r"(z), "r"(w) : "memory");
}
__device__ __forceinline__ void ldsm4(uint32_t a, uint32_t& r0, uint32_t& r1, uint32_t& r2, uint32_t& r3) {
  asm volatile("ldmatrix.sync.aligned.m8n8.x4.shared.b16 {%0,%1,%2,%3}, [%4];" : "=r"(r0), "=r"(r1), "=r"(r2), "=r"(r3) : "r"(a) : "memory");
}
__device__ __forceinline__ void ldsm4t(uint32_t a, uint32_t& r0, uint32_t& r1, uint32_t& r2, uint32_t& r3) {
  asm volatile("ldmatrix.sync.aligned.m8n8.x4.trans.shared.b16 {%0,%1,%2,%3}, [%4];" : "=r"(r0), "=r"(r1), "=r"(r2), "=r"(r3) : "r"(a) : "memory");
}
__device__ __forceinline__ void ldsm2t(uint32_t a, uint32_t& r0, uint32_t& r1) {
  asm volatile("ldmatrix.sync.aligned.m8n8.x2.trans.shared.b16 {%0,%1}, [%2];" : "=r"(r0), "=r"(r1) : "r"(a) : "memory");
}
__device__ __forceinline__ void stsm4(uint32_t a, uint32_t r0, uint32_t r1, uint32_t r2, uint32_t r3) {
  asm volatile("stmatrix.sync.aligned.m8n8.x4.shared.b16 [%0], {%1,%2,%3,%4};" ::"r"(a), "r"(r0), "r"(r1), "r"(r2), "r"(r3) : "memory");
}
__device__ __forceinline__ void mma_f16(float* c, uint32_t a0, uint32_t a1, uint32_t a2, uint32_t a3, uint32_t b0, uint32_t b1) {
  asm("mma.sync.aligned.m16n8k16.row.col.f32.f16.f16.f32 {%0,%1,%2,%3},{%4,%5,%6,%7},{%8,%9},{%0,%1,%2,%3};"
               : "+f"(c[0]), "+f"(c[1]), "+f"(c[2]), "+f"(c[3]) : "r"(a0), "r"(a1), "r"(a2), "r"(a3), "r"(b0), "r"(b1));
}
__device__ __forceinline__ uint4 ld_relaxed4(const void* p) {
  uint4 v; asm volatile("ld.relaxed.gpu.global.v4.b32 {%0,%1,%2,%3}, [%4];" : "=r"(v.x), "=r"(v.y), "=r"(v.z), "=r"(v.w) : "l"(p) : "memory"); return v;
}
__device__ __forceinline__ uint4 ld_2x64(const void* p) {
  uint4 v;
  asm volatile("{.reg .b64 a, c; ld.relaxed.gpu.global.v2.b64 {a, c}, [%4]; mov.b64 {%0,%1}, a; mov.b64 {%2,%3}, c;}"
               : "=r"(v.x), "=r"(v.y), "=r"(v.z), "=r"(v.w) : "l"(p) : "memory");
  return v;
}
__device__ __forceinline__ void st_relaxed2(void* p, uint32_t x, uint32_t y) {
  asm volatile("st.relaxed.gpu.global.v2.b32 [%0], {%1,%2};" ::"l"(p), "r"(x), "r"(y) : "memory");
}
__device__ __forceinline__ uint4 ld_b128(const void* p) {
  uint4 v;
  asm volatile("{.reg .b128 t; .reg .b64 a, c; ld.relaxed.gpu.global.b128 t, [%4]; mov.b128 {a, c}, t; mov.b64 {%0,%1}, a; mov.b64 {%2,%3}, c;}"
               : "=r"(v.x), "=r"(v.y), "=r"(v.z), "=r"(v.w) : "l"(p) : "memory");
  return v;
}
__device__ __forceinline__ void st_b128(void* p, uint32_t tag, uint32_t x, uint32_t y, uint32_t z, uint32_t w) {
  asm volatile("{.reg .b128 t; .reg .b64 a, c; mov.b64 a, {%1,%2}; mov.b64 c, {%3,%4}; mov.b128 t, {a, c}; st.relaxed.gpu.global.b128 [%0], t;}"
               ::"l"(p), "r"((x & ~1u) | tag), "r"(y), "r"(z), "r"(w) : "memory");
}
__device__ __forceinline__ unsigned ld_relaxed1(const unsigned* p) {
  unsigned v; asm volatile("ld.relaxed.gpu.global.u32 %0, [%1];" : "=r"(v) : "l"(p) : "memory"); return v;
}
__device__ __forceinline__ void red_relaxed(unsigned* p) {
  asm volatile("red.relaxed.gpu.global.add.u32 [%0], 1;" ::"l"(p) : "memory");
}
__device__ __forceinline__ void red_release(unsigned* p) {
  asm volatile("red.release.gpu.global.add.u32 [%0], 1;" ::"l"(p) : "memory");
}
__device__ __forceinline__ void wait_count(const unsigned* p, unsigned target) {
#pragma unroll 1
  for (int it = 0; it < SPIN_MAX; it++) {
    if ((int)(ld_relaxed1(p) - target) >= 0) break;
    __nanosleep(40);
  }
  asm volatile("fence.acq_rel.gpu;" ::: "memory");
}
__device__ __forceinline__ uint32_t pack_h2(float lo, float hi) { uint32_t r; asm("cvt.rn.f16x2.f32 %0, %1, %2;" : "=r"(r) : "f"(hi), "f"(lo)); return r; }
__device__ __forceinline__ uint32_t pack_bf2(float lo, float hi) { uint32_t r; asm("cvt.rn.bf16x2.f32 %0, %1, %2;" : "=r"(r) : "f"(hi), "f"(lo)); return r; }
__device__ __forceinline__ uint32_t pack_bf2v(float lo, float hi) { uint32_t r; asm volatile("cvt.rn.bf16x2.f32 %0, %1, %2;" : "=r"(r) : "f"(hi), "f"(lo)); return r; }
__device__ __forceinline__ float bf_lo(uint32_t w) { return __uint_as_float(w << 16); }
__device__ __forceinline__ float bf_hi(uint32_t w) { return __uint_as_float(w & 0xffff0000u); }
__device__ __forceinline__ float rbf(float v) { return __bfloat162float(__float2bfloat16_rn(v)); }
__device__ __forceinline__ float2 h2f(uint32_t w) { return __half22float2(*reinterpret_cast<__half2*>(&w)); }
__device__ __forceinline__ float ex2f(float v) { float r; asm("ex2.approx.ftz.f32 %0, %1;" : "=f"(r) : "f"(v)); return r; }
__device__ __forceinline__ float rcpf_(float v) { float r; asm("rcp.approx.f32 %0, %1;" : "=f"(r) : "f"(v)); return r; }
__device__ __forceinline__ float sqrtf_(float v) { float r; asm("sqrt.approx.f32 %0, %1;" : "=f"(r) : "f"(v)); return r; }
__device__ __forceinline__ float tanhf_(float v) { float r; asm volatile("tanh.approx.f32 %0, %1;" : "=f"(r) : "f"(v)); return r; }

__device__ __forceinline__ void wg_ss_bf16_n256(float* d, uint64_t da, uint64_t db, int sc) {
  asm volatile("{.reg .pred p; setp.ne.b32 p, %130, 0;\n"
    "wgmma.mma_async.sync.aligned.m64n256k16.f32.bf16.bf16 {%0, %1, %2, %3, %4, %5, %6, %7, %8, %9, %10, %11, %12, %13, %14, %15, %16, %17, %18, %19, %20, %21, %22, %23, %24, %25, %26, %27, %28, %29, %30, %31, %32, %33, %34, %35, %36, %37, %38, %39, %40, %41, %42, %43, %44, %45, %46, %47, %48, %49, %50, %51, %52, %53, %54, %55, %56, %57, %58, %59, %60, %61, %62, %63, %64, %65, %66, %67, %68, %69, %70, %71, %72, %73, %74, %75, %76, %77, %78, %79, %80, %81, %82, %83, %84, %85, %86, %87, %88, %89, %90, %91, %92, %93, %94, %95, %96, %97, %98, %99, %100, %101, %102, %103, %104, %105, %106, %107, %108, %109, %110, %111, %112, %113, %114, %115, %116, %117, %118, %119, %120, %121, %122, %123, %124, %125, %126, %127}, %128, %129, p, 1, 1, 0, 1;}\n"
    : "+f"(d[0]), "+f"(d[1]), "+f"(d[2]), "+f"(d[3]), "+f"(d[4]), "+f"(d[5]), "+f"(d[6]), "+f"(d[7]), "+f"(d[8]), "+f"(d[9]), "+f"(d[10]), "+f"(d[11]), "+f"(d[12]), "+f"(d[13]), "+f"(d[14]), "+f"(d[15]), "+f"(d[16]), "+f"(d[17]), "+f"(d[18]), "+f"(d[19]), "+f"(d[20]), "+f"(d[21]), "+f"(d[22]), "+f"(d[23]), "+f"(d[24]), "+f"(d[25]), "+f"(d[26]), "+f"(d[27]), "+f"(d[28]), "+f"(d[29]), "+f"(d[30]), "+f"(d[31]), "+f"(d[32]), "+f"(d[33]), "+f"(d[34]), "+f"(d[35]), "+f"(d[36]), "+f"(d[37]), "+f"(d[38]), "+f"(d[39]), "+f"(d[40]), "+f"(d[41]), "+f"(d[42]), "+f"(d[43]), "+f"(d[44]), "+f"(d[45]), "+f"(d[46]), "+f"(d[47]), "+f"(d[48]), "+f"(d[49]), "+f"(d[50]), "+f"(d[51]), "+f"(d[52]), "+f"(d[53]), "+f"(d[54]), "+f"(d[55]), "+f"(d[56]), "+f"(d[57]), "+f"(d[58]), "+f"(d[59]), "+f"(d[60]), "+f"(d[61]), "+f"(d[62]), "+f"(d[63]), "+f"(d[64]), "+f"(d[65]), "+f"(d[66]), "+f"(d[67]), "+f"(d[68]), "+f"(d[69]), "+f"(d[70]), "+f"(d[71]), "+f"(d[72]), "+f"(d[73]), "+f"(d[74]), "+f"(d[75]), "+f"(d[76]), "+f"(d[77]), "+f"(d[78]), "+f"(d[79]), "+f"(d[80]), "+f"(d[81]), "+f"(d[82]), "+f"(d[83]), "+f"(d[84]), "+f"(d[85]), "+f"(d[86]), "+f"(d[87]), "+f"(d[88]), "+f"(d[89]), "+f"(d[90]), "+f"(d[91]), "+f"(d[92]), "+f"(d[93]), "+f"(d[94]), "+f"(d[95]), "+f"(d[96]), "+f"(d[97]), "+f"(d[98]), "+f"(d[99]), "+f"(d[100]), "+f"(d[101]), "+f"(d[102]), "+f"(d[103]), "+f"(d[104]), "+f"(d[105]), "+f"(d[106]), "+f"(d[107]), "+f"(d[108]), "+f"(d[109]), "+f"(d[110]), "+f"(d[111]), "+f"(d[112]), "+f"(d[113]), "+f"(d[114]), "+f"(d[115]), "+f"(d[116]), "+f"(d[117]), "+f"(d[118]), "+f"(d[119]), "+f"(d[120]), "+f"(d[121]), "+f"(d[122]), "+f"(d[123]), "+f"(d[124]), "+f"(d[125]), "+f"(d[126]), "+f"(d[127])
    : "l"(da), "l"(db), "r"(sc));
}

__device__ __forceinline__ void wg_ss_bf16_n256k(float* d, uint64_t da, uint64_t db, int sc) {
  asm volatile("{.reg .pred p; setp.ne.b32 p, %130, 0;\n"
    "wgmma.mma_async.sync.aligned.m64n256k16.f32.bf16.bf16 {%0, %1, %2, %3, %4, %5, %6, %7, %8, %9, %10, %11, %12, %13, %14, %15, %16, %17, %18, %19, %20, %21, %22, %23, %24, %25, %26, %27, %28, %29, %30, %31, %32, %33, %34, %35, %36, %37, %38, %39, %40, %41, %42, %43, %44, %45, %46, %47, %48, %49, %50, %51, %52, %53, %54, %55, %56, %57, %58, %59, %60, %61, %62, %63, %64, %65, %66, %67, %68, %69, %70, %71, %72, %73, %74, %75, %76, %77, %78, %79, %80, %81, %82, %83, %84, %85, %86, %87, %88, %89, %90, %91, %92, %93, %94, %95, %96, %97, %98, %99, %100, %101, %102, %103, %104, %105, %106, %107, %108, %109, %110, %111, %112, %113, %114, %115, %116, %117, %118, %119, %120, %121, %122, %123, %124, %125, %126, %127}, %128, %129, p, 1, 1, 0, 0;}\n"
    : "+f"(d[0]), "+f"(d[1]), "+f"(d[2]), "+f"(d[3]), "+f"(d[4]), "+f"(d[5]), "+f"(d[6]), "+f"(d[7]), "+f"(d[8]), "+f"(d[9]), "+f"(d[10]), "+f"(d[11]), "+f"(d[12]), "+f"(d[13]), "+f"(d[14]), "+f"(d[15]), "+f"(d[16]), "+f"(d[17]), "+f"(d[18]), "+f"(d[19]), "+f"(d[20]), "+f"(d[21]), "+f"(d[22]), "+f"(d[23]), "+f"(d[24]), "+f"(d[25]), "+f"(d[26]), "+f"(d[27]), "+f"(d[28]), "+f"(d[29]), "+f"(d[30]), "+f"(d[31]), "+f"(d[32]), "+f"(d[33]), "+f"(d[34]), "+f"(d[35]), "+f"(d[36]), "+f"(d[37]), "+f"(d[38]), "+f"(d[39]), "+f"(d[40]), "+f"(d[41]), "+f"(d[42]), "+f"(d[43]), "+f"(d[44]), "+f"(d[45]), "+f"(d[46]), "+f"(d[47]), "+f"(d[48]), "+f"(d[49]), "+f"(d[50]), "+f"(d[51]), "+f"(d[52]), "+f"(d[53]), "+f"(d[54]), "+f"(d[55]), "+f"(d[56]), "+f"(d[57]), "+f"(d[58]), "+f"(d[59]), "+f"(d[60]), "+f"(d[61]), "+f"(d[62]), "+f"(d[63]), "+f"(d[64]), "+f"(d[65]), "+f"(d[66]), "+f"(d[67]), "+f"(d[68]), "+f"(d[69]), "+f"(d[70]), "+f"(d[71]), "+f"(d[72]), "+f"(d[73]), "+f"(d[74]), "+f"(d[75]), "+f"(d[76]), "+f"(d[77]), "+f"(d[78]), "+f"(d[79]), "+f"(d[80]), "+f"(d[81]), "+f"(d[82]), "+f"(d[83]), "+f"(d[84]), "+f"(d[85]), "+f"(d[86]), "+f"(d[87]), "+f"(d[88]), "+f"(d[89]), "+f"(d[90]), "+f"(d[91]), "+f"(d[92]), "+f"(d[93]), "+f"(d[94]), "+f"(d[95]), "+f"(d[96]), "+f"(d[97]), "+f"(d[98]), "+f"(d[99]), "+f"(d[100]), "+f"(d[101]), "+f"(d[102]), "+f"(d[103]), "+f"(d[104]), "+f"(d[105]), "+f"(d[106]), "+f"(d[107]), "+f"(d[108]), "+f"(d[109]), "+f"(d[110]), "+f"(d[111]), "+f"(d[112]), "+f"(d[113]), "+f"(d[114]), "+f"(d[115]), "+f"(d[116]), "+f"(d[117]), "+f"(d[118]), "+f"(d[119]), "+f"(d[120]), "+f"(d[121]), "+f"(d[122]), "+f"(d[123]), "+f"(d[124]), "+f"(d[125]), "+f"(d[126]), "+f"(d[127])
    : "l"(da), "l"(db), "r"(sc));
}

__device__ __forceinline__ void wg_rs_bf16_n64(float* d, uint32_t a0, uint32_t a1, uint32_t a2, uint32_t a3, uint64_t db, int sc) {
  asm volatile("{.reg .pred p; setp.ne.b32 p, %37, 0;\n"
    "wgmma.mma_async.sync.aligned.m64n64k16.f32.bf16.bf16 {%0, %1, %2, %3, %4, %5, %6, %7, %8, %9, %10, %11, %12, %13, %14, %15, %16, %17, %18, %19, %20, %21, %22, %23, %24, %25, %26, %27, %28, %29, %30, %31}, {%32,%33,%34,%35}, %36, p, 1, 1, 1;}\n"
    : "+f"(d[0]), "+f"(d[1]), "+f"(d[2]), "+f"(d[3]), "+f"(d[4]), "+f"(d[5]), "+f"(d[6]), "+f"(d[7]), "+f"(d[8]), "+f"(d[9]), "+f"(d[10]), "+f"(d[11]), "+f"(d[12]), "+f"(d[13]), "+f"(d[14]), "+f"(d[15]), "+f"(d[16]), "+f"(d[17]), "+f"(d[18]), "+f"(d[19]), "+f"(d[20]), "+f"(d[21]), "+f"(d[22]), "+f"(d[23]), "+f"(d[24]), "+f"(d[25]), "+f"(d[26]), "+f"(d[27]), "+f"(d[28]), "+f"(d[29]), "+f"(d[30]), "+f"(d[31])
    : "r"(a0), "r"(a1), "r"(a2), "r"(a3), "l"(db), "r"(sc));
}

__device__ __forceinline__ void wg_rs_f16_n32k(float* d, uint32_t a0, uint32_t a1, uint32_t a2, uint32_t a3, uint64_t db, int sc) {
  asm volatile("{.reg .pred p; setp.ne.b32 p, %21, 0;\n"
    "wgmma.mma_async.sync.aligned.m64n32k16.f32.f16.f16 {%0, %1, %2, %3, %4, %5, %6, %7, %8, %9, %10, %11, %12, %13, %14, %15}, {%16,%17,%18,%19}, %20, p, 1, 1, 0;}\n"
    : "+f"(d[0]), "+f"(d[1]), "+f"(d[2]), "+f"(d[3]), "+f"(d[4]), "+f"(d[5]), "+f"(d[6]), "+f"(d[7]), "+f"(d[8]), "+f"(d[9]), "+f"(d[10]), "+f"(d[11]), "+f"(d[12]), "+f"(d[13]), "+f"(d[14]), "+f"(d[15])
    : "r"(a0), "r"(a1), "r"(a2), "r"(a3), "l"(db), "r"(sc));
}

__device__ __forceinline__ void wg_rs_f16_n24t(float* d, uint32_t a0, uint32_t a1, uint32_t a2, uint32_t a3, uint64_t db, int sc) {
  asm volatile("{.reg .pred p; setp.ne.b32 p, %17, 0;\n"
    "wgmma.mma_async.sync.aligned.m64n24k16.f32.f16.f16 {%0, %1, %2, %3, %4, %5, %6, %7, %8, %9, %10, %11}, {%12,%13,%14,%15}, %16, p, 1, 1, 1;}\n"
    : "+f"(d[0]), "+f"(d[1]), "+f"(d[2]), "+f"(d[3]), "+f"(d[4]), "+f"(d[5]), "+f"(d[6]), "+f"(d[7]), "+f"(d[8]), "+f"(d[9]), "+f"(d[10]), "+f"(d[11])
    : "r"(a0), "r"(a1), "r"(a2), "r"(a3), "l"(db), "r"(sc));
}

__device__ __forceinline__ void wg_rs_f16_n16t(float* d, uint32_t a0, uint32_t a1, uint32_t a2, uint32_t a3, uint64_t db, int sc) {
  asm volatile("{.reg .pred p; setp.ne.b32 p, %13, 0;\n"
    "wgmma.mma_async.sync.aligned.m64n16k16.f32.f16.f16 {%0, %1, %2, %3, %4, %5, %6, %7}, {%8,%9,%10,%11}, %12, p, 1, 1, 1;}\n"
    : "+f"(d[0]), "+f"(d[1]), "+f"(d[2]), "+f"(d[3]), "+f"(d[4]), "+f"(d[5]), "+f"(d[6]), "+f"(d[7])
    : "r"(a0), "r"(a1), "r"(a2), "r"(a3), "l"(db), "r"(sc));
}

struct cf { float x, y; };
__device__ __forceinline__ cf cmul(cf a, cf b) { cf r; r.x = fmaf(a.x, b.x, -a.y * b.y); r.y = fmaf(a.x, b.y, a.y * b.x); return r; }
__device__ __forceinline__ cf zpow(float rho2, float phi, float e) {
  const float m = ex2f(rho2 * e), ang = phi * e;
  cf r; r.x = m * __cosf(ang); r.y = m * __sinf(ang); return r;
}
__device__ __forceinline__ __half2 H2(uint32_t v) { return *reinterpret_cast<__half2*>(&v); }
__device__ __forceinline__ uint32_t U32(__half2 v) { return *reinterpret_cast<uint32_t*>(&v); }
__device__ __forceinline__ uint32_t hprod(uint32_t v, uint32_t r, uint32_t rr) {
  return U32(__hfma2(__high2half2(H2(v)), H2(rr), __hmul2(__low2half2(H2(v)), H2(r))));
}
template <bool CONJ>
__device__ __forceinline__ void hprod2(uint32_t re, uint32_t im, uint32_t r, uint32_t& ore, uint32_t& oim) {
  const __half2 rx = __low2half2(H2(r)), ry = __high2half2(H2(r));
  if (CONJ) {
    ore = U32(__hfma2(H2(re), rx, __hmul2(H2(im), ry)));
    oim = U32(__hfma2(H2(im), rx, __hneg2(__hmul2(H2(re), ry))));
  } else {
    ore = U32(__hfma2(H2(re), rx, __hneg2(__hmul2(H2(im), ry))));
    oim = U32(__hfma2(H2(re), ry, __hmul2(H2(im), rx)));
  }
}
__device__ __forceinline__ cf csq(cf a) { cf r; r.x = fmaf(a.x, a.x, -a.y * a.y); r.y = (a.x + a.x) * a.y; return r; }
__device__ __forceinline__ cf cmulc(cf a, cf b) { cf r; r.x = fmaf(a.x, b.x, a.y * b.y); r.y = fmaf(a.y, b.x, -a.x * b.y); return r; }
__device__ __forceinline__ uint32_t pk(cf a) { return pack_h2(a.x, a.y); }
__device__ __forceinline__ uint32_t ldg32(const void* p, int o) { uint32_t v; asm volatile("ld.global.nc.b32 %0, [%1];" : "=r"(v) : "l"((const char*)p + o)); return v; }
__device__ __forceinline__ uint32_t rot90(uint32_t v) { return __byte_perm(v, 0, 0x1032) ^ 0x00008000u; }
__device__ __forceinline__ uint32_t hadd2u(uint32_t a, uint32_t b) { return U32(__hadd2(H2(a), H2(b))); }

struct KgIn { uint32_t cur[6], nxt[6], ldt, dk; bool odd; };
__device__ __forceinline__ float pow2_floor(float v) { return __uint_as_float(__float_as_uint(fminf(fmaxf(v, 1e-30f), 1e30f)) & 0x7f800000u); }
__device__ __forceinline__ void kgen_mma(float* acc, const uint32_t (*A)[4], const uint32_t (*B)[6], int csrc) {
#pragma unroll
  for (int ks = 0; ks < 4; ks++) {
    const uint32_t rl = __shfl_sync(0xffffffffu, B[ks][4], csrc), rh = __shfl_sync(0xffffffffu, B[ks][5], csrc);
    const uint32_t rlr = rot90(rl), rhr = rot90(rh);
    mma_f16(acc + 0, A[ks][0], A[ks][1], A[ks][2], A[ks][3], B[ks][0], B[ks][1]);
    mma_f16(acc + 4, A[ks][0], A[ks][1], A[ks][2], A[ks][3], B[ks][2], B[ks][3]);
    mma_f16(acc + 8, A[ks][0], A[ks][1], A[ks][2], A[ks][3], B[ks][4], B[ks][5]);
    const uint32_t c0 = hprod(A[ks][0], rl, rlr), c1 = hprod(A[ks][1], rl, rlr);
    const uint32_t c2 = hprod(A[ks][2], rh, rhr), c3 = hprod(A[ks][3], rh, rhr);
    mma_f16(acc + 12, c0, c1, c2, c3, B[ks][0], B[ks][1]);
    mma_f16(acc + 16, c0, c1, c2, c3, B[ks][2], B[ks][3]);
    mma_f16(acc + 20, c0, c1, c2, c3, B[ks][4], B[ks][5]);
  }
}
__device__ __forceinline__ void kgen_warp(KgIn& k, int nw, uint32_t stg, uint32_t tbl, int lane) {
  float dl, dt, sc, inv_sc;
  {
    const uint32_t M = 0x7fff7fffu;
    uint32_t mx[2];
#pragma unroll
    for (int i = 0; i < 2; i++) {
      const uint32_t m = __vmaxu2(__vmaxu2(k.cur[2 + 2 * i] & M, k.cur[3 + 2 * i] & M), __vmaxu2(k.nxt[2 + 2 * i] & M, k.nxt[3 + 2 * i] & M));
      mx[i] = __reduce_max_sync(0xffffffffu, max(m << 16, m & 0xffff0000u));
    }
    dt = rbf(ex2f((k.odd ? bf_hi(k.ldt) : bf_lo(k.ldt)) * 1.4426950408889634f));
    sc = pow2_floor(0.125f * __uint_as_float(mx[0]) * __uint_as_float(mx[1]));
    inv_sc = rcpf_(sc);
    if (lane == 0) sts64f(tbl + TBL_SC + 8, dt, (k.odd ? bf_hi(k.dk) : bf_lo(k.dk)) * rcpf_(dt));
    dl = dt * 1.4426950408889634f;
  }
  const uint32_t st0 = stg + lane * KREC + (((lane >> 2) & 1) << 4), st1 = st0 ^ 16;
  const int mat = lane >> 3, rowi = lane & 7;
  const uint32_t ldB = stg + (4 * (mat & 1) + (rowi >> 1)) * KREC + ((((mat >> 1) * 2 + (rowi & 1)) << 4) ^ ((mat & 1) << 4));
  const uint32_t ldA = stg + (4 * (mat >> 1) + (rowi >> 1)) * KREC + ((((mat & 1) * 2 + (rowi & 1)) << 4) ^ ((mat >> 1) << 4)) + 96;
  const int csrc = 20 + (lane & 3);
  float acc[24];
  uint32_t B[4][6], A[4][4];
#pragma unroll
  for (int i = 0; i < 24; i++) { acc[i] = 0.f; B[i / 6][i % 6] = 0u; }
#pragma unroll
  for (int i = 0; i < 16; i++) A[i / 4][i % 4] = 0u;
#pragma unroll 1
  for (int it = 0; it < 2 * nw; it++) {
    const uint32_t sel = (it & 1) ? 0x3244u : 0x1044u;
    float v[6];
#pragma unroll
    for (int i = 0; i < 6; i++) { v[i] = __uint_as_float(__byte_perm(k.cur[i], 0, sel)); if (it == 1) k.cur[i] = k.nxt[i]; }
    const float rho2 = v[0] * dl, phi = v[1] * dt;
    const cf bb = {v[2] * inv_sc, v[3] * -inv_sc}, cc = {v[4], v[5]};
    const cf X0 = cmulc(bb, cc);
    const cf z1 = zpow(rho2, phi, 1.f), z64 = zpow(rho2, phi, 64.f);
    kgen_mma(acc, A, B, csrc);
    const cf z2 = csq(z1), z3 = cmul(z2, z1), z4 = csq(z2), z8 = csq(z4), z16 = csq(z8), z24 = cmul(z16, z8), z32 = csq(z16);
    const cf z128 = csq(z64), y1 = csq(z128), y2 = csq(y1), y3 = cmul(y2, y1), y4 = csq(y2);
    const cf X4 = cmulc(X0, z4), W4 = cmulc(X0, y4), W8 = cmulc(W4, y4);
    uint32_t re[4], im[4], r2[4], i2[4];
    re[0] = pack_h2(X0.x, X4.x); im[0] = pack_h2(X0.y, X4.y);
    hprod2<true>(re[0], im[0], pk(z1), re[1], im[1]);
    hprod2<true>(re[0], im[0], pk(z2), re[2], im[2]);
    hprod2<true>(re[0], im[0], pk(z3), re[3], im[3]);
    sts128(st0, re[0], re[1], re[2], re[3]);
    sts128(st1, im[0], im[1], im[2], im[3]);
    const uint32_t hy1 = pk(y1), hy2 = pk(y2);
    hprod2<true>(re[0], im[0], hy1, r2[0], i2[0]);
    hprod2<true>(re[2], im[2], hy1, r2[1], i2[1]);
    hprod2<true>(re[0], im[0], hy2, r2[2], i2[2]);
    hprod2<true>(re[0], im[0], pk(y3), r2[3], i2[3]);
    sts128(st0 + 32, r2[0], r2[1], r2[2], r2[3]);
    sts128(st1 + 32, i2[0], i2[1], i2[2], i2[3]);
    const cf W5 = cmulc(W4, y1);
    re[0] = pack_h2(W4.x, W5.x); im[0] = pack_h2(W4.y, W5.y);
    hprod2<true>(re[0], im[0], hy2, re[1], im[1]);
    sts128(st0 + 64, re[0], re[1], pack_h2(W8.x, z128.x), hy1);
    sts128(st1 + 64, im[0], im[1], pack_h2(W8.y, z128.y), hy1);
    re[0] = pack_h2(1.f, z32.x); im[0] = pack_h2(0.f, z32.y);
    hprod2<false>(re[0], im[0], pk(z8), re[1], im[1]);
    hprod2<false>(re[0], im[0], pk(z16), re[2], im[2]);
    hprod2<false>(re[0], im[0], pk(z24), re[3], im[3]);
    const uint32_t h64 = pk(z64);
#pragma unroll
    for (int j = 0; j < 4; j++) hprod2<false>(re[j], im[j], h64, r2[j], i2[j]);
    sts128(st0 + 96, re[0], re[1], re[2], re[3]);
    sts128(st1 + 96, im[0], im[1], im[2], im[3]);
    sts128(st0 + 128, r2[0], r2[1], r2[2], r2[3]);
    sts128(st1 + 128, i2[0], i2[1], i2[2], i2[3]);
    __syncwarp();
#pragma unroll
    for (int ks = 0; ks < 4; ks++) {
      ldsm2t(ldB + ks * 8 * KREC + 64, B[ks][4], B[ks][5]);
      ldsm4t(ldA + ks * 8 * KREC, A[ks][0], A[ks][1], A[ks][2], A[ks][3]);
      ldsm4t(ldB + ks * 8 * KREC, B[ks][0], B[ks][1], B[ks][2], B[ks][3]);
    }
  }
  kgen_mma(acc, A, B, csrc);
#pragma unroll
  for (int q = 0; q < 4; q++)
#pragma unroll
    for (int nt = 0; nt < 3; nt++) {
      const float* a = acc + 12 * (q >> 1) + 4 * nt + 2 * (q & 1);
      sts64f(stg + (q * 3 + nt) * 256 + lane * 8, a[0] * sc, a[1] * sc);
    }
  if (lane == 0) sts32f(stg + 3072, sc);
}

__device__ __forceinline__ void tput(uint32_t tbl, int X, uint32_t h) {
  sts16(tbl + 2 * (1296 - X), (uint16_t)h);
  sts16(tbl + TBL_C1 + 2 * (1297 - X), (uint16_t)h);
}
__device__ __forceinline__ void ktab_build(uint32_t src, bool four, int q, uint32_t tbl, int lane) {
  const int tq = lane & 3, r = 8 * q + (lane >> 3) + ((lane >> 2) & 1) * 4;
  float v[6];
  const float2 dd = lds64f(tbl + TBL_SC + 8);
  float sc = fmaxf(fmaxf(lds32f(src + 3072), lds32f(src + 3072 + KSTG)), pow2_floor(fabsf(dd.y) * (1.f / 4096.f)));
  if (four) sc = fmaxf(sc, fmaxf(lds32f(src + 3072 + 2 * KSTG), lds32f(src + 3072 + 3 * KSTG)));
  const float inv = rcpf_(sc);
  src += q * 768 + lane * 8;
#pragma unroll
  for (int nt = 0; nt < 3; nt++) {
    const float2 a = lds64f(src + nt * 256), c = lds64f(src + nt * 256 + KSTG);
    v[2 * nt] = a.x + c.x; v[2 * nt + 1] = a.y + c.y;
  }
  if (four) {
#pragma unroll
    for (int nt = 0; nt < 3; nt++) {
      const float2 a = lds64f(src + nt * 256 + 2 * KSTG), c = lds64f(src + nt * 256 + 3 * KSTG);
      v[2 * nt] += a.x + c.x; v[2 * nt + 1] += a.y + c.y;
    }
  }
  const bool first = (r == 0);
  if (first && tq == 0) { v[0] += dd.y; sts64f(tbl + TBL_SC, v[4] * inv, dd.x * sc); }
  const uint32_t h0 = pack_h2(v[0] * inv, v[1] * inv), h1 = pack_h2(v[2] * inv, v[3] * inv), h2 = pack_h2(v[4] * inv, v[5] * inv);
  tput(tbl, 64 + 8 * r + tq, h0);
  tput(tbl, 68 + 8 * r + tq, h0 >> 16);
  const bool lo = tq < 2;
  const int k2 = 32 * (tq - 2) + r;
  const bool sp = first && tq == 2;
  const int Xa = lo ? 320 + 8 * r + 2 * tq : (sp ? 576 : 911 + k2), Xb = lo ? Xa + 4 : 720 + k2;
  tput(tbl, Xa, h1);
  tput(tbl, Xb, h1 >> 16);
  if (tq == 0 || sp) {
    tput(tbl, Xa + 1, h1);
    if (Xa != 320) tput(tbl, Xa - 1, h1);
    const uint32_t hb = sp ? h1 : h1 >> 16, hc = sp ? h2 : h1 >> 16;
    tput(tbl, sp ? 578 : Xb + 1, hb);
    tput(tbl, sp ? 1295 : Xb - 1, hc);
  }
  if (lo) {
    const int X3 = ((r & 1) ? 1104 : 1231) + 32 * tq + (r >> 1);
    tput(tbl, X3 == 1231 ? 975 : X3, h2);
    tput(tbl, X3 + 16, h2 >> 16);
  }
}

__device__ __forceinline__ void sig_windows(uint32_t sig, int t) {
  uint32_t U[20];
#pragma unroll
  for (int c = 0; c < 5; c++) {
    const int kap = 2 * t - 3 + c + 72;
    const uint4 v = lds128(sig + SIG_U + (kap & 7) * U_LBO + (kap >> 3) * 16);
    U[4 * c] = v.x; U[4 * c + 1] = v.y; U[4 * c + 2] = v.z; U[4 * c + 3] = v.w;
  }
  uint32_t O[19], A2[17], A4[17], V2[8], V5[8];
#pragma unroll
  for (int i = 3; i < 19; i++) O[i] = __byte_perm(U[i - 1], U[i], 0x5432);
#pragma unroll
  for (int i = 3; i < 17; i++) A2[i] = hadd2u(U[i], O[i]);
#pragma unroll
  for (int i = 4; i < 17; i++) A4[i] = hadd2u(A2[i], A2[i - 1]);
#pragma unroll
  for (int k = 0; k < 8; k++) { V2[k] = hadd2u(O[11 + k], U[10 + k]); V5[k] = hadd2u(A4[9 + k], U[7 + k]); }
#pragma unroll
  for (int h = 0; h < 2; h++) {
    sts128(sig + SIG_V3 + t * 32 + h * 16, hadd2u(V2[4 * h], O[10 + 4 * h]), hadd2u(V2[4 * h + 1], O[11 + 4 * h]),
           hadd2u(V2[4 * h + 2], O[12 + 4 * h]), hadd2u(V2[4 * h + 3], O[13 + 4 * h]));
    sts128(sig + SIG_V5 + t * 32 + h * 16, V5[4 * h], V5[4 * h + 1], V5[4 * h + 2], V5[4 * h + 3]);
  }
  if (t < 64) {
    uint32_t V7[8], V9[8];
#pragma unroll
    for (int k = 0; k < 8; k++) {
      V7[k] = hadd2u(V5[k], hadd2u(O[10 + k], O[7 + k]));
      V9[k] = hadd2u(hadd2u(A4[6 + k], A4[4 + k]), U[2 + k]);
    }
#pragma unroll
    for (int h = 0; h < 2; h++) {
      sts128(sig + SIG_V7 + h * 1024 + t * 16, V7[4 * h], V7[4 * h + 1], V7[4 * h + 2], V7[4 * h + 3]);
      sts128(sig + SIG_V9 + h * 1024 + t * 16, V9[4 * h], V9[4 * h + 1], V9[4 * h + 2], V9[4 * h + 3]);
      sts128(sig + SIG_V2 + h * 1024 + t * 16, V2[4 * h], V2[4 * h + 1], V2[4 * h + 2], V2[4 * h + 3]);
    }
  }
}

__device__ __forceinline__ void conv_channel(uint32_t tbl, uint32_t sig, uint32_t y2b, uint32_t y3b, float k1024,
                                             int w, int lane, int barid, float* res, int ts) {
  TSTAMP(ts);
  const int g = lane >> 2, tq = lane & 3;
  const uint32_t tb = tbl + ((g & 1) ? TBL_C1 + 2 : 0) + 2 * (1296 - (g - 2 * tq)) - 32 * w + 112;
  float a2[12], a3[8];
#pragma unroll
  for (int i = 0; i < 16; i++) res[i] = 0.f;
#pragma unroll
  for (int i = 0; i < 12; i++) a2[i] = 0.f;
#pragma unroll
  for (int q = 0; q < 4; q++) {
    const float2 f = h2f(lds32(sig + SIG_V2 + (q >> 1) * 1024 + (16 * w + 8 * (q & 1) + g) * 16 + tq * 4));
    a3[2 * q] = k1024 * f.x;
    a3[2 * q + 1] = k1024 * f.y;
  }
  const uint64_t dU = mkdesc(sig + SIG_U, U_LBO, 128, 0);
  const uint64_t dV = mkdesc(sig, 128, 1024, 0);
  fence_regs<16>(res); fence_regs<12>(a2); fence_regs<8>(a3);
  constexpr int LB = 2 * U_LBO / 16;
  uint32_t Rd[75], R2[2][17], R3[2][9];
  auto load_group = [&](int gi) {
    const int it = gi >> 1, hb = gi & 1;
    if (gi == 0) Rd[0] = lds32(tb - 128);
#pragma unroll
    for (int i = 1; i < (gi == 17 ? 7 : 5); i++) Rd[4 * gi + i] = lds32(tb - 128 - 16 * (4 * gi + i));
    if (gi < 16) {
      const int sg = it >> 2, n2 = gi & 7;
      if (n2 == 0) R2[sg][0] = lds32(tb - 1440 - 384 * sg);
      R2[sg][2 * n2 + 1] = lds32(tb - 1440 - 384 * sg - 16 * (2 * n2 + 1));
      R2[sg][2 * n2 + 2] = lds32(tb - 1440 - 384 * sg - 16 * (2 * n2 + 2));
      if (!hb) {
        const int n3 = it & 3;
        if (n3 == 0) R3[sg][0] = lds32(tb - 2208 - 256 * sg);
        R3[sg][2 * n3 + 1] = lds32(tb - 2208 - 256 * sg - 16 * (2 * n3 + 1));
        R3[sg][2 * n3 + 2] = lds32(tb - 2208 - 256 * sg - 16 * (2 * n3 + 2));
      }
    }
  };
  auto dense = [&](int n) {
    wg_rs_f16_n32k(res, Rd[2 * n + 1], Rd[2 * n + 2], Rd[2 * n], Rd[2 * n + 1], dU + ((3 - (n & 3)) * LB + 9 - (n >> 2)), 1);
  };
  load_group(0);
  load_group(1);
#pragma unroll
  for (int gi = 0; gi < 18; gi++) {
    const int it = gi >> 1, sg = it >> 2, n2 = gi & 7, n3 = it & 3;
    wg_fence();
    dense(2 * gi);
    if (gi < 16)
      wg_rs_f16_n24t(a2, R2[sg][2 * n2 + 1], R2[sg][2 * n2 + 2], R2[sg][2 * n2], R2[sg][2 * n2 + 1],
                     dV + ((SIG_V3 + 768) / 16 + 256 * sg - 16 * (n2 & 3) - 64 * (n2 >> 2)), 1);
    dense(2 * gi + 1);
    if (gi < 16 && !(gi & 1))
      wg_rs_f16_n16t(a3, R3[sg][2 * n3 + 1], R3[sg][2 * n3 + 2], R3[sg][2 * n3], R3[sg][2 * n3 + 1],
                     dV + ((SIG_V7 + 768) / 16 + 128 * sg - 16 * n3), 1);
    if (gi == 17) dense(36);
    wg_commit();
    if (gi < 16) { wg_wait<1>(); load_group(gi + 2); }
  }
  TSTAMP(ts + 1);
  wg_wait<2>();
  fence_regs<12>(a2); fence_regs<8>(a3);
  bar_sync(barid, 128);
  {
    const uint32_t o2 = y2b + (136 * w + 8 * g + 2 * tq) * 4, o3 = y3b + (272 * w + 16 * g + 2 * tq) * 4;
#pragma unroll
    for (int q = 0; q < 6; q++) sts64f(o2 + (544 * (q >> 1) + 64 * (q & 1)) * 4, a2[2 * q], a2[2 * q + 1]);
#pragma unroll
    for (int q = 0; q < 4; q++) sts64f(o3 + (8 * (q >> 1) + 136 * (q & 1)) * 4, a3[2 * q], a3[2 * q + 1]);
  }
  bar_sync(barid, 128);
  const uint32_t go = (136 * tq + 16 * w + g) * 4;
  float ex[12];
#pragma unroll
  for (int i = 0; i < 12; i++) {
    const int o = 544 * (i >> 2) + 64 * (i & 1) + 8 * ((i >> 1) & 1);
    ex[i] = lds32f(y2b + go + o * 4);
    if (i >= 4) ex[i] += lds32f(y3b + go + (o - 544) * 4);
  }
  wg_wait<0>();
  fence_regs<16>(res);
#pragma unroll
  for (int i = 0; i < 12; i++) res[4 + i] += ex[i];
  TSTAMP(ts + 2);
}

__device__ __forceinline__ void red16x2(float& a, float& c) {
#pragma unroll
  for (int o = 1; o < 16; o <<= 1) { a += __shfl_xor_sync(0xffffffffu, a, o); c += __shfl_xor_sync(0xffffffffu, c, o); }
}
__device__ __forceinline__ void ln_rows(uint32_t* u, uint32_t term, uint32_t stg_row, int lane) {
  const int j = lane & 15;
  const float piv = __shfl_sync(0xffffffffu, bf_lo(u[0]), lane & 16);
  float s0 = 0.f, s1 = 0.f, q0 = 0.f, q1 = 0.f;
#pragma unroll
  for (int i = 0; i < 14; i++) {
    const float a = bf_lo(u[i]) - piv, c = bf_hi(u[i]) - piv;
    s0 += a; s1 += c; q0 = fmaf(a, a, q0); q1 = fmaf(c, c, q1);
  }
  float s = s0 + s1, q = q0 + q1;
  red16x2(s, q);
  s *= (1.f / D_); q *= (1.f / D_);
  const __nv_bfloat16 m1b = __float2bfloat16_rn(s + piv);
  const __nv_bfloat162 m1v = __halves2bfloat162(m1b, m1b);
  const float den = rbf(sqrtf_(rbf(rbf(fmaxf(fmaf(-s, s, q), 0.f)) + 1e-5f)));
  const float rden = rcpf_(den);
  s0 = s1 = q0 = q1 = 0.f;
#pragma unroll
  for (int i = 0; i < 14; i++) {
    const __nv_bfloat162 cv = __hsub2(*reinterpret_cast<__nv_bfloat162*>(&u[i]), m1v);
    const uint32_t c = *reinterpret_cast<const uint32_t*>(&cv);
    const uint32_t n = pack_bf2(bf_lo(c) * rden, bf_hi(c) * rden);
    const float a = bf_lo(n), e = bf_hi(n);
    s0 += a; s1 += e; q0 = fmaf(a, a, q0); q1 = fmaf(e, e, q1);
    u[i] = pack_h2(a, e);
  }
#pragma unroll
  for (int i = 0; i < 7; i++)
    asm volatile("st.shared.v2.b32 [%0], {%1,%2};" ::"r"(stg_row + (j + 16 * i) * 8), "r"(u[2 * i]), "r"(u[2 * i + 1]) : "memory");
  s = s0 + s1; q = q0 + q1;
  red16x2(s, q);
  s *= (1.f / D_); q *= (1.f / D_);
  const float den2 = rbf(sqrtf_(rbf(rbf(fmaxf(fmaf(-s, s, q), 0.f)) + 1e-5f)));
  if (j == 0) {
    const float ir = den * den2, mu = fmaf(rbf(s), den, __bfloat162float(m1b));
    const float ih = rbf(ir), mh = rbf(mu);
    const uint32_t mm = pack_bf2(mh, mh);
    sts128(term, pack_bf2(mu - mh, ih), mm, pack_bf2(mu - mh, ir - ih), mm);
  }
}

__device__ __forceinline__ void poll_tag(const unsigned* p, uint32_t tag) {
#pragma unroll 1
  for (int it = 0; it < 4096; it++) {
    if (!((ld_relaxed1(p) ^ tag) & 1)) break;
    __nanosleep(32);
  }
}
template <int NV, int STRIDE>
__device__ __forceinline__ void recv_part(const uint4* src, uint32_t tag, float* pre) {
  uint4 v[NV];
#pragma unroll 1
  for (int it = 0; it < RETRY_MAX; it++) {
    uint32_t bad = 0;
#pragma unroll
    for (int q = 0; q < NV; q++) v[q] = ld_b128(src + q * STRIDE);
#pragma unroll
    for (int q = 0; q < NV; q++) bad |= v[q].x ^ tag;
    const unsigned m = __ballot_sync(0xffffffffu, bad & 1);
    if (!m) break;
    if ((threadIdx.x & 31) == __ffs(m) - 1) poll_tag((const unsigned*)(src + (NV - 1) * STRIDE), tag);
    __syncwarp();
  }
#pragma unroll
  for (int q = 0; q < NV; q++) {
    const uint32_t u[4] = {v[q].x, v[q].y, v[q].z, v[q].w};
#pragma unroll
    for (int k = 0; k < 4; k++) { pre[8 * q + 2 * k] += bf_lo(u[k]); pre[8 * q + 2 * k + 1] += bf_hi(u[k]); }
  }
}
__device__ __forceinline__ void send_part(uint4* dst, uint32_t tag, const float* a) {
#pragma unroll
  for (int q = 0; q < 4; q++)
    st_b128(dst + q * 256, tag, pack_bf2(a[8 * q], a[8 * q + 1]), pack_bf2(a[8 * q + 2], a[8 * q + 3]),
            pack_bf2(a[8 * q + 4], a[8 * q + 5]), pack_bf2(a[8 * q + 6], a[8 * q + 7]));
}
__device__ __forceinline__ bool last_release(uint32_t cnt) {
  unsigned old;
  asm volatile("atom.relaxed.cta.shared.inc.u32 %0, [%1], 7;" : "=r"(old) : "r"(cnt) : "memory");
  return old == 7;
}
__device__ __forceinline__ int mod7(int v) { return v >= 7 ? v - 7 : v; }

#define IDS const int tid = opaque(tid0), lane = tid & 31, t = tid & 127, wg = tid >> 7, w = (tid >> 5) & 3; \
            (void)lane; (void)t; (void)wg; (void)w;

__global__ void __launch_bounds__(384, 1)
fused_kernel(const Params p, const __grid_constant__ CUtensorMap tm_x, const __grid_constant__ CUtensorMap tm_w1,
             const __grid_constant__ CUtensorMap tm_w2, const __grid_constant__ CUtensorMap tm_out) {
  const uint32_t sb = smem_u32(smem_raw);
  const uint32_t ms = sb + OFF_M;
  const uint32_t bar0 = ms + M_BAR;
  const int tid0 = threadIdx.x;
  const int b = blockIdx.x;
  const bool is_ssm = b >= NMLP;
  const int G = b / NRK, rk = b - G * NRK;
  const int kc0 = (G + rk) % 7;
  TSINIT();
  TSTAMP(0);
  {
    IDS
    TSTAMP(28);
    uint4 ld[7];
    KgIn kin;
    unsigned ep = 0;
    uint32_t b1w;
    const int rl = 2 * (tid >> 5) + (lane >> 4);
    {
      const int d = is_ssm ? 2 * (112 + 3 * (b - NMLP) + wg) + (w >> 1) : (wg < 2 ? 2 * b + wg : 336 + b);
      const int off = d * NST + 64 * (is_ssm ? 2 * (w & 1) : w) + 2 * lane;
      const __nv_bfloat16* P[10] = {p.a_re + off, p.a_im + off, p.b_re + off, p.b_im + off, p.c_re + off, p.c_im + off,
                                    p.log_dt + (d & ~1), p.dskip + (d & ~1), p.b1 + 64 * (is_ssm ? 0 : b >> 2) + (t & 62),
                                    wg < 2 ? p.x + (size_t)(16 * (b & 127) + rl) * D_ + 4 * (lane & 15)
                                           : p.w1 + (size_t)(112 * (b & 3) + (t >> 3)) * F_ + 64 * (is_ssm ? 0 : b >> 2) + 8 * (t & 7)};
      const unsigned* pe = &p.s->epoch;
      asm volatile("" : "+l"(P[0]), "+l"(P[1]), "+l"(P[2]), "+l"(P[3]), "+l"(P[4]), "+l"(P[5]), "+l"(P[6]), "+l"(P[7]), "+l"(P[8]), "+l"(P[9]), "+l"(pe));
      if (wg < 2) {
#pragma unroll
        for (int i = 0; i < 7; i++) asm volatile("ld.global.nc.v2.b32 {%0,%1}, [%2];" : "=r"(ld[i].x), "=r"(ld[i].y) : "l"(P[9] + 64 * i));
      } else {
#pragma unroll
        for (int i = 0; i < 7; i++)
          asm volatile("ld.global.nc.v4.b32 {%0,%1,%2,%3}, [%4];" : "=r"(ld[i].x), "=r"(ld[i].y), "=r"(ld[i].z), "=r"(ld[i].w) : "l"(P[9] + (size_t)i * 16 * F_));
      }
#pragma unroll
      for (int i = 0; i < 6; i++) kin.cur[i] = ldg32(P[i], 0);
      kin.ldt = ldg32(P[6], 0); kin.dk = ldg32(P[7], 0); b1w = ldg32(P[8], 0);
      if (tid == 256 + 32) ep = ld_relaxed1(pe);
#pragma unroll
      for (int i = 0; i < 6; i++) kin.nxt[i] = 0u;
      if (is_ssm) {
#pragma unroll
        for (int i = 0; i < 6; i++) kin.nxt[i] = ldg32(P[i], 128);
      }
      asm volatile("" :: "l"(P[0]), "l"(P[1]), "l"(P[2]), "l"(P[3]), "l"(P[4]), "l"(P[5]), "l"(P[6]), "l"(P[7]), "l"(P[8]), "l"(P[9]), "l"(pe));
      kin.odd = d & 1;
    }
    const uint32_t tbl = is_ssm ? sb + (4 * wg + (w >> 1)) * TBL : sb + OFF_T + wg * TBL;
#pragma unroll 1
    for (int i = is_ssm ? t & 63 : t; i < TBL_SC / 16; i += is_ssm ? 64 : 128) sts128(tbl + i * 16, 0u, 0u, 0u, 0u);
    const uint32_t lns = is_ssm ? sb + S_WORK + 2 * S_WGB : sb + OFF_B;
    const int wi = __shfl_sync(0xffffffffu, tid >> 5, 0);
    if (wi < 4 && lane == 0) {
      if (wi < 3) mbar_init(bar0 + 8 * wi, 1);
      asm volatile("fence.mbarrier_init.release.cluster;" ::: "memory");
      if (!is_ssm) asm volatile("prefetch.tensormap [%0];" ::"l"(wi == 0 ? &tm_x : wi == 1 ? &tm_w1 : wi == 2 ? &tm_w2 : &tm_out) : "memory");
    }
    __syncwarp();
    if (wi == 4 && lane < 16) asm volatile("st.shared.b32 [%0], 0;" ::"r"(ms + M_REL + 4 * lane) : "memory");
    TSTAMP(31);
    if (wg < 2) {
      uint32_t u[14];
#pragma unroll
      for (int i = 0; i < 7; i++) { u[2 * i] = ld[i].x; u[2 * i + 1] = ld[i].y; }
      ln_rows(u, ms + M_LT + rl * 16, lns + ((rl & 1) | ((rl >> 2) << 1) | ((rl & 2) << 2)) * 912, lane);
      bar_arrive(7, 384);
      if (wi < 3 && lane == 0 && !is_ssm) {
        const int kc = mod7(kc0 + wi);
        mbar_expect(bar0 + 8 * wi, 49152);
        tma_2d(sb + OFF_X + wi * 16384, &tm_x, 64 * kc, 128 * G, bar0 + 8 * wi);
        tma_3d(sb + OFF_W + wi * 32768, &tm_w1, 0, 64 * kc, 4 * rk, bar0 + 8 * wi);
      }
      __syncwarp();
    } else {
      float cs[8];
#pragma unroll
      for (int k = 0; k < 8; k++) cs[k] = 0.f;
#pragma unroll
      for (int i = 0; i < 7; i++) {
        const uint32_t uu[4] = {ld[i].x, ld[i].y, ld[i].z, ld[i].w};
#pragma unroll
        for (int k = 0; k < 4; k++) { cs[2 * k] += bf_lo(uu[k]); cs[2 * k + 1] += bf_hi(uu[k]); }
      }
#pragma unroll
      for (int st = 0; st < 2; st++) {
        const int n = 4 >> st;
        const bool up = (lane >> (4 - st)) & 1;
#pragma unroll
        for (int k = 0; k < n; k++) {
          const float give = up ? cs[k] : cs[k + n], keep = up ? cs[k + n] : cs[k];
          cs[k] = keep + __shfl_xor_sync(0xffffffffu, give, 16 >> st);
        }
      }
      sts64f(ms + M_CSR + (w * 64 + (lane & 7) * 8 + (lane >> 3) * 2) * 4, cs[0], cs[1]);
      if (t == 32) { asm volatile("st.shared.b32 [%0], %1;" ::"r"(ms + M_EP), "r"(ep + 1) : "memory"); red_relaxed(&p.s->cntA); }
      bar_sync(7, 384);
      const uint32_t la = lns + (lane & 15) * 912 + (lane >> 4) * 16 + w * 224;
      uint2* dst = (uint2*)(p.s->xnT + (size_t)(56 * w + (lane >> 3)) * 512 + 4 * b) + (lane & 7);
      uint32_t r[28];
#pragma unroll
      for (int k = 0; k < 7; k++) ldsm4t(la + k * 32, r[4 * k], r[4 * k + 1], r[4 * k + 2], r[4 * k + 3]);
      const uint32_t tag = lds32(ms + M_EP) & 1;
      if (b < 128) {
#pragma unroll
        for (int k = 0; k < 14; k++) st_relaxed2(dst + k * 4096, (r[2 * k] & ~1u) | tag, (r[2 * k + 1] & ~1u) | tag);
      }
      if (t < 64 && !is_ssm) {
        const uint32_t a = ms + M_CSR + t * 4;
        const float c = -((lds32f(a) + lds32f(a + 256)) + (lds32f(a + 512) + lds32f(a + 768)));
        const float ch = rbf(c);
        uint2* dx = (uint2*)(p.s->bx + (b >> 4) * 512 + ((b >> 1) & 1) * 256 + ((b >> 2) & 3) * 64 + t) + (b & 1);
        const float b1v = (b & 2) ? 0.f : ((t & 1) ? bf_hi(b1w) : bf_lo(b1w));
        asm volatile("{.reg .b64 a; mov.b64 a, {%1,%2}; st.relaxed.gpu.global.b64 [%0], a;}"
                     ::"l"(dx), "r"(pack_bf2(ch, b1v)), "r"((pack_bf2(c - ch, ch) & ~1u) | tag) : "memory");
      }
      if (t >= 64 && t < 80 && b < 128) {
        const uint4 a = lds128(ms + M_LT + (t - 64) * 16);
        st_b128(p.s->ax + 16 * b + t - 64, tag, a.x, a.y, a.z, a.w);
      }
      bar_sync(6, 128);
    }
    TSTAMP(29);
    const uint32_t stg = is_ssm ? sb + S_WORK + wg * S_WGB + w * KSTG : sb + (wg < 2 ? OFF_A + 4 * wg * KSTG : OFF_B) + w * KSTG;
    kgen_warp(kin, is_ssm ? 2 : 1, stg, tbl, lane);
  }
  TSTAMP(1);
  uint4 v[4], tv[5];
  {
    IDS
    bar_sync(4 + wg, 128);
    if (!is_ssm && wg == 2) {
#pragma unroll
      for (int q = 0; q < 4; q++) tv[q] = ld_2x64(p.s->bx + 512 * rk + q * 128 + t);
      tv[4] = ld_b128(p.s->ax + 128 * G + t);
    }
    if (is_ssm || wg == 2) {
      const uint4* src = p.s->xnT + (size_t)(is_ssm ? 112 + 3 * (b - NMLP) + wg : b) * 512 + t;
#pragma unroll
      for (int q = 0; q < 4; q++) v[q] = ld_relaxed4(src + q * 128);
    }
#pragma unroll 1
    for (int c = is_ssm ? 1 : 0; c >= 0; c--) {
      const uint32_t src = is_ssm ? sb + S_WORK + wg * S_WGB + 2 * c * KSTG : sb + (wg < 2 ? OFF_A + 4 * wg * KSTG : OFF_B);
      ktab_build(src, !is_ssm, w, is_ssm ? sb + (4 * wg + c) * TBL : sb + OFF_T + wg * TBL, lane);
    }
    fence_async();
  }
  TSTAMP(2);
  __syncthreads();

  if (is_ssm || __shfl_sync(0xffffffffu, tid0 >> 7, 0) == 2) {
    asm volatile("setmaxnreg.dec.sync.aligned.u32 136;");
    if (!is_ssm) {
      IDS
      const unsigned ep1 = lds32(ms + M_EP);
#pragma unroll 1
      for (int it = 0; it < 16 * RETRY_MAX; it++) {
        uint32_t bad = tv[4].x ^ ep1;
#pragma unroll
        for (int q = 0; q < 4; q++) bad |= (tv[q].y ^ ep1) | (tv[q].w ^ ep1);
        if (!__any_sync(0xffffffffu, bad & 1)) break;
        __nanosleep(200);
#pragma unroll
        for (int q = 0; q < 4; q++) tv[q] = ld_2x64(p.s->bx + 512 * rk + q * 128 + t);
        tv[4] = ld_b128(p.s->ax + 128 * G + t);
      }
#pragma unroll
      for (int q = 0; q < 5; q++) sts128(sb + OFF_B + (q < 4 ? B_BX + q * 2048 : B_AX) + t * 16, tv[q].x, tv[q].y, tv[q].z, tv[q].w);
      fence_async();
      bar_arrive(1, 384);
      if (t == 96) { bulk_s2g(p.s->tbl + b * (TBL / 16), sb + OFF_T + 2 * TBL, TBL); bulk_commit(); }
      if (t == 64)
        asm volatile("cp.async.bulk.prefetch.L2.global [%0], %1;" ::"l"(p.w2 + (size_t)(256 * rk + 16 * G) * D_), "r"(16 * D_ * 2) : "memory");
    }
#pragma unroll 1
    for (int pi = opaque(0); ; pi++) {
      {
        IDS
        const unsigned ep1 = lds32(ms + M_EP);
        const int pair = !is_ssm ? b : (pi == 0 ? 112 + 3 * (b - NMLP) : (b < NMLP + 12 ? 172 + 3 * (b - NMLP) : 184 + 2 * (b - NMLP))) + wg;
        const uint32_t work = is_ssm ? sb + S_WORK + wg * S_WGB : sb + OFF_A;
        const uint32_t z = work + SIG_V3 - 1024 + (t >> 6) * 4096 + (t & 63) * 16;
        sts128(z, 0u, 0u, 0u, 0u); sts128(z + SIG, 0u, 0u, 0u, 0u);
        if (t < 72) {
          const uint32_t zu = work + SIG_U + (t & 7) * U_LBO + (t >> 3) * 16;
          sts128(zu, 0u, 0u, 0u, 0u); sts128(zu + SIG, 0u, 0u, 0u, 0u);
        }
        const uint4* src = p.s->xnT + (size_t)pair * 512 + t;
#pragma unroll 1
        for (int it = 0; it < RETRY_MAX; it++) {
          uint32_t bad = 0;
#pragma unroll
          for (int q = 0; q < 4; q++) bad |= (((v[q].x ^ ep1) | (v[q].y ^ ep1) | (v[q].z ^ ep1) | (v[q].w ^ ep1)) & 1) << q;
          const unsigned m = __ballot_sync(0xffffffffu, bad);
          if (!m) break;
          if (lane == __ffs(m) - 1) poll_tag((const unsigned*)(src + (__ffs(bad) - 1) * 128) + 3, ep1);
          __syncwarp();
#pragma unroll
          for (int q = 0; q < 4; q++) v[q] = ld_relaxed4(src + q * 128);
        }
        TSTAMP(5);
        const uint32_t a = work + ((t >> 1) & 1) * SIG + SIG_U + (2 * ((t >> 2) & 3) + (t & 1)) * U_LBO + ((t >> 4) + 9) * 16;
#pragma unroll
        for (int q = 0; q < 4; q++) sts128(a + q * 128, v[q].x & ~1u, v[q].y & ~1u, v[q].z & ~1u, v[q].w & ~1u);
        bar_sync(4 + wg, 128);
#pragma unroll 1
        for (int k = w; k < 6; k += 4) sig_windows(work + (k & 1) * SIG, (k >> 1) * 32 + lane);
        fence_async();
        if (t == 96 && !is_ssm) { bulk_wait0(); red_release(&p.s->cntT); }
        if (pi == 1) mbar_wait(bar0 + 8 * wg, 0);
        TSTAMP(6);
        bar_sync(is_ssm ? 4 + wg : 3, is_ssm ? 128 : 384);
        TSTAMP(7);
      }
      uint32_t keep[8];
      float res[16];
#pragma unroll 1
      for (int c = 0; c < 2; c++) {
        IDS
        const int wgu = __shfl_sync(0xffffffffu, wg, 0);
        const uint32_t work = is_ssm ? sb + S_WORK + wgu * S_WGB : sb + OFF_A;
        const uint32_t tbl = (is_ssm ? sb + (4 * wgu + 2 * pi) * TBL : sb + OFF_T) + c * TBL;
        conv_channel(tbl, work + c * SIG, is_ssm ? work + 2 * SIG + Y3B : sb + OFF_B, work + 2 * SIG, lds32f(tbl + TBL_SC), w, lane, 4 + wgu, res, 16 + 3 * (2 * pi + c));
        const float os = lds32f(tbl + TBL_SC + 4);
        if (c == 0) {
#pragma unroll
          for (int i = 0; i < 8; i++) keep[i] = pack_bf2(res[2 * i] * os, res[2 * i + 1] * os);
          if (is_ssm && pi == 0 && t == 96 && (b < NMLP + 12 || wg < 2)) {
            wait_count(&p.s->cntT, lds32(ms + M_EP) * NMLP);
            asm volatile("fence.proxy.async;" ::: "memory");
            mbar_expect(bar0 + 8 * wg, 2 * TBL);
            bulk_g2s(sb + (4 * wg + 2) * TBL, p.s->tbl + (2 * ((b < NMLP + 12 ? 172 + 3 * (b - NMLP) : 184 + 2 * (b - NMLP)) + wg) - 336) * (TBL / 16),
                     2 * TBL, bar0 + 8 * wg);
          }
          __syncwarp();
        } else {
          const int pair = !is_ssm ? b : (pi == 0 ? 112 + 3 * (b - NMLP) : (b < NMLP + 12 ? 172 + 3 * (b - NMLP) : 184 + 2 * (b - NMLP))) + wg;
          uint4* dst = p.s->s2 + ((size_t)(lane & 3) * 224 + pair) * 32 + w * 8 + (lane >> 2);
          const uint32_t tag = lds32(ms + M_EP) & 1;
#pragma unroll
          for (int nt = 0; nt < 4; nt++) {
            const uint32_t n0 = pack_bf2(res[4 * nt] * os, res[4 * nt + 1] * os), n1 = pack_bf2(res[4 * nt + 2] * os, res[4 * nt + 3] * os);
            st_b128(dst + nt * 4 * 224 * 32, tag, __byte_perm(keep[2 * nt], n0, 0x5410), __byte_perm(keep[2 * nt + 1], n1, 0x5410),
                    __byte_perm(keep[2 * nt], n0, 0x7632), __byte_perm(keep[2 * nt + 1], n1, 0x7632));
          }
        }
      }
      TSTAMP(8 + pi);
      {
        IDS
        if (pi == 1 || !is_ssm || (b >= NMLP + 12 && wg == 2)) break;
        const uint4* src = p.s->xnT + (size_t)((b < NMLP + 12 ? 172 + 3 * (b - NMLP) : 184 + 2 * (b - NMLP)) + wg) * 512 + t;
#pragma unroll
        for (int q = 0; q < 4; q++) v[q] = ld_relaxed4(src + q * 128);
      }
    }
    if (!is_ssm) {
      IDS
      const uint32_t tag = lds32(ms + M_EP) & 1;
      float pre[64];
#pragma unroll
      for (int i = 0; i < 64; i++) pre[i] = 0.f;
#pragma unroll 1
      for (int s = 0; s < 4; s++) recv_part<8, 128>(p.s->part + ((size_t)b * 6 + s) * 1024 + t, tag, pre);
      bar_sync(6, 128);
#pragma unroll
      for (int i = 0; i < 16; i++)
        sts128(sb + OFF_A + ((2 * (i >> 2) + (i & 1)) * 256 + ((i >> 1) & 1) * 128 + t) * 16, __float_as_uint(pre[4 * i]),
               __float_as_uint(pre[4 * i + 1]), __float_as_uint(pre[4 * i + 2]), __float_as_uint(pre[4 * i + 3]));
      bar_arrive(2, 384);
      if (b == 0 && t == 0) {
        const unsigned ep1 = lds32(ms + M_EP);
        wait_count(&p.s->cntA, ep1 * NCTA);
        *(volatile unsigned*)&p.s->epoch = ep1;
      }
      TSTAMP(12);
    }
    TSDUMP();
  } else {
    bar_arrive(1, 384);
    asm volatile("setmaxnreg.inc.sync.aligned.u32 192;");
    bar_sync(7, 384);
    uint32_t H[64];
    {
      float acc[128];
      float p0, q0, p1, q1;
      {
        IDS
        const int wgu = __shfl_sync(0xffffffffu, wg, 0);
        int sl = 0;
#pragma unroll 1
        for (int s = 0; s < 7; s++) {
          mbar_wait(bar0 + 8 * sl, (s >= 3 && s < 6));
          const uint64_t da = mkdesc(sb + OFF_X + sl * 16384 + wgu * 8192, 16, 1024, 1);
          const uint64_t db = mkdesc(sb + OFF_W + sl * 32768, 8192, 1024, 1);
          wg_fence();
#pragma unroll
          for (int k = 0; k < 4; k++) wg_ss_bf16_n256(acc, da + 2 * k, db + 128 * k, (s | k) != 0);
          wg_commit();
          wg_wait<1>();
          const int pl = sl == 0 ? 2 : sl - 1;
          sl = sl == 2 ? 0 : sl + 1;
          if (s > 0 && lane == 0 && last_release(ms + M_REL + 4 * s)) {
            mbar_expect(bar0 + 8 * pl, s == 5 ? 32768 : 49152);
            if (s < 5) tma_3d(sb + OFF_W + pl * 32768, &tm_w1, 0, 64 * mod7(kc0 + s + 2), 4 * rk, bar0 + 8 * pl);
            else tma_2d(sb + OFF_W + pl * 32768, &tm_w2, 64 * mod7(rk + s - 4), 256 * rk, bar0 + 8 * pl);
            if (s != 5) tma_2d(sb + OFF_X + pl * 16384, &tm_x, 64 * (s < 5 ? mod7(kc0 + s + 2) : rk), 128 * G, bar0 + 8 * pl);
          }
        }
        TSTAMP(9);
        bar_sync(1, 384);
        wg_fence();
        wg_ss_bf16_n256k(acc, mkdesc(sb + OFF_B + B_AX + wgu * 1024, 0, 128, 0), mkdesc(sb + OFF_B + B_BX, 4096, 128, 0), 1);
        wg_commit();
        wg_wait<1>();
        if (lane == 0 && last_release(ms + M_REL + 4 * 7)) {
          mbar_expect(bar0, 65536);
#pragma unroll 1
          for (int c = 2; c < 4; c++) tma_2d(sb + (c - 2) * OFF_X, &tm_w2, 64 * mod7(rk + 1 + c), 256 * rk, bar0);
        }
        bar_arrive(3, 384);
        const uint32_t ra = sb + OFF_B + B_AX + (16 * (tid >> 5) + (lane >> 2)) * 16;
        const float r0 = rcpf_(bf_hi(lds32(ra)) + bf_hi(lds32(ra + 8))), r1 = rcpf_(bf_hi(lds32(ra + 128)) + bf_hi(lds32(ra + 136)));
        p0 = 0.7978845608028654f * r0; q0 = 0.0356774081363001f * r0 * r0 * r0;
        p1 = 0.7978845608028654f * r1; q1 = 0.0356774081363001f * r1 * r1 * r1;
      }
      wg_wait<0>();
      fence_regs<128>(acc);
      TSTAMP(16);
      float hq[4];
#pragma unroll
      for (int i = 0; i < 64; i++) {
        const float pp = (i & 1) ? p1 : p0, qq = (i & 1) ? q1 : q0;
        const float a = acc[2 * i], c = acc[2 * i + 1];
        const float ta = tanhf_(a * fmaf(a * a, qq, pp)), tc = tanhf_(c * fmaf(c * c, qq, pp));
        if (i >= 2) H[i - 2] = pack_bf2v(hq[(i & 1) * 2], hq[(i & 1) * 2 + 1]);
        hq[(i & 1) * 2] = fmaf(a, ta, a); hq[(i & 1) * 2 + 1] = fmaf(c, tc, c);
      }
      H[62] = pack_bf2v(hq[0], hq[1]); H[63] = pack_bf2v(hq[2], hq[3]);
    }
    TSTAMP(3);
    float accA[32], accB[32];
    const uint32_t tag = lds32(ms + M_EP) & 1;
    auto issue2 = [&](int c, float* acc) {
      const uint32_t base = sb + ((0x0213021u >> (4 * c)) & 3) * 32768;
      if (c != 3) mbar_wait(bar0 + 8 * ((0x0210021u >> (4 * c)) & 3), (0x34 >> c) & 1);
      const uint64_t db = mkdesc(base, 8192, 1024, 1);
      wg_fence();
#pragma unroll
      for (int k = 0; k < 16; k++) wg_rs_bf16_n64(acc, H[4 * k], H[4 * k + 1], H[4 * k + 2], H[4 * k + 3], db + 128 * k, k != 0);
      wg_commit();
    };
    auto process = [&](int s, float* acc) {
      wg_wait<1>();
      fence_regs<32>(acc);
      const int tid = opaque(tid0);
      if (s < 3 && (tid & 31) == 0 && last_release(ms + M_REL + 4 * (8 + s))) {
        const int sl = (0x021u >> (4 * s)) & 3;
        mbar_expect(bar0 + 8 * sl, 32768);
        tma_2d(sb + sl * 32768, &tm_w2, 64 * mod7(mod7(rk + 5 + s)), 256 * rk, bar0 + 8 * sl);
      }
      send_part(p.s->part + ((size_t)(G * 7 + mod7(rk + 1 + s)) * 6 + s) * 1024 + tid, tag, acc);
      TSTAMP(10 + s);
    };
    issue2(0, accA);
#pragma unroll
    for (int s = 0; s < 6; s += 2) {
      issue2(s + 1, accB);
      process(s, accA);
      issue2(s + 2, accA);
      process(s + 1, accB);
    }
    TSTAMP(4);
    IDS
    const int g = lane >> 2, tq = lane & 3;
    uint32_t sw[16];
    {
      const uint4* sp = p.s->s2 + ((size_t)G * 224 + 32 * rk + tq) * 32 + w * 8 + g;
#pragma unroll 1
      for (int it = 0; it < RETRY_MAX; it++) {
        uint32_t bad = 0;
#pragma unroll
        for (int i = 0; i < 8; i++) {
          const uint4 v = ld_b128(sp + i * 4 * 32);
          bad |= ((v.x ^ tag) & 1) << i;
          sw[2 * i] = wg ? v.z : v.x; sw[2 * i + 1] = wg ? v.w : v.y;
        }
        const unsigned m = __ballot_sync(0xffffffffu, bad);
        if (!m) break;
        if (lane == __ffs(m) - 1) poll_tag((const unsigned*)(sp + (__ffs(bad) - 1) * 4 * 32), tag);
        __syncwarp();
      }
    }
    TSTAMP(5);
    uint32_t b2w[8];
#pragma unroll
    for (int i = 0; i < 8; i++) b2w[i] = __ldg((const uint32_t*)(p.b2 + 64 * rk) + 4 * i + tq);
    wg_wait<0>();
    fence_regs<32>(accA);
    TSTAMP(6);
    bar_sync(2, 384);
#pragma unroll
    for (int i = 0; i < 8; i++) {
      const uint4 v = lds128(sb + OFF_A + (i * 256 + tid) * 16);
      accA[4 * i] += __uint_as_float(v.x); accA[4 * i + 1] += __uint_as_float(v.y);
      accA[4 * i + 2] += __uint_as_float(v.z); accA[4 * i + 3] += __uint_as_float(v.w);
    }
    const uint32_t xa = sb + OFF_X + 2 * 16384 + (16 * (tid >> 5) + (lane & 15)) * 128;
    uint32_t xw[16];
#pragma unroll
    for (int q = 0; q < 4; q++) ldsm4(xa + (((2 * q + (lane >> 4)) ^ (lane & 7)) << 4), xw[4 * q], xw[4 * q + 1], xw[4 * q + 2], xw[4 * q + 3]);
    const uint32_t ra = sb + OFF_B + B_AX + (16 * (tid >> 5) + g) * 16;
    const float r0 = 0.5f * rcpf_(bf_hi(lds32(ra)) + bf_hi(lds32(ra + 8))), r1 = 0.5f * rcpf_(bf_hi(lds32(ra + 128)) + bf_hi(lds32(ra + 136)));
#pragma unroll 1
    for (int s = 4; s < 6; s++) recv_part<4, 256>(p.s->part + ((size_t)b * 6 + s) * 1024 + tid, tag, accA);
    TSTAMP(7);
#pragma unroll
    for (int k = 0; k < 16; k++) {
      const float rr = (k & 1) ? r1 : r0;
      const float o0 = fmaf(accA[2 * k], rr, bf_lo(b2w[k >> 1])), o1 = fmaf(accA[2 * k + 1], rr, bf_hi(b2w[k >> 1]));
      const float g0 = o0 * rcpf_(1.f + ex2f(o0 * -1.4426950408889634f)), g1 = o1 * rcpf_(1.f + ex2f(o1 * -1.4426950408889634f));
      xw[k] = pack_bf2(fmaf(bf_lo(sw[k]), g0, bf_lo(xw[k])), fmaf(bf_hi(sw[k]), g1, bf_hi(xw[k])));
    }
#pragma unroll
    for (int q = 0; q < 4; q++) stsm4(xa + (((2 * q + (lane >> 4)) ^ (lane & 7)) << 4), xw[4 * q], xw[4 * q + 1], xw[4 * q + 2], xw[4 * q + 3]);
    fence_async();
    __syncwarp();
    if (lane == 0) {
      tma_store_2d(&tm_out, sb + OFF_X + 2 * 16384 + (tid >> 5) * 2048, 64 * rk, 128 * G + 16 * (tid >> 5));
      bulk_commit();
      bulk_wait0_read();
    }
    TSTAMP(8);
    TSDUMP();
  }
}

typedef CUresult (*EncodeFn)(CUtensorMap*, CUtensorMapDataType, cuuint32_t, void*, const cuuint64_t*, const cuuint64_t*,
                             const cuuint32_t*, const cuuint32_t*, CUtensorMapInterleave, CUtensorMapSwizzle,
                             CUtensorMapL2promotion, CUtensorMapFloatOOBfill);

void make_map(EncodeFn fn, CUtensorMap* m, const void* ptr, int rank, const cuuint64_t* dims, const cuuint64_t* strides, const cuuint32_t* box) {
  const cuuint32_t es[3] = {1, 1, 1};
  fn(m, CU_TENSOR_MAP_DATA_TYPE_BFLOAT16, rank, const_cast<void*>(ptr), dims, strides, box, es, CU_TENSOR_MAP_INTERLEAVE_NONE,
     CU_TENSOR_MAP_SWIZZLE_128B, CU_TENSOR_MAP_L2_PROMOTION_L2_128B, CU_TENSOR_MAP_FLOAT_OOB_FILL_NONE);
}

}

extern "C" void kernel_launch(void* const* d_in, const int* in_sizes, int n_in, void* d_out, int out_size) {
  (void)in_sizes; (void)n_in; (void)out_size;
  void* fnp = nullptr;
  cudaDriverEntryPointQueryResult qr;
  cudaGetDriverEntryPoint("cuTensorMapEncodeTiled", &fnp, cudaEnableDefault, &qr);
  EncodeFn fn = (EncodeFn)fnp;
  Params p;
  p.x = (const __nv_bfloat16*)d_in[0];
  p.a_re = (const __nv_bfloat16*)d_in[1]; p.a_im = (const __nv_bfloat16*)d_in[2];
  p.b_re = (const __nv_bfloat16*)d_in[3]; p.b_im = (const __nv_bfloat16*)d_in[4];
  p.c_re = (const __nv_bfloat16*)d_in[5]; p.c_im = (const __nv_bfloat16*)d_in[6];
  p.log_dt = (const __nv_bfloat16*)d_in[7]; p.dskip = (const __nv_bfloat16*)d_in[8];
  p.w1 = (const __nv_bfloat16*)d_in[10]; p.b1 = (const __nv_bfloat16*)d_in[11];
  p.w2 = (const __nv_bfloat16*)d_in[12]; p.b2 = (const __nv_bfloat16*)d_in[13];
  void* sp = nullptr;
  cudaGetSymbolAddress(&sp, g_scr);
  p.s = (Scratch*)sp;
  CUtensorMap mx, mw1, mw2, mo;
  {
    const cuuint64_t dims[2] = {448, 2048}, str[1] = {896};
    const cuuint32_t box[2] = {64, 128}, boxo[2] = {64, 16};
    make_map(fn, &mx, p.x, 2, dims, str, box);
    make_map(fn, &mo, d_out, 2, dims, str, boxo);
  }
  {
    const cuuint64_t dims[3] = {64, 448, 28}, str[2] = {3584, 128};
    const cuuint32_t box[3] = {64, 64, 4};
    make_map(fn, &mw1, p.w1, 3, dims, str, box);
  }
  {
    const cuuint64_t dims[2] = {448, 1792}, str[1] = {896};
    const cuuint32_t box[2] = {64, 256};
    make_map(fn, &mw2, p.w2, 2, dims, str, box);
  }
  cudaFuncSetAttribute(fused_kernel, cudaFuncAttributeMaxDynamicSharedMemorySize, SMEM_BYTES);
  fused_kernel<<<NCTA, 384, SMEM_BYTES>>>(p, mx, mw1, mw2, mo);
}
```

```cpp
#include <cuda_runtime.h>
#include <cuda_bf16.h>
#include <cuda_fp16.h>
#include <cuda.h>
#include <stdint.h>

namespace {

constexpr int D_ = 448, NST = 256, F_ = 1792;
constexpr int NRK = 7, NMLP = 112, NCTA = 132;
constexpr int SPIN_MAX = 1 << 20, RETRY_MAX = 512;

struct Scratch {
  unsigned cntA, pad0[31], cntT, pad1[31], epoch, pad2[63];
  uint4 ax[2048];
  uint4 bx[7 * 512];
  uint4 tbl[112 * 329];
  uint4 xnT[224 * 512];
  uint4 s2[16 * 224 * 32];
  uint4 part[16 * 7 * 6 * 1024];
};
__device__ Scratch g_scr;
#define TSTAMP(i)
#define TSINIT()
#define TSDUMP()
extern __shared__ __align__(1024) uint8_t smem_raw[];

constexpr int TBL_SC = 5248, TBL = 5264;
constexpr int TBL_C1 = 2624;
constexpr int SIG = 19584;
constexpr int SIG_U = 0, U_LBO = 656, SIG_V3 = 6272, SIG_V5 = 10368, SIG_V7 = 13440, SIG_V9 = 15488, SIG_V2 = 17536;
constexpr int Y2B = 6528, Y3B = 4352;
constexpr int KREC = 160, KSTG = 32 * KREC;
constexpr int OFF_W = 0, OFF_X = 98304, OFF_A = 147456, OFF_B = OFF_A + 8 * KSTG + 2560, OFF_T = OFF_B + 4 * KSTG;
constexpr int OFF_M = OFF_T + 15872;
constexpr int B_AX = Y2B, B_BX = B_AX + 2048;
constexpr int M_BAR = 0, M_REL = 128, M_EP = 192, M_CSR = 256, M_LT = 1280, M_END = 1536;
constexpr int SMEM_BYTES = OFF_M + M_END + 384;
constexpr int S_WORK = 63232, S_WGB = 2 * SIG + Y2B + Y3B;
static_assert(S_WORK + 3 * S_WGB <= OFF_M && SMEM_BYTES <= 232448, "smem");

struct Params {
  const __nv_bfloat16 *x, *a_re, *a_im, *b_re, *b_im, *c_re, *c_im, *log_dt, *dskip, *w1, *b1, *w2, *b2;
  Scratch* s;
};

__device__ __forceinline__ int opaque(int x) { int v; asm volatile("mov.u32 %0, %1;" : "=r"(v) : "r"(x)); return v; }
__device__ __forceinline__ int rd_bid() { int v; asm volatile("mov.u32 %0, %%ctaid.x;" : "=r"(v)); return v; }
__device__ __forceinline__ uint32_t smem_u32(const void* p) { return (uint32_t)__cvta_generic_to_shared(p); }
__device__ __forceinline__ void mbar_init(uint32_t bar, int cnt) { asm volatile("mbarrier.init.shared::cta.b64 [%0], %1;" ::"r"(bar), "r"(cnt)); }
__device__ __forceinline__ void mbar_expect(uint32_t bar, uint32_t bytes) {
  asm volatile("mbarrier.arrive.expect_tx.shared::cta.b64 _, [%0], %1;" ::"r"(bar), "r"(bytes) : "memory");
}
__device__ __forceinline__ void mbar_wait(uint32_t bar, uint32_t parity) {
  uint32_t done = 0;
#pragma unroll 1
  for (int it = 0; it < SPIN_MAX; it++) {
    asm volatile("{.reg .pred p; mbarrier.try_wait.parity.shared::cta.b64 p, [%1], %2; selp.u32 %0,1,0,p;}"
                 : "=r"(done) : "r"(bar), "r"(parity) : "memory");
    if (done) break;
  }
}
__device__ __forceinline__ void tma_2d(uint32_t dst, const CUtensorMap* m, int c0, int c1, uint32_t bar) {
  asm volatile("cp.async.bulk.tensor.2d.shared::cluster.global.mbarrier::complete_tx::bytes [%0], [%1, {%3, %4}], [%2];"
               ::"r"(dst), "l"(m), "r"(bar), "r"(c0), "r"(c1) : "memory");
}
__device__ __forceinline__ void tma_3d(uint32_t dst, const CUtensorMap* m, int c0, int c1, int c2, uint32_t bar) {
  asm volatile("cp.async.bulk.tensor.3d.shared::cluster.global.mbarrier::complete_tx::bytes [%0], [%1, {%3, %4, %5}], [%2];"
               ::"r"(dst), "l"(m), "r"(bar), "r"(c0), "r"(c1), "r"(c2) : "memory");
}
__device__ __forceinline__ void tma_store_2d(const CUtensorMap* m, uint32_t src, int c0, int c1) {
  asm volatile("cp.async.bulk.tensor.2d.global.shared::cta.bulk_group [%0, {%2, %3}], [%1];"
               ::"l"(m), "r"(src), "r"(c0), "r"(c1) : "memory");
}
__device__ __forceinline__ void bulk_s2g(void* dst, uint32_t src, uint32_t bytes) {
  asm volatile("cp.async.bulk.global.shared::cta.bulk_group [%0], [%1], %2;" ::"l"(dst), "r"(src), "r"(bytes) : "memory");
}
__device__ __forceinline__ void bulk_g2s(uint32_t dst, const void* src, uint32_t bytes, uint32_t bar) {
  asm volatile("cp.async.bulk.shared::cluster.global.mbarrier::complete_tx::bytes [%0], [%1], %2, [%3];"
               ::"r"(dst), "l"(src), "r"(bytes), "r"(bar) : "memory");
}
__device__ __forceinline__ void bulk_commit() { asm volatile("cp.async.bulk.commit_group;" ::: "memory"); }
__device__ __forceinline__ void bulk_wait0() { asm volatile("cp.async.bulk.wait_group 0;" ::: "memory"); }
__device__ __forceinline__ void bulk_wait0_read() { asm volatile("cp.async.bulk.wait_group.read 0;" ::: "memory"); }
__device__ __forceinline__ void fence_async() { asm volatile("fence.proxy.async.shared::cta;" ::: "memory"); }
__device__ __forceinline__ void bar_sync(int id, int n) { asm volatile("bar.sync %0, %1;" ::"r"(id), "r"(n) : "memory"); }
__device__ __forceinline__ void bar_arrive(int id, int n) { asm volatile("bar.arrive %0, %1;" ::"r"(id), "r"(n) : "memory"); }
__device__ __forceinline__ void wg_fence() { asm volatile("wgmma.fence.sync.aligned;" ::: "memory"); }
__device__ __forceinline__ void wg_commit() { asm volatile("wgmma.commit_group.sync.aligned;" ::: "memory"); }
template <int N> __device__ __forceinline__ void wg_wait() { asm volatile("wgmma.wait_group.sync.aligned %0;" ::"n"(N) : "memory"); }
template <int N> __device__ __forceinline__ void fence_regs(float* d) {
#pragma unroll
  for (int i = 0; i < N; i++) asm volatile("" : "+f"(d[i])::"memory");
}
__device__ __forceinline__ uint64_t mkdesc(uint32_t addr, uint32_t lbo, uint32_t sbo, uint32_t sw) {
  return (uint64_t)((addr & 0x3FFFF) >> 4) | ((uint64_t)(lbo >> 4) << 16) | ((uint64_t)(sbo >> 4) << 32) | ((uint64_t)sw << 62);
}
__device__ __forceinline__ uint32_t lds32(uint32_t a) { uint32_t v; asm volatile("ld.shared.b32 %0, [%1];" : "=r"(v) : "r"(a) : "memory"); return v; }
__device__ __forceinline__ float lds32f(uint32_t a) { float v; asm volatile("ld.shared.f32 %0, [%1];" : "=f"(v) : "r"(a) : "memory"); return v; }
__device__ __forceinline__ float2 lds64f(uint32_t a) { float2 v; asm volatile("ld.shared.v2.f32 {%0,%1}, [%2];" : "=f"(v.x), "=f"(v.y) : "r"(a) : "memory"); return v; }
__device__ __forceinline__ uint4 lds128(uint32_t a) {
  uint4 v; asm volatile("ld.shared.v4.b32 {%0,%1,%2,%3}, [%4];" : "=r"(v.x), "=r"(v.y), "=r"(v.z), "=r"(v.w) : "r"(a) : "memory"); return v;
}
__device__ __forceinline__ void sts16(uint32_t a, uint16_t v) { asm volatile("st.shared.b16 [%0], %1;" ::"r"(a), "h"(v) : "memory"); }
__device__ __forceinline__ void sts32f(uint32_t a, float v) { asm volatile("st.shared.f32 [%0], %1;" ::"r"(a), "f"(v) : "memory"); }
__device__ __forceinline__ void sts64f(uint32_t a, float x, float y) { asm volatile("st.shared.v2.f32 [%0], {%1,%2};" ::"r"(a), "f"(x), "f"(y) : "memory"); }
__device__ __forceinline__ void sts128(uint32_t a, uint32_t x, uint32_t y, uint32_t z, uint32_t w) {
  asm volatile("st.shared.v4.b32 [%0], {%1,%2,%3,%4};" ::"r"(a), "r"(x), "r"(y), "r"(z), "r"(w) : "memory");
}
__device__ __forceinline__ void ldsm4(uint32_t a, uint32_t& r0, uint32_t& r1, uint32_t& r2, uint32_t& r3) {
  asm volatile("ldmatrix.sync.aligned.m8n8.x4.shared.b16 {%0,%1,%2,%3}, [%4];" : "=r"(r0), "=r"(r1), "=r"(r2), "=r"(r3) : "r"(a) : "memory");
}
__device__ __forceinline__ void ldsm4t(uint32_t a, uint32_t& r0, uint32_t& r1, uint32_t& r2, uint32_t& r3) {
  asm volatile("ldmatrix.sync.aligned.m8n8.x4.trans.shared.b16 {%0,%1,%2,%3}, [%4];" : "=r"(r0), "=r"(r1), "=r"(r2), "=r"(r3) : "r"(a) : "memory");
}
__device__ __forceinline__ void ldsm2t(uint32_t a, uint32_t& r0, uint32_t& r1) {
  asm volatile("ldmatrix.sync.aligned.m8n8.x2.trans.shared.b16 {%0,%1}, [%2];" : "=r"(r0), "=r"(r1) : "r"(a) : "memory");
}
__device__ __forceinline__ void stsm4(uint32_t a, uint32_t r0, uint32_t r1, uint32_t r2, uint32_t r3) {
  asm volatile("stmatrix.sync.aligned.m8n8.x4.shared.b16 [%0], {%1,%2,%3,%4};" ::"r"(a), "r"(r0), "r"(r1), "r"(r2), "r"(r3) : "memory");
}
__device__ __forceinline__ void mma_f16(float* c, uint32_t a0, uint32_t a1, uint32_t a2, uint32_t a3, uint32_t b0, uint32_t b1) {
  asm("mma.sync.aligned.m16n8k16.row.col.f32.f16.f16.f32 {%0,%1,%2,%3},{%4,%5,%6,%7},{%8,%9},{%0,%1,%2,%3};"
               : "+f"(c[0]), "+f"(c[1]), "+f"(c[2]), "+f"(c[3]) : "r"(a0), "r"(a1), "r"(a2), "r"(a3), "r"(b0), "r"(b1));
}
__device__ __forceinline__ uint4 ld_relaxed4(const void* p) {
  uint4 v; asm volatile("ld.relaxed.gpu.global.v4.b32 {%0,%1,%2,%3}, [%4];" : "=r"(v.x), "=r"(v.y), "=r"(v.z), "=r"(v.w) : "l"(p) : "memory"); return v;
}
__device__ __forceinline__ uint4 ld_2x64(const void* p) {
  uint4 v;
  asm volatile("{.reg .b64 a, c; ld.relaxed.gpu.global.v2.b64 {a, c}, [%4]; mov.b64 {%0,%1}, a; mov.b64 {%2,%3}, c;}"
               : "=r"(v.x), "=r"(v.y), "=r"(v.z), "=r"(v.w) : "l"(p) : "memory");
  return v;
}
__device__ __forceinline__ void st_relaxed2(void* p, uint32_t x, uint32_t y) {
  asm volatile("st.relaxed.gpu.global.v2.b32 [%0], {%1,%2};" ::"l"(p), "r"(x), "r"(y) : "memory");
}
__device__ __forceinline__ uint4 ld_b128(const void* p) {
  uint4 v;
  asm volatile("{.reg .b128 t; .reg .b64 a, c; ld.relaxed.gpu.global.b128 t, [%4]; mov.b128 {a, c}, t; mov.b64 {%0,%1}, a; mov.b64 {%2,%3}, c;}"
               : "=r"(v.x), "=r"(v.y), "=r"(v.z), "=r"(v.w) : "l"(p) : "memory");
  return v;
}
__device__ __forceinline__ void st_b128(void* p, uint32_t tag, uint32_t x, uint32_t y, uint32_t z, uint32_t w) {
  asm volatile("{.reg .b128 t; .reg .b64 a, c; mov.b64 a, {%1,%2}; mov.b64 c, {%3,%4}; mov.b128 t, {a, c}; st.relaxed.gpu.global.b128 [%0], t;}"
               ::"l"(p), "r"((x & ~1u) | tag), "r"(y), "r"(z), "r"(w) : "memory");
}
__device__ __forceinline__ unsigned ld_relaxed1(const unsigned* p) {
  unsigned v; asm volatile("ld.relaxed.gpu.global.u32 %0, [%1];" : "=r"(v) : "l"(p) : "memory"); return v;
}
__device__ __forceinline__ void red_relaxed(unsigned* p) {
  asm volatile("red.relaxed.gpu.global.add.u32 [%0], 1;" ::"l"(p) : "memory");
}
__device__ __forceinline__ void red_release(unsigned* p) {
  asm volatile("red.release.gpu.global.add.u32 [%0], 1;" ::"l"(p) : "memory");
}
__device__ __forceinline__ void wait_count(const unsigned* p, unsigned target) {
#pragma unroll 1
  for (int it = 0; it < SPIN_MAX; it++) {
    if ((int)(ld_relaxed1(p) - target) >= 0) break;
    __nanosleep(40);
  }
  asm volatile("fence.acq_rel.gpu;" ::: "memory");
}
__device__ __forceinline__ uint32_t pack_h2(float lo, float hi) { uint32_t r; asm("cvt.rn.f16x2.f32 %0, %1, %2;" : "=r"(r) : "f"(hi), "f"(lo)); return r; }
__device__ __forceinline__ uint32_t pack_bf2(float lo, float hi) { uint32_t r; asm("cvt.rn.bf16x2.f32 %0, %1, %2;" : "=r"(r) : "f"(hi), "f"(lo)); return r; }
__device__ __forceinline__ uint32_t pack_bf2v(float lo, float hi) { uint32_t r; asm volatile("cvt.rn.bf16x2.f32 %0, %1, %2;" : "=r"(r) : "f"(hi), "f"(lo)); return r; }
__device__ __forceinline__ float bf_lo(uint32_t w) { return __uint_as_float(w << 16); }
__device__ __forceinline__ float bf_hi(uint32_t w) { return __uint_as_float(w & 0xffff0000u); }
__device__ __forceinline__ float rbf(float v) { return __bfloat162float(__float2bfloat16_rn(v)); }
__device__ __forceinline__ float2 h2f(uint32_t w) { return __half22float2(*reinterpret_cast<__half2*>(&w)); }
__device__ __forceinline__ float ex2f(float v) { float r; asm("ex2.approx.ftz.f32 %0, %1;" : "=f"(r) : "f"(v)); return r; }
__device__ __forceinline__ float rcpf_(float v) { float r; asm("rcp.approx.f32 %0, %1;" : "=f"(r) : "f"(v)); return r; }
__device__ __forceinline__ float sqrtf_(float v) { float r; asm("sqrt.approx.f32 %0, %1;" : "=f"(r) : "f"(v)); return r; }
__device__ __forceinline__ float tanhf_(float v) { float r; asm volatile("tanh.approx.f32 %0, %1;" : "=f"(r) : "f"(v)); return r; }

__device__ __forceinline__ void wg_ss_bf16_n256(float* d, uint64_t da, uint64_t db, int sc) {
  asm volatile("{.reg .pred p; setp.ne.b32 p, %130, 0;\n"
    "wgmma.mma_async.sync.aligned.m64n256k16.f32.bf16.bf16 {%0, %1, %2, %3, %4, %5, %6, %7, %8, %9, %10, %11, %12, %13, %14, %15, %16, %17, %18, %19, %20, %21, %22, %23, %24, %25, %26, %27, %28, %29, %30, %31, %32, %33, %34, %35, %36, %37, %38, %39, %40, %41, %42, %43, %44, %45, %46, %47, %48, %49, %50, %51, %52, %53, %54, %55, %56, %57, %58, %59, %60, %61, %62, %63, %64, %65, %66, %67, %68, %69, %70, %71, %72, %73, %74, %75, %76, %77, %78, %79, %80, %81, %82, %83, %84, %85, %86, %87, %88, %89, %90, %91, %92, %93, %94, %95, %96, %97, %98, %99, %100, %101, %102, %103, %104, %105, %106, %107, %108, %109, %110, %111, %112, %113, %114, %115, %116, %117, %118, %119, %120, %121, %122, %123, %124, %125, %126, %127}, %128, %129, p, 1, 1, 0, 1;}\n"
    : "+f"(d[0]), "+f"(d[1]), "+f"(d[2]), "+f"(d[3]), "+f"(d[4]), "+f"(d[5]), "+f"(d[6]), "+f"(d[7]), "+f"(d[8]), "+f"(d[9]), "+f"(d[10]), "+f"(d[11]), "+f"(d[12]), "+f"(d[13]), "+f"(d[14]), "+f"(d[15]), "+f"(d[16]), "+f"(d[17]), "+f"(d[18]), "+f"(d[19]), "+f"(d[20]), "+f"(d[21]), "+f"(d[22]), "+f"(d[23]), "+f"(d[24]), "+f"(d[25]), "+f"(d[26]), "+f"(d[27]), "+f"(d[28]), "+f"(d[29]), "+f"(d[30]), "+f"(d[31]), "+f"(d[32]), "+f"(d[33]), "+f"(d[34]), "+f"(d[35]), "+f"(d[36]), "+f"(d[37]), "+f"(d[38]), "+f"(d[39]), "+f"(d[40]), "+f"(d[41]), "+f"(d[42]), "+f"(d[43]), "+f"(d[44]), "+f"(d[45]), "+f"(d[46]), "+f"(d[47]), "+f"(d[48]), "+f"(d[49]), "+f"(d[50]), "+f"(d[51]), "+f"(d[52]), "+f"(d[53]), "+f"(d[54]), "+f"(d[55]), "+f"(d[56]), "+f"(d[57]), "+f"(d[58]), "+f"(d[59]), "+f"(d[60]), "+f"(d[61]), "+f"(d[62]), "+f"(d[63]), "+f"(d[64]), "+f"(d[65]), "+f"(d[66]), "+f"(d[67]), "+f"(d[68]), "+f"(d[69]), "+f"(d[70]), "+f"(d[71]), "+f"(d[72]), "+f"(d[73]), "+f"(d[74]), "+f"(d[75]), "+f"(d[76]), "+f"(d[77]), "+f"(d[78]), "+f"(d[79]), "+f"(d[80]), "+f"(d[81]), "+f"(d[82]), "+f"(d[83]), "+f"(d[84]), "+f"(d[85]), "+f"(d[86]), "+f"(d[87]), "+f"(d[88]), "+f"(d[89]), "+f"(d[90]), "+f"(d[91]), "+f"(d[92]), "+f"(d[93]), "+f"(d[94]), "+f"(d[95]), "+f"(d[96]), "+f"(d[97]), "+f"(d[98]), "+f"(d[99]), "+f"(d[100]), "+f"(d[101]), "+f"(d[102]), "+f"(d[103]), "+f"(d[104]), "+f"(d[105]), "+f"(d[106]), "+f"(d[107]), "+f"(d[108]), "+f"(d[109]), "+f"(d[110]), "+f"(d[111]), "+f"(d[112]), "+f"(d[113]), "+f"(d[114]), "+f"(d[115]), "+f"(d[116]), "+f"(d[117]), "+f"(d[118]), "+f"(d[119]), "+f"(d[120]), "+f"(d[121]), "+f"(d[122]), "+f"(d[123]), "+f"(d[124]), "+f"(d[125]), "+f"(d[126]), "+f"(d[127])
    : "l"(da), "l"(db), "r"(sc));
}

__device__ __forceinline__ void wg_ss_bf16_n256k(float* d, uint64_t da, uint64_t db, int sc) {
  asm volatile("{.reg .pred p; setp.ne.b32 p, %130, 0;\n"
    "wgmma.mma_async.sync.aligned.m64n256k16.f32.bf16.bf16 {%0, %1, %2, %3, %4, %5, %6, %7, %8, %9, %10, %11, %12, %13, %14, %15, %16, %17, %18, %19, %20, %21, %22, %23, %24, %25, %26, %27, %28, %29, %30, %31, %32, %33, %34, %35, %36, %37, %38, %39, %40, %41, %42, %43, %44, %45, %46, %47, %48, %49, %50, %51, %52, %53, %54, %55, %56, %57, %58, %59, %60, %61, %62, %63, %64, %65, %66, %67, %68, %69, %70, %71, %72, %73, %74, %75, %76, %77, %78, %79, %80, %81, %82, %83, %84, %85, %86, %87, %88, %89, %90, %91, %92, %93, %94, %95, %96, %97, %98, %99, %100, %101, %102, %103, %104, %105, %106, %107, %108, %109, %110, %111, %112, %113, %114, %115, %116, %117, %118, %119, %120, %121, %122, %123, %124, %125, %126, %127}, %128, %129, p, 1, 1, 0, 0;}\n"
    : "+f"(d[0]), "+f"(d[1]), "+f"(d[2]), "+f"(d[3]), "+f"(d[4]), "+f"(d[5]), "+f"(d[6]), "+f"(d[7]), "+f"(d[8]), "+f"(d[9]), "+f"(d[10]), "+f"(d[11]), "+f"(d[12]), "+f"(d[13]), "+f"(d[14]), "+f"(d[15]), "+f"(d[16]), "+f"(d[17]), "+f"(d[18]), "+f"(d[19]), "+f"(d[20]), "+f"(d[21]), "+f"(d[22]), "+f"(d[23]), "+f"(d[24]), "+f"(d[25]), "+f"(d[26]), "+f"(d[27]), "+f"(d[28]), "+f"(d[29]), "+f"(d[30]), "+f"(d[31]), "+f"(d[32]), "+f"(d[33]), "+f"(d[34]), "+f"(d[35]), "+f"(d[36]), "+f"(d[37]), "+f"(d[38]), "+f"(d[39]), "+f"(d[40]), "+f"(d[41]), "+f"(d[42]), "+f"(d[43]), "+f"(d[44]), "+f"(d[45]), "+f"(d[46]), "+f"(d[47]), "+f"(d[48]), "+f"(d[49]), "+f"(d[50]), "+f"(d[51]), "+f"(d[52]), "+f"(d[53]), "+f"(d[54]), "+f"(d[55]), "+f"(d[56]), "+f"(d[57]), "+f"(d[58]), "+f"(d[59]), "+f"(d[60]), "+f"(d[61]), "+f"(d[62]), "+f"(d[63]), "+f"(d[64]), "+f"(d[65]), "+f"(d[66]), "+f"(d[67]), "+f"(d[68]), "+f"(d[69]), "+f"(d[70]), "+f"(d[71]), "+f"(d[72]), "+f"(d[73]), "+f"(d[74]), "+f"(d[75]), "+f"(d[76]), "+f"(d[77]), "+f"(d[78]), "+f"(d[79]), "+f"(d[80]), "+f"(d[81]), "+f"(d[82]), "+f"(d[83]), "+f"(d[84]), "+f"(d[85]), "+f"(d[86]), "+f"(d[87]), "+f"(d[88]), "+f"(d[89]), "+f"(d[90]), "+f"(d[91]), "+f"(d[92]), "+f"(d[93]), "+f"(d[94]), "+f"(d[95]), "+f"(d[96]), "+f"(d[97]), "+f"(d[98]), "+f"(d[99]), "+f"(d[100]), "+f"(d[101]), "+f"(d[102]), "+f"(d[103]), "+f"(d[104]), "+f"(d[105]), "+f"(d[106]), "+f"(d[107]), "+f"(d[108]), "+f"(d[109]), "+f"(d[110]), "+f"(d[111]), "+f"(d[112]), "+f"(d[113]), "+f"(d[114]), "+f"(d[115]), "+f"(d[116]), "+f"(d[117]), "+f"(d[118]), "+f"(d[119]), "+f"(d[120]), "+f"(d[121]), "+f"(d[122]), "+f"(d[123]), "+f"(d[124]), "+f"(d[125]), "+f"(d[126]), "+f"(d[127])
    : "l"(da), "l"(db), "r"(sc));
}

__device__ __forceinline__ void wg_rs_bf16_n64(float* d, uint32_t a0, uint32_t a1, uint32_t a2, uint32_t a3, uint64_t db, int sc) {
  asm volatile("{.reg .pred p; setp.ne.b32 p, %37, 0;\n"
    "wgmma.mma_async.sync.aligned.m64n64k16.f32.bf16.bf16 {%0, %1, %2, %3, %4, %5, %6, %7, %8, %9, %10, %11, %12, %13, %14, %15, %16, %17, %18, %19, %20, %21, %22, %23, %24, %25, %26, %27, %28, %29, %30, %31}, {%32,%33,%34,%35}, %36, p, 1, 1, 1;}\n"
    : "+f"(d[0]), "+f"(d[1]), "+f"(d[2]), "+f"(d[3]), "+f"(d[4]), "+f"(d[5]), "+f"(d[6]), "+f"(d[7]), "+f"(d[8]), "+f"(d[9]), "+f"(d[10]), "+f"(d[11]), "+f"(d[12]), "+f"(d[13]), "+f"(d[14]), "+f"(d[15]), "+f"(d[16]), "+f"(d[17]), "+f"(d[18]), "+f"(d[19]), "+f"(d[20]), "+f"(d[21]), "+f"(d[22]), "+f"(d[23]), "+f"(d[24]), "+f"(d[25]), "+f"(d[26]), "+f"(d[27]), "+f"(d[28]), "+f"(d[29]), "+f"(d[30]), "+f"(d[31])
    : "r"(a0), "r"(a1), "r"(a2), "r"(a3), "l"(db), "r"(sc));
}

__device__ __forceinline__ void wg_rs_f16_n32k(float* d, uint32_t a0, uint32_t a1, uint32_t a2, uint32_t a3, uint64_t db, int sc) {
  asm volatile("{.reg .pred p; setp.ne.b32 p, %21, 0;\n"
    "wgmma.mma_async.sync.aligned.m64n32k16.f32.f16.f16 {%0, %1, %2, %3, %4, %5, %6, %7, %8, %9, %10, %11, %12, %13, %14, %15}, {%16,%17,%18,%19}, %20, p, 1, 1, 0;}\n"
    : "+f"(d[0]), "+f"(d[1]), "+f"(d[2]), "+f"(d[3]), "+f"(d[4]), "+f"(d[5]), "+f"(d[6]), "+f"(d[7]), "+f"(d[8]), "+f"(d[9]), "+f"(d[10]), "+f"(d[11]), "+f"(d[12]), "+f"(d[13]), "+f"(d[14]), "+f"(d[15])
    : "r"(a0), "r"(a1), "r"(a2), "r"(a3), "l"(db), "r"(sc));
}

__device__ __forceinline__ void wg_rs_f16_n24t(float* d, uint32_t a0, uint32_t a1, uint32_t a2, uint32_t a3, uint64_t db, int sc) {
  asm volatile("{.reg .pred p; setp.ne.b32 p, %17, 0;\n"
    "wgmma.mma_async.sync.aligned.m64n24k16.f32.f16.f16 {%0, %1, %2, %3, %4, %5, %6, %7, %8, %9, %10, %11}, {%12,%13,%14,%15}, %16, p, 1, 1, 1;}\n"
    : "+f"(d[0]), "+f"(d[1]), "+f"(d[2]), "+f"(d[3]), "+f"(d[4]), "+f"(d[5]), "+f"(d[6]), "+f"(d[7]), "+f"(d[8]), "+f"(d[9]), "+f"(d[10]), "+f"(d[11])
    : "r"(a0), "r"(a1), "r"(a2), "r"(a3), "l"(db), "r"(sc));
}

__device__ __forceinline__ void wg_rs_f16_n16t(float* d, uint32_t a0, uint32_t a1, uint32_t a2, uint32_t a3, uint64_t db, int sc) {
  asm volatile("{.reg .pred p; setp.ne.b32 p, %13, 0;\n"
    "wgmma.mma_async.sync.aligned.m64n16k16.f32.f16.f16 {%0, %1, %2, %3, %4, %5, %6, %7}, {%8,%9,%10,%11}, %12, p, 1, 1, 1;}\n"
    : "+f"(d[0]), "+f"(d[1]), "+f"(d[2]), "+f"(d[3]), "+f"(d[4]), "+f"(d[5]), "+f"(d[6]), "+f"(d[7])
    : "r"(a0), "r"(a1), "r"(a2), "r"(a3), "l"(db), "r"(sc));
}

struct cf { float x, y; };
__device__ __forceinline__ cf cmul(cf a, cf b) { cf r; r.x = fmaf(a.x, b.x, -a.y * b.y); r.y = fmaf(a.x, b.y, a.y * b.x); return r; }
__device__ __forceinline__ cf zpow(float rho2, float phi, float e) {
  const float m = ex2f(rho2 * e), ang = phi * e;
  cf r; r.x = m * __cosf(ang); r.y = m * __sinf(ang); return r;
}
__device__ __forceinline__ __half2 H2(uint32_t v) { return *reinterpret_cast<__half2*>(&v); }
__device__ __forceinline__ uint32_t U32(__half2 v) { return *reinterpret_cast<uint32_t*>(&v); }
__device__ __forceinline__ uint32_t hprod(uint32_t v, uint32_t r, uint32_t rr) {
  return U32(__hfma2(__high2half2(H2(v)), H2(rr), __hmul2(__low2half2(H2(v)), H2(r))));
}
template <bool CONJ>
__device__ __forceinline__ void hprod2(uint32_t re, uint32_t im, uint32_t r, uint32_t& ore, uint32_t& oim) {
  const __half2 rx = __low2half2(H2(r)), ry = __high2half2(H2(r));
  if (CONJ) {
    ore = U32(__hfma2(H2(re), rx, __hmul2(H2(im), ry)));
    oim = U32(__hfma2(H2(im), rx, __hneg2(__hmul2(H2(re), ry))));
  } else {
    ore = U32(__hfma2(H2(re), rx, __hneg2(__hmul2(H2(im), ry))));
    oim = U32(__hfma2(H2(re), ry, __hmul2(H2(im), rx)));
  }
}
__device__ __forceinline__ cf csq(cf a) { cf r; r.x = fmaf(a.x, a.x, -a.y * a.y); r.y = (a.x + a.x) * a.y; return r; }
__device__ __forceinline__ cf cmulc(cf a, cf b) { cf r; r.x = fmaf(a.x, b.x, a.y * b.y); r.y = fmaf(a.y, b.x, -a.x * b.y); return r; }
__device__ __forceinline__ uint32_t pk(cf a) { return pack_h2(a.x, a.y); }
__device__ __forceinline__ uint32_t ldg32(const void* p, int o) { uint32_t v; asm volatile("ld.global.nc.b32 %0, [%1];" : "=r"(v) : "l"((const char*)p + o)); return v; }
__device__ __forceinline__ uint32_t rot90(uint32_t v) { return __byte_perm(v, 0, 0x1032) ^ 0x00008000u; }
__device__ __forceinline__ uint32_t hadd2u(uint32_t a, uint32_t b) { return U32(__hadd2(H2(a), H2(b))); }

struct KgIn { uint32_t cur[6], nxt[6], ldt, dk; bool odd; };
__device__ __forceinline__ float pow2_floor(float v) { return __uint_as_float(__float_as_uint(fminf(fmaxf(v, 1e-30f), 1e30f)) & 0x7f800000u); }
__device__ __forceinline__ void kgen_mma(float* acc, const uint32_t (*A)[4], const uint32_t (*B)[6], int csrc) {
#pragma unroll
  for (int ks = 0; ks < 4; ks++) {
    const uint32_t rl = __shfl_sync(0xffffffffu, B[ks][4], csrc), rh = __shfl_sync(0xffffffffu, B[ks][5], csrc);
    const uint32_t rlr = rot90(rl), rhr = rot90(rh);
    mma_f16(acc + 0, A[ks][0], A[ks][1], A[ks][2], A[ks][3], B[ks][0], B[ks][1]);
    mma_f16(acc + 4, A[ks][0], A[ks][1], A[ks][2], A[ks][3], B[ks][2], B[ks][3]);
    mma_f16(acc + 8, A[ks][0], A[ks][1], A[ks][2], A[ks][3], B[ks][4], B[ks][5]);
    const uint32_t c0 = hprod(A[ks][0], rl, rlr), c1 = hprod(A[ks][1], rl, rlr);
    const uint32_t c2 = hprod(A[ks][2], rh, rhr), c3 = hprod(A[ks][3], rh, rhr);
    mma_f16(acc + 12, c0, c1, c2, c3, B[ks][0], B[ks][1]);
    mma_f16(acc + 16, c0, c1, c2, c3, B[ks][2], B[ks][3]);
    mma_f16(acc + 20, c0, c1, c2, c3, B[ks][4], B[ks][5]);
  }
}
template <class Mid>
__device__ __forceinline__ void kgen_warp(KgIn& k, int nw, uint32_t stg, uint32_t tbl, int lane, Mid mid) {
  float dl, dt, sc, inv_sc;
  {
    const uint32_t M = 0x7fff7fffu;
    uint32_t mx[2];
#pragma unroll
    for (int i = 0; i < 2; i++) {
      const uint32_t m = __vmaxu2(__vmaxu2(k.cur[2 + 2 * i] & M, k.cur[3 + 2 * i] & M), __vmaxu2(k.nxt[2 + 2 * i] & M, k.nxt[3 + 2 * i] & M));
      mx[i] = __reduce_max_sync(0xffffffffu, max(m << 16, m & 0xffff0000u));
    }
    dt = rbf(ex2f((k.odd ? bf_hi(k.ldt) : bf_lo(k.ldt)) * 1.4426950408889634f));
    sc = pow2_floor(0.125f * __uint_as_float(mx[0]) * __uint_as_float(mx[1]));
    inv_sc = rcpf_(sc);
    if (lane == 0) sts64f(tbl + TBL_SC + 8, dt, (k.odd ? bf_hi(k.dk) : bf_lo(k.dk)) * rcpf_(dt));
    dl = dt * 1.4426950408889634f;
  }
  const uint32_t st0 = stg + lane * KREC + (((lane >> 2) & 1) << 4), st1 = st0 ^ 16;
  const int mat = lane >> 3, rowi = lane & 7;
  const uint32_t ldB = stg + (4 * (mat & 1) + (rowi >> 1)) * KREC + ((((mat >> 1) * 2 + (rowi & 1)) << 4) ^ ((mat & 1) << 4));
  const uint32_t ldA = stg + (4 * (mat >> 1) + (rowi >> 1)) * KREC + ((((mat & 1) * 2 + (rowi & 1)) << 4) ^ ((mat >> 1) << 4)) + 96;
  const int csrc = 20 + (lane & 3);
  float acc[24];
  uint32_t B[4][6], A[4][4];
#pragma unroll
  for (int i = 0; i < 24; i++) { acc[i] = 0.f; B[i / 6][i % 6] = 0u; }
#pragma unroll
  for (int i = 0; i < 16; i++) A[i / 4][i % 4] = 0u;
#pragma unroll 1
  for (int it = 0; it < 2 * nw; it++) {
    if (it == 1) mid();
    const uint32_t sel = (it & 1) ? 0x3244u : 0x1044u;
    float v[6];
#pragma unroll
    for (int i = 0; i < 6; i++) { v[i] = __uint_as_float(__byte_perm(k.cur[i], 0, sel)); if (it == 1) k.cur[i] = k.nxt[i]; }
    const float rho2 = v[0] * dl, phi = v[1] * dt;
    const cf bb = {v[2] * inv_sc, v[3] * -inv_sc}, cc = {v[4], v[5]};
    const cf X0 = cmulc(bb, cc);
    const cf z1 = zpow(rho2, phi, 1.f), z64 = zpow(rho2, phi, 64.f);
    kgen_mma(acc, A, B, csrc);
    const cf z2 = csq(z1), z3 = cmul(z2, z1), z4 = csq(z2), z8 = csq(z4), z16 = csq(z8), z24 = cmul(z16, z8), z32 = csq(z16);
    const cf z128 = csq(z64), y1 = csq(z128), y2 = csq(y1), y3 = cmul(y2, y1), y4 = csq(y2);
    const cf X4 = cmulc(X0, z4), W4 = cmulc(X0, y4), W8 = cmulc(W4, y4);
    uint32_t re[4], im[4], r2[4], i2[4];
    re[0] = pack_h2(X0.x, X4.x); im[0] = pack_h2(X0.y, X4.y);
    hprod2<true>(re[0], im[0], pk(z1), re[1], im[1]);
    hprod2<true>(re[0], im[0], pk(z2), re[2], im[2]);
    hprod2<true>(re[0], im[0], pk(z3), re[3], im[3]);
    sts128(st0, re[0], re[1], re[2], re[3]);
    sts128(st1, im[0], im[1], im[2], im[3]);
    const uint32_t hy1 = pk(y1), hy2 = pk(y2);
    hprod2<true>(re[0], im[0], hy1, r2[0], i2[0]);
    hprod2<true>(re[2], im[2], hy1, r2[1], i2[1]);
    hprod2<true>(re[0], im[0], hy2, r2[2], i2[2]);
    hprod2<true>(re[0], im[0], pk(y3), r2[3], i2[3]);
    sts128(st0 + 32, r2[0], r2[1], r2[2], r2[3]);
    sts128(st1 + 32, i2[0], i2[1], i2[2], i2[3]);
    const cf W5 = cmulc(W4, y1);
    re[0] = pack_h2(W4.x, W5.x); im[0] = pack_h2(W4.y, W5.y);
    hprod2<true>(re[0], im[0], hy2, re[1], im[1]);
    sts128(st0 + 64, re[0], re[1], pack_h2(W8.x, z128.x), hy1);
    sts128(st1 + 64, im[0], im[1], pack_h2(W8.y, z128.y), hy1);
    re[0] = pack_h2(1.f, z32.x); im[0] = pack_h2(0.f, z32.y);
    hprod2<false>(re[0], im[0], pk(z8), re[1], im[1]);
    hprod2<false>(re[0], im[0], pk(z16), re[2], im[2]);
    hprod2<false>(re[0], im[0], pk(z24), re[3], im[3]);
    const uint32_t h64 = pk(z64);
#pragma unroll
    for (int j = 0; j < 4; j++) hprod2<false>(re[j], im[j], h64, r2[j], i2[j]);
    sts128(st0 + 96, re[0], re[1], re[2], re[3]);
    sts128(st1 + 96, im[0], im[1], im[2], im[3]);
    sts128(st0 + 128, r2[0], r2[1], r2[2], r2[3]);
    sts128(st1 + 128, i2[0], i2[1], i2[2], i2[3]);
    __syncwarp();
#pragma unroll
    for (int ks = 0; ks < 4; ks++) {
      ldsm2t(ldB + ks * 8 * KREC + 64, B[ks][4], B[ks][5]);
      ldsm4t(ldA + ks * 8 * KREC, A[ks][0], A[ks][1], A[ks][2], A[ks][3]);
      ldsm4t(ldB + ks * 8 * KREC, B[ks][0], B[ks][1], B[ks][2], B[ks][3]);
    }
  }
  kgen_mma(acc, A, B, csrc);
#pragma unroll
  for (int q = 0; q < 4; q++)
#pragma unroll
    for (int nt = 0; nt < 3; nt++) {
      const float* a = acc + 12 * (q >> 1) + 4 * nt + 2 * (q & 1);
      sts64f(stg + (q * 3 + nt) * 256 + lane * 8, a[0] * sc, a[1] * sc);
    }
  if (lane == 0) sts32f(stg + 3072, sc);
}

__device__ __forceinline__ void tput(uint32_t tbl, int X, uint32_t h) {
  sts16(tbl + 2 * (1296 - X), (uint16_t)h);
  sts16(tbl + TBL_C1 + 2 * (1297 - X), (uint16_t)h);
}
__device__ __forceinline__ void ktab_build(uint32_t src, bool four, int q, uint32_t tbl, int lane) {
  const int tq = lane & 3, r = 8 * q + (lane >> 3) + ((lane >> 2) & 1) * 4;
  float v[6];
  const float2 dd = lds64f(tbl + TBL_SC + 8);
  float sc = fmaxf(fmaxf(lds32f(src + 3072), lds32f(src + 3072 + KSTG)), pow2_floor(fabsf(dd.y) * (1.f / 4096.f)));
  if (four) sc = fmaxf(sc, fmaxf(lds32f(src + 3072 + 2 * KSTG), lds32f(src + 3072 + 3 * KSTG)));
  const float inv = rcpf_(sc);
  src += q * 768 + lane * 8;
#pragma unroll
  for (int nt = 0; nt < 3; nt++) {
    const float2 a = lds64f(src + nt * 256), c = lds64f(src + nt * 256 + KSTG);
    v[2 * nt] = a.x + c.x; v[2 * nt + 1] = a.y + c.y;
  }
  if (four) {
#pragma unroll
    for (int nt = 0; nt < 3; nt++) {
      const float2 a = lds64f(src + nt * 256 + 2 * KSTG), c = lds64f(src + nt * 256 + 3 * KSTG);
      v[2 * nt] += a.x + c.x; v[2 * nt + 1] += a.y + c.y;
    }
  }
  const bool first = (r == 0);
  if (first && tq == 0) { v[0] += dd.y; sts64f(tbl + TBL_SC, v[4] * inv, dd.x * sc); }
  const uint32_t h0 = pack_h2(v[0] * inv, v[1] * inv), h1 = pack_h2(v[2] * inv, v[3] * inv), h2 = pack_h2(v[4] * inv, v[5] * inv);
  tput(tbl, 64 + 8 * r + tq, h0);
  tput(tbl, 68 + 8 * r + tq, h0 >> 16);
  const bool lo = tq < 2;
  const int k2 = 32 * (tq - 2) + r;
  const bool sp = first && tq == 2;
  const int Xa = lo ? 320 + 8 * r + 2 * tq : (sp ? 576 : 911 + k2), Xb = lo ? Xa + 4 : 720 + k2;
  tput(tbl, Xa, h1);
  tput(tbl, Xb, h1 >> 16);
  if (tq == 0 || sp) {
    tput(tbl, Xa + 1, h1);
    if (Xa != 320) tput(tbl, Xa - 1, h1);
    const uint32_t hb = sp ? h1 : h1 >> 16, hc = sp ? h2 : h1 >> 16;
    tput(tbl, sp ? 578 : Xb + 1, hb);
    tput(tbl, sp ? 1295 : Xb - 1, hc);
  }
  if (lo) {
    const int X3 = ((r & 1) ? 1104 : 1231) + 32 * tq + (r >> 1);
    tput(tbl, X3 == 1231 ? 975 : X3, h2);
    tput(tbl, X3 + 16, h2 >> 16);
  }
}

__device__ __forceinline__ void sig_windows(uint32_t sig, int t) {
  uint32_t U[20];
#pragma unroll
  for (int c = 0; c < 5; c++) {
    const int kap = 2 * t - 3 + c + 72;
    const uint4 v = lds128(sig + SIG_U + (kap & 7) * U_LBO + (kap >> 3) * 16);
    U[4 * c] = v.x; U[4 * c + 1] = v.y; U[4 * c + 2] = v.z; U[4 * c + 3] = v.w;
  }
  uint32_t O[19], A2[17], A4[17], V2[8], V5[8];
#pragma unroll
  for (int i = 3; i < 19; i++) O[i] = __byte_perm(U[i - 1], U[i], 0x5432);
#pragma unroll
  for (int i = 3; i < 17; i++) A2[i] = hadd2u(U[i], O[i]);
#pragma unroll
  for (int i = 4; i < 17; i++) A4[i] = hadd2u(A2[i], A2[i - 1]);
#pragma unroll
  for (int k = 0; k < 8; k++) { V2[k] = hadd2u(O[11 + k], U[10 + k]); V5[k] = hadd2u(A4[9 + k], U[7 + k]); }
#pragma unroll
  for (int h = 0; h < 2; h++) {
    sts128(sig + SIG_V3 + t * 32 + h * 16, hadd2u(V2[4 * h], O[10 + 4 * h]), hadd2u(V2[4 * h + 1], O[11 + 4 * h]),
           hadd2u(V2[4 * h + 2], O[12 + 4 * h]), hadd2u(V2[4 * h + 3], O[13 + 4 * h]));
    sts128(sig + SIG_V5 + t * 32 + h * 16, V5[4 * h], V5[4 * h + 1], V5[4 * h + 2], V5[4 * h + 3]);
  }
  if (t < 64) {
    uint32_t V7[8], V9[8];
#pragma unroll
    for (int k = 0; k < 8; k++) {
      V7[k] = hadd2u(V5[k], hadd2u(O[10 + k], O[7 + k]));
      V9[k] = hadd2u(hadd2u(A4[6 + k], A4[4 + k]), U[2 + k]);
    }
#pragma unroll
    for (int h = 0; h < 2; h++) {
      sts128(sig + SIG_V7 + h * 1024 + t * 16, V7[4 * h], V7[4 * h + 1], V7[4 * h + 2], V7[4 * h + 3]);
      sts128(sig + SIG_V9 + h * 1024 + t * 16, V9[4 * h], V9[4 * h + 1], V9[4 * h + 2], V9[4 * h + 3]);
      sts128(sig + SIG_V2 + h * 1024 + t * 16, V2[4 * h], V2[4 * h + 1], V2[4 * h + 2], V2[4 * h + 3]);
    }
  }
}

__device__ __forceinline__ void conv_channel(uint32_t tbl, uint32_t sig, uint32_t y2b, uint32_t y3b, float k1024,
                                             int w, int lane, int barid, float* res, int ts) {
  TSTAMP(ts);
  const int g = lane >> 2, tq = lane & 3;
  const uint32_t tb = tbl + ((g & 1) ? TBL_C1 + 2 : 0) + 2 * (1296 - (g - 2 * tq)) - 32 * w + 112;
  float a2[12], a3[8];
#pragma unroll
  for (int i = 0; i < 16; i++) res[i] = 0.f;
#pragma unroll
  for (int i = 0; i < 12; i++) a2[i] = 0.f;
#pragma unroll
  for (int q = 0; q < 4; q++) {
    const float2 f = h2f(lds32(sig + SIG_V2 + (q >> 1) * 1024 + (16 * w + 8 * (q & 1) + g) * 16 + tq * 4));
    a3[2 * q] = k1024 * f.x;
    a3[2 * q + 1] = k1024 * f.y;
  }
  const uint64_t dU = mkdesc(sig + SIG_U, U_LBO, 128, 0);
  const uint64_t dV = mkdesc(sig, 128, 1024, 0);
  fence_regs<16>(res); fence_regs<12>(a2); fence_regs<8>(a3);
  constexpr int LB = 2 * U_LBO / 16;
  uint32_t Rd[75], R2[2][17], R3[2][9];
  auto load_group = [&](int gi) {
    const int it = gi >> 1, hb = gi & 1;
    if (gi == 0) Rd[0] = lds32(tb - 128);
#pragma unroll
    for (int i = 1; i < (gi == 17 ? 7 : 5); i++) Rd[4 * gi + i] = lds32(tb - 128 - 16 * (4 * gi + i));
    if (gi < 16) {
      const int sg = it >> 2, n2 = gi & 7;
      if (n2 == 0) R2[sg][0] = lds32(tb - 1440 - 384 * sg);
      R2[sg][2 * n2 + 1] = lds32(tb - 1440 - 384 * sg - 16 * (2 * n2 + 1));
      R2[sg][2 * n2 + 2] = lds32(tb - 1440 - 384 * sg - 16 * (2 * n2 + 2));
      if (!hb) {
        const int n3 = it & 3;
        if (n3 == 0) R3[sg][0] = lds32(tb - 2208 - 256 * sg);
        R3[sg][2 * n3 + 1] = lds32(tb - 2208 - 256 * sg - 16 * (2 * n3 + 1));
        R3[sg][2 * n3 + 2] = lds32(tb - 2208 - 256 * sg - 16 * (2 * n3 + 2));
      }
    }
  };
  auto dense = [&](int n) {
    wg_rs_f16_n32k(res, Rd[2 * n + 1], Rd[2 * n + 2], Rd[2 * n], Rd[2 * n + 1], dU + ((3 - (n & 3)) * LB + 9 - (n >> 2)), 1);
  };
  load_group(0);
  load_group(1);
#pragma unroll
  for (int gi = 0; gi < 18; gi++) {
    const int it = gi >> 1, sg = it >> 2, n2 = gi & 7, n3 = it & 3;
    wg_fence();
    dense(2 * gi);
    if (gi < 16)
      wg_rs_f16_n24t(a2, R2[sg][2 * n2 + 1], R2[sg][2 * n2 + 2], R2[sg][2 * n2], R2[sg][2 * n2 + 1],
                     dV + ((SIG_V3 + 768) / 16 + 256 * sg - 16 * (n2 & 3) - 64 * (n2 >> 2)), 1);
    dense(2 * gi + 1);
    if (gi < 16 && !(gi & 1))
      wg_rs_f16_n16t(a3, R3[sg][2 * n3 + 1], R3[sg][2 * n3 + 2], R3[sg][2 * n3], R3[sg][2 * n3 + 1],
                     dV + ((SIG_V7 + 768) / 16 + 128 * sg - 16 * n3), 1);
    if (gi == 17) dense(36);
    wg_commit();
    if (gi < 16) { wg_wait<1>(); load_group(gi + 2); }
  }
  TSTAMP(ts + 1);
  wg_wait<2>();
  fence_regs<12>(a2); fence_regs<8>(a3);
  bar_sync(barid, 128);
  {
    const uint32_t o2 = y2b + (136 * w + 8 * g + 2 * tq) * 4, o3 = y3b + (272 * w + 16 * g + 2 * tq) * 4;
#pragma unroll
    for (int q = 0; q < 6; q++) sts64f(o2 + (544 * (q >> 1) + 64 * (q & 1)) * 4, a2[2 * q], a2[2 * q + 1]);
#pragma unroll
    for (int q = 0; q < 4; q++) sts64f(o3 + (8 * (q >> 1) + 136 * (q & 1)) * 4, a3[2 * q], a3[2 * q + 1]);
  }
  bar_sync(barid, 128);
  const uint32_t go = (136 * tq + 16 * w + g) * 4;
  float ex[12];
#pragma unroll
  for (int i = 0; i < 12; i++) {
    const int o = 544 * (i >> 2) + 64 * (i & 1) + 8 * ((i >> 1) & 1);
    ex[i] = lds32f(y2b + go + o * 4);
    if (i >= 4) ex[i] += lds32f(y3b + go + (o - 544) * 4);
  }
  wg_wait<0>();
  fence_regs<16>(res);
#pragma unroll
  for (int i = 0; i < 12; i++) res[4 + i] += ex[i];
  TSTAMP(ts + 2);
}

__device__ __forceinline__ void red16x2(float& a, float& c) {
#pragma unroll
  for (int o = 1; o < 16; o <<= 1) { a += __shfl_xor_sync(0xffffffffu, a, o); c += __shfl_xor_sync(0xffffffffu, c, o); }
}
__device__ __forceinline__ void ln_rows(uint32_t* u, uint32_t term, uint32_t stg_row, int lane) {
  const int j = lane & 15;
  const float piv = __shfl_sync(0xffffffffu, bf_lo(u[0]), lane & 16);
  float s0 = 0.f, s1 = 0.f, q0 = 0.f, q1 = 0.f;
#pragma unroll
  for (int i = 0; i < 14; i++) {
    const float a = bf_lo(u[i]) - piv, c = bf_hi(u[i]) - piv;
    s0 += a; s1 += c; q0 = fmaf(a, a, q0); q1 = fmaf(c, c, q1);
  }
  float s = s0 + s1, q = q0 + q1;
  red16x2(s, q);
  s *= (1.f / D_); q *= (1.f / D_);
  const __nv_bfloat16 m1b = __float2bfloat16_rn(s + piv);
  const __nv_bfloat162 m1v = __halves2bfloat162(m1b, m1b);
  const float den = rbf(sqrtf_(rbf(rbf(fmaxf(fmaf(-s, s, q), 0.f)) + 1e-5f)));
  const float rden = rcpf_(den);
  s0 = s1 = q0 = q1 = 0.f;
#pragma unroll
  for (int i = 0; i < 14; i++) {
    const __nv_bfloat162 cv = __hsub2(*reinterpret_cast<__nv_bfloat162*>(&u[i]), m1v);
    const uint32_t c = *reinterpret_cast<const uint32_t*>(&cv);
    const uint32_t n = pack_bf2(bf_lo(c) * rden, bf_hi(c) * rden);
    const float a = bf_lo(n), e = bf_hi(n);
    s0 += a; s1 += e; q0 = fmaf(a, a, q0); q1 = fmaf(e, e, q1);
    u[i] = pack_h2(a, e);
  }
#pragma unroll
  for (int i = 0; i < 7; i++)
    asm volatile("st.shared.v2.b32 [%0], {%1,%2};" ::"r"(stg_row + (j + 16 * i) * 8), "r"(u[2 * i]), "r"(u[2 * i + 1]) : "memory");
  s = s0 + s1; q = q0 + q1;
  red16x2(s, q);
  s *= (1.f / D_); q *= (1.f / D_);
  const float den2 = rbf(sqrtf_(rbf(rbf(fmaxf(fmaf(-s, s, q), 0.f)) + 1e-5f)));
  if (j == 0) {
    const float ir = den * den2, mu = fmaf(rbf(s), den, __bfloat162float(m1b));
    const float ih = rbf(ir), mh = rbf(mu);
    const uint32_t mm = pack_bf2(mh, mh);
    sts128(term, pack_bf2(mu - mh, ih), mm, pack_bf2(mu - mh, ir - ih), mm);
  }
}

__device__ __forceinline__ void poll_tag(const unsigned* p, uint32_t tag) {
#pragma unroll 1
  for (int it = 0; it < 4096; it++) {
    if (!((ld_relaxed1(p) ^ tag) & 1)) break;
    __nanosleep(32);
  }
}
template <int NV, int STRIDE>
__device__ __forceinline__ void recv_part(const uint4* src, uint32_t tag, float* pre) {
  uint4 v[NV];
#pragma unroll 1
  for (int it = 0; it < RETRY_MAX; it++) {
    uint32_t bad = 0;
#pragma unroll
    for (int q = 0; q < NV; q++) v[q] = ld_b128(src + q * STRIDE);
#pragma unroll
    for (int q = 0; q < NV; q++) bad |= v[q].x ^ tag;
    const unsigned m = __ballot_sync(0xffffffffu, bad & 1);
    if (!m) break;
    if ((threadIdx.x & 31) == __ffs(m) - 1) poll_tag((const unsigned*)(src + (NV - 1) * STRIDE), tag);
    __syncwarp();
  }
#pragma unroll
  for (int q = 0; q < NV; q++) {
    const uint32_t u[4] = {v[q].x, v[q].y, v[q].z, v[q].w};
#pragma unroll
    for (int k = 0; k < 4; k++) { pre[8 * q + 2 * k] += bf_lo(u[k]); pre[8 * q + 2 * k + 1] += bf_hi(u[k]); }
  }
}
__device__ __forceinline__ void send_part(uint4* dst, uint32_t tag, const float* a) {
#pragma unroll
  for (int q = 0; q < 4; q++)
    st_b128(dst + q * 256, tag, pack_bf2(a[8 * q], a[8 * q + 1]), pack_bf2(a[8 * q + 2], a[8 * q + 3]),
            pack_bf2(a[8 * q + 4], a[8 * q + 5]), pack_bf2(a[8 * q + 6], a[8 * q + 7]));
}
__device__ __forceinline__ bool last_release(uint32_t cnt) {
  unsigned old;
  asm volatile("atom.relaxed.cta.shared.inc.u32 %0, [%1], 7;" : "=r"(old) : "r"(cnt) : "memory");
  return old == 7;
}
__device__ __forceinline__ int mod7(int v) { return v >= 7 ? v - 7 : v; }

#define IDS const int tid = opaque(tid0), lane = tid & 31, t = tid & 127, wg = tid >> 7, w = (tid >> 5) & 3; \
            (void)lane; (void)t; (void)wg; (void)w;

__global__ void __launch_bounds__(384, 1)
fused_kernel(const Params p, const __grid_constant__ CUtensorMap tm_x, const __grid_constant__ CUtensorMap tm_w1,
             const __grid_constant__ CUtensorMap tm_w2, const __grid_constant__ CUtensorMap tm_out) {
  const uint32_t sb = smem_u32(smem_raw);
  const uint32_t ms = sb + OFF_M;
  const uint32_t bar0 = ms + M_BAR;
  const int tid0 = threadIdx.x;
  const int b = blockIdx.x;
  const bool is_ssm = b >= NMLP;
  const int G = b / NRK, rk = b - G * NRK;
  const int kc0 = (G + rk) % 7;
  TSINIT();
  TSTAMP(0);
  {
    IDS
    TSTAMP(28);
    uint4 ld[7];
    KgIn kin;
    unsigned ep = 0;
    uint32_t b1w;
    const int rl = 2 * (tid >> 5) + (lane >> 4);
    {
      const int d = is_ssm ? 2 * (112 + 3 * (b - NMLP) + wg) + (w >> 1) : (wg < 2 ? 2 * b + wg : 336 + b);
      const int off = d * NST + 64 * (is_ssm ? 2 * (w & 1) : w) + 2 * lane;
      const __nv_bfloat16* P[10] = {p.a_re + off, p.a_im + off, p.b_re + off, p.b_im + off, p.c_re + off, p.c_im + off,
                                    p.log_dt + (d & ~1), p.dskip + (d & ~1), p.b1 + 64 * (is_ssm ? 0 : b >> 2) + (t & 62),
                                    wg < 2 ? p.x + (size_t)(16 * (b & 127) + rl) * D_ + 4 * (lane & 15)
                                           : p.w1 + (size_t)(112 * (b & 3) + (t >> 3)) * F_ + 64 * (is_ssm ? 0 : b >> 2) + 8 * (t & 7)};
      const unsigned* pe = &p.s->epoch;
      asm volatile("" : "+l"(P[0]), "+l"(P[1]), "+l"(P[2]), "+l"(P[3]), "+l"(P[4]), "+l"(P[5]), "+l"(P[6]), "+l"(P[7]), "+l"(P[8]), "+l"(P[9]), "+l"(pe));
#pragma unroll
      for (int i = 0; i < 6; i++) kin.cur[i] = ldg32(P[i], 0);
      kin.ldt = ldg32(P[6], 0); kin.dk = ldg32(P[7], 0); b1w = ldg32(P[8], 0);
      if (tid == 256 + 32) ep = ld_relaxed1(pe);
#pragma unroll
      for (int i = 0; i < 6; i++) kin.nxt[i] = 0u;
      if (is_ssm) {
#pragma unroll
        for (int i = 0; i < 6; i++) kin.nxt[i] = ldg32(P[i], 128);
      }
      if (wg < 2) {
#pragma unroll
        for (int i = 0; i < 7; i++) asm volatile("ld.global.nc.v2.b32 {%0,%1}, [%2];" : "=r"(ld[i].x), "=r"(ld[i].y) : "l"(P[9] + 64 * i));
      } else {
#pragma unroll
        for (int i = 0; i < 7; i++)
          asm volatile("ld.global.nc.v4.b32 {%0,%1,%2,%3}, [%4];" : "=r"(ld[i].x), "=r"(ld[i].y), "=r"(ld[i].z), "=r"(ld[i].w) : "l"(P[9] + (size_t)i * 16 * F_));
      }
      asm volatile("" :: "l"(P[0]), "l"(P[1]), "l"(P[2]), "l"(P[3]), "l"(P[4]), "l"(P[5]), "l"(P[6]), "l"(P[7]), "l"(P[8]), "l"(P[9]), "l"(pe));
      kin.odd = d & 1;
    }
    const uint32_t tbl = is_ssm ? sb + (4 * wg + (w >> 1)) * TBL : sb + OFF_T + wg * TBL;
#pragma unroll 1
    for (int i = is_ssm ? t & 63 : t; i < TBL_SC / 16; i += is_ssm ? 64 : 128) sts128(tbl + i * 16, 0u, 0u, 0u, 0u);
    const uint32_t lns = is_ssm ? sb + S_WORK + 2 * S_WGB + 4 * KSTG : sb + OFF_X + 2 * 16384;
    const int wi = __shfl_sync(0xffffffffu, tid >> 5, 0);
    if (wi < 4 && lane == 0) {
      if (wi < 3) mbar_init(bar0 + 8 * wi, 1);
      asm volatile("fence.mbarrier_init.release.cluster;" ::: "memory");
      if (!is_ssm) asm volatile("prefetch.tensormap [%0];" ::"l"(wi == 0 ? &tm_x : wi == 1 ? &tm_w1 : wi == 2 ? &tm_w2 : &tm_out) : "memory");
    }
    __syncwarp();
    if (wi == 4 && lane < 16) asm volatile("st.shared.b32 [%0], 0;" ::"r"(ms + M_REL + 4 * lane) : "memory");
    TSTAMP(31);
    auto mid = [&]() {
    TSTAMP(30);
    if (wg < 2) {
      uint32_t u[14];
#pragma unroll
      for (int i = 0; i < 7; i++) { u[2 * i] = ld[i].x; u[2 * i + 1] = ld[i].y; }
      ln_rows(u, ms + M_LT + rl * 16, lns + ((rl & 1) | ((rl >> 2) << 1) | ((rl & 2) << 2)) * 912, lane);
      bar_arrive(7, 384);
    } else {
      float cs[8];
#pragma unroll
      for (int k = 0; k < 8; k++) cs[k] = 0.f;
#pragma unroll
      for (int i = 0; i < 7; i++) {
        const uint32_t uu[4] = {ld[i].x, ld[i].y, ld[i].z, ld[i].w};
#pragma unroll
        for (int k = 0; k < 4; k++) { cs[2 * k] += bf_lo(uu[k]); cs[2 * k + 1] += bf_hi(uu[k]); }
      }
#pragma unroll
      for (int st = 0; st < 2; st++) {
        const int n = 4 >> st;
        const bool up = (lane >> (4 - st)) & 1;
#pragma unroll
        for (int k = 0; k < n; k++) {
          const float give = up ? cs[k] : cs[k + n], keep = up ? cs[k + n] : cs[k];
          cs[k] = keep + __shfl_xor_sync(0xffffffffu, give, 16 >> st);
        }
      }
      sts64f(ms + M_CSR + (w * 64 + (lane & 7) * 8 + (lane >> 3) * 2) * 4, cs[0], cs[1]);
      if (t == 32) { asm volatile("st.shared.b32 [%0], %1;" ::"r"(ms + M_EP), "r"(ep + 1) : "memory"); red_relaxed(&p.s->cntA); }
      bar_sync(7, 384);
      const uint32_t la = lns + (lane & 15) * 912 + (lane >> 4) * 16 + w * 224;
      uint2* dst = (uint2*)(p.s->xnT + (size_t)(56 * w + (lane >> 3)) * 512 + 4 * b) + (lane & 7);
      uint32_t r[28];
#pragma unroll
      for (int k = 0; k < 7; k++) ldsm4t(la + k * 32, r[4 * k], r[4 * k + 1], r[4 * k + 2], r[4 * k + 3]);
      const uint32_t tag = lds32(ms + M_EP) & 1;
      fence_async();
      bar_sync(6, 128);
      if (b < 128) {
#pragma unroll
        for (int k = 0; k < 14; k++) st_relaxed2(dst + k * 4096, (r[2 * k] & ~1u) | tag, (r[2 * k + 1] & ~1u) | tag);
      }
      if (t < 64 && !is_ssm) {
        const uint32_t a = ms + M_CSR + t * 4;
        const float c = -((lds32f(a) + lds32f(a + 256)) + (lds32f(a + 512) + lds32f(a + 768)));
        const float ch = rbf(c);
        uint2* dx = (uint2*)(p.s->bx + (b >> 4) * 512 + ((b >> 1) & 1) * 256 + ((b >> 2) & 3) * 64 + t) + (b & 1);
        const float b1v = (b & 2) ? 0.f : ((t & 1) ? bf_hi(b1w) : bf_lo(b1w));
        asm volatile("{.reg .b64 a; mov.b64 a, {%1,%2}; st.relaxed.gpu.global.b64 [%0], a;}"
                     ::"l"(dx), "r"(pack_bf2(ch, b1v)), "r"((pack_bf2(c - ch, ch) & ~1u) | tag) : "memory");
      }
      if (t >= 64 && t < 80 && b < 128) {
        const uint4 a = lds128(ms + M_LT + (t - 64) * 16);
        st_b128(p.s->ax + 16 * b + t - 64, tag, a.x, a.y, a.z, a.w);
      }
    }
    if ((wi == 0 || wi == 1 || wi == 10) && lane == 0 && !is_ssm) {
      const int i = wi & 3, kc = mod7(kc0 + i);
      mbar_expect(bar0 + 8 * i, 49152);
      tma_2d(sb + OFF_X + i * 16384, &tm_x, 64 * kc, 128 * G, bar0 + 8 * i);
      tma_3d(sb + OFF_W + i * 32768, &tm_w1, 0, 64 * kc, 4 * rk, bar0 + 8 * i);
    }
    __syncwarp();
    TSTAMP(29);
    };
    const uint32_t stg = is_ssm ? sb + S_WORK + wg * S_WGB + w * KSTG : sb + (wg < 2 ? OFF_A + 4 * wg * KSTG : OFF_B) + w * KSTG;
    kgen_warp(kin, is_ssm ? 2 : 1, stg, tbl, lane, mid);
  }
  TSTAMP(1);
  uint4 v[4], tv[5];
  {
    IDS
    bar_sync(4 + wg, 128);
    if (!is_ssm && wg == 2) {
#pragma unroll
      for (int q = 0; q < 4; q++) tv[q] = ld_2x64(p.s->bx + 512 * rk + q * 128 + t);
      tv[4] = ld_b128(p.s->ax + 128 * G + t);
    }
    if (is_ssm || wg == 2) {
      const uint4* src = p.s->xnT + (size_t)(is_ssm ? 112 + 3 * (b - NMLP) + wg : b) * 512 + t;
#pragma unroll
      for (int q = 0; q < 4; q++) v[q] = ld_relaxed4(src + q * 128);
    }
#pragma unroll 1
    for (int c = is_ssm ? 1 : 0; c >= 0; c--) {
      const uint32_t src = is_ssm ? sb + S_WORK + wg * S_WGB + 2 * c * KSTG : sb + (wg < 2 ? OFF_A + 4 * wg * KSTG : OFF_B);
      ktab_build(src, !is_ssm, w, is_ssm ? sb + (4 * wg + c) * TBL : sb + OFF_T + wg * TBL, lane);
    }
    fence_async();
  }
  TSTAMP(2);
  __syncthreads();

  if (is_ssm || __shfl_sync(0xffffffffu, tid0 >> 7, 0) == 2) {
    asm volatile("setmaxnreg.dec.sync.aligned.u32 136;");
    if (!is_ssm) {
      IDS
      const unsigned ep1 = lds32(ms + M_EP);
#pragma unroll 1
      for (int it = 0; it < 16 * RETRY_MAX; it++) {
        uint32_t bad = tv[4].x ^ ep1;
#pragma unroll
        for (int q = 0; q < 4; q++) bad |= (tv[q].y ^ ep1) | (tv[q].w ^ ep1);
        if (!__any_sync(0xffffffffu, bad & 1)) break;
        __nanosleep(200);
#pragma unroll
        for (int q = 0; q < 4; q++) tv[q] = ld_2x64(p.s->bx + 512 * rk + q * 128 + t);
        tv[4] = ld_b128(p.s->ax + 128 * G + t);
      }
#pragma unroll
      for (int q = 0; q < 5; q++) sts128(sb + OFF_B + (q < 4 ? B_BX + q * 2048 : B_AX) + t * 16, tv[q].x, tv[q].y, tv[q].z, tv[q].w);
      fence_async();
      bar_arrive(1, 384);
      if (t == 96) { bulk_s2g(p.s->tbl + b * (TBL / 16), sb + OFF_T + 2 * TBL, TBL); bulk_commit(); }
      if (t == 64)
        asm volatile("cp.async.bulk.prefetch.L2.global [%0], %1;" ::"l"(p.w2 + (size_t)(256 * rk + 16 * G) * D_), "r"(16 * D_ * 2) : "memory");
    }
#pragma unroll 1
    for (int pi = opaque(0); ; pi++) {
      {
        IDS
        const unsigned ep1 = lds32(ms + M_EP);
        const int pair = !is_ssm ? b : (pi == 0 ? 112 + 3 * (b - NMLP) : (b < NMLP + 12 ? 172 + 3 * (b - NMLP) : 184 + 2 * (b - NMLP))) + wg;
        const uint32_t work = is_ssm ? sb + S_WORK + wg * S_WGB : sb + OFF_A;
        const uint32_t z = work + SIG_V3 - 1024 + (t >> 6) * 4096 + (t & 63) * 16;
        sts128(z, 0u, 0u, 0u, 0u); sts128(z + SIG, 0u, 0u, 0u, 0u);
        if (t < 72) {
          const uint32_t zu = work + SIG_U + (t & 7) * U_LBO + (t >> 3) * 16;
          sts128(zu, 0u, 0u, 0u, 0u); sts128(zu + SIG, 0u, 0u, 0u, 0u);
        }
        const uint4* src = p.s->xnT + (size_t)pair * 512 + t;
#pragma unroll 1
        for (int it = 0; it < RETRY_MAX; it++) {
          uint32_t bad = 0;
#pragma unroll
          for (int q = 0; q < 4; q++) bad |= (((v[q].x ^ ep1) | (v[q].y ^ ep1) | (v[q].z ^ ep1) | (v[q].w ^ ep1)) & 1) << q;
          const unsigned m = __ballot_sync(0xffffffffu, bad);
          if (!m) break;
          if (lane == __ffs(m) - 1) poll_tag((const unsigned*)(src + (__ffs(bad) - 1) * 128) + 3, ep1);
          __syncwarp();
#pragma unroll
          for (int q = 0; q < 4; q++) v[q] = ld_relaxed4(src + q * 128);
        }
        TSTAMP(5);
        const uint32_t a = work + ((t >> 1) & 1) * SIG + SIG_U + (2 * ((t >> 2) & 3) + (t & 1)) * U_LBO + ((t >> 4) + 9) * 16;
#pragma unroll
        for (int q = 0; q < 4; q++) sts128(a + q * 128, v[q].x & ~1u, v[q].y & ~1u, v[q].z & ~1u, v[q].w & ~1u);
        bar_sync(4 + wg, 128);
#pragma unroll 1
        for (int k = w; k < 6; k += 4) sig_windows(work + (k & 1) * SIG, (k >> 1) * 32 + lane);
        fence_async();
        if (t == 96 && !is_ssm) { bulk_wait0(); red_release(&p.s->cntT); }
        if (pi == 1) mbar_wait(bar0 + 8 * wg, 0);
        TSTAMP(6);
        bar_sync(is_ssm ? 4 + wg : 3, is_ssm ? 128 : 384);
        TSTAMP(7);
      }
      uint32_t keep[8];
      float res[16];
#pragma unroll 1
      for (int c = 0; c < 2; c++) {
        IDS
        const int wgu = __shfl_sync(0xffffffffu, wg, 0);
        const uint32_t work = is_ssm ? sb + S_WORK + wgu * S_WGB : sb + OFF_A;
        const uint32_t tbl = (is_ssm ? sb + (4 * wgu + 2 * pi) * TBL : sb + OFF_T) + c * TBL;
        conv_channel(tbl, work + c * SIG, is_ssm ? work + 2 * SIG + Y3B : sb + OFF_B, work + 2 * SIG, lds32f(tbl + TBL_SC), w, lane, 4 + wgu, res, 16 + 3 * (2 * pi + c));
        const float os = lds32f(tbl + TBL_SC + 4);
        if (c == 0) {
#pragma unroll
          for (int i = 0; i < 8; i++) keep[i] = pack_bf2(res[2 * i] * os, res[2 * i + 1] * os);
          if (is_ssm && pi == 0 && t == 96 && (b < NMLP + 12 || wg < 2)) {
            wait_count(&p.s->cntT, lds32(ms + M_EP) * NMLP);
            asm volatile("fence.proxy.async;" ::: "memory");
            mbar_expect(bar0 + 8 * wg, 2 * TBL);
            bulk_g2s(sb + (4 * wg + 2) * TBL, p.s->tbl + (2 * ((b < NMLP + 12 ? 172 + 3 * (b - NMLP) : 184 + 2 * (b - NMLP)) + wg) - 336) * (TBL / 16),
                     2 * TBL, bar0 + 8 * wg);
          }
          __syncwarp();
        } else {
          const int pair = !is_ssm ? b : (pi == 0 ? 112 + 3 * (b - NMLP) : (b < NMLP + 12 ? 172 + 3 * (b - NMLP) : 184 + 2 * (b - NMLP))) + wg;
          uint4* dst = p.s->s2 + ((size_t)(lane & 3) * 224 + pair) * 32 + w * 8 + (lane >> 2);
          const uint32_t tag = lds32(ms + M_EP) & 1;
#pragma unroll
          for (int nt = 0; nt < 4; nt++) {
            const uint32_t n0 = pack_bf2(res[4 * nt] * os, res[4 * nt + 1] * os), n1 = pack_bf2(res[4 * nt + 2] * os, res[4 * nt + 3] * os);
            st_b128(dst + nt * 4 * 224 * 32, tag, __byte_perm(keep[2 * nt], n0, 0x5410), __byte_perm(keep[2 * nt + 1], n1, 0x5410),
                    __byte_perm(keep[2 * nt], n0, 0x7632), __byte_perm(keep[2 * nt + 1], n1, 0x7632));
          }
        }
      }
      TSTAMP(8 + pi);
      {
        IDS
        if (pi == 1 || !is_ssm || (b >= NMLP + 12 && wg == 2)) break;
        const uint4* src = p.s->xnT + (size_t)((b < NMLP + 12 ? 172 + 3 * (b - NMLP) : 184 + 2 * (b - NMLP)) + wg) * 512 + t;
#pragma unroll
        for (int q = 0; q < 4; q++) v[q] = ld_relaxed4(src + q * 128);
      }
    }
    if (!is_ssm) {
      IDS
      const uint32_t tag = lds32(ms + M_EP) & 1;
      float pre[64];
#pragma unroll
      for (int i = 0; i < 64; i++) pre[i] = 0.f;
#pragma unroll 1
      for (int s = 0; s < 4; s++) recv_part<8, 128>(p.s->part + ((size_t)b * 6 + s) * 1024 + t, tag, pre);
      bar_sync(6, 128);
#pragma unroll
      for (int i = 0; i < 16; i++)
        sts128(sb + OFF_A + ((2 * (i >> 2) + (i & 1)) * 256 + ((i >> 1) & 1) * 128 + t) * 16, __float_as_uint(pre[4 * i]),
               __float_as_uint(pre[4 * i + 1]), __float_as_uint(pre[4 * i + 2]), __float_as_uint(pre[4 * i + 3]));
      bar_arrive(2, 384);
      if (b == 0 && t == 0) {
        const unsigned ep1 = lds32(ms + M_EP);
        wait_count(&p.s->cntA, ep1 * NCTA);
        *(volatile unsigned*)&p.s->epoch = ep1;
      }
      TSTAMP(12);
    }
    TSDUMP();
  } else {
    bar_arrive(1, 384);
    asm volatile("setmaxnreg.inc.sync.aligned.u32 192;");
    bar_sync(7, 384);
    uint32_t H[64];
    {
      float acc[128];
      float p0, q0, p1, q1;
      {
        IDS
        const int wgu = __shfl_sync(0xffffffffu, wg, 0);
        int sl = 0;
#pragma unroll 1
        for (int s = 0; s < 7; s++) {
          mbar_wait(bar0 + 8 * sl, (s >= 3 && s < 6));
          TSTAMP(17 + s);
          const uint64_t da = mkdesc(sb + OFF_X + sl * 16384 + wgu * 8192, 16, 1024, 1);
          const uint64_t db = mkdesc(sb + OFF_W + sl * 32768, 8192, 1024, 1);
          wg_fence();
#pragma unroll
          for (int k = 0; k < 4; k++) wg_ss_bf16_n256(acc, da + 2 * k, db + 128 * k, (s | k) != 0);
          wg_commit();
          wg_wait<1>();
          const int pl = sl == 0 ? 2 : sl - 1;
          sl = sl == 2 ? 0 : sl + 1;
          if (s > 0 && lane == 0 && last_release(ms + M_REL + 4 * s)) {
            mbar_expect(bar0 + 8 * pl, s == 5 ? 32768 : 49152);
            if (s < 5) tma_3d(sb + OFF_W + pl * 32768, &tm_w1, 0, 64 * mod7(kc0 + s + 2), 4 * rk, bar0 + 8 * pl);
            else tma_2d(sb + OFF_W + pl * 32768, &tm_w2, 64 * mod7(rk + s - 4), 256 * rk, bar0 + 8 * pl);
            if (s != 5) tma_2d(sb + OFF_X + pl * 16384, &tm_x, 64 * (s < 5 ? mod7(kc0 + s + 2) : rk), 128 * G, bar0 + 8 * pl);
          }
        }
        TSTAMP(9);
        bar_sync(1, 384);
        wg_fence();
        wg_ss_bf16_n256k(acc, mkdesc(sb + OFF_B + B_AX + wgu * 1024, 0, 128, 0), mkdesc(sb + OFF_B + B_BX, 4096, 128, 0), 1);
        wg_commit();
        wg_wait<1>();
        if (lane == 0 && last_release(ms + M_REL + 4 * 7)) {
          mbar_expect(bar0, 65536);
#pragma unroll 1
          for (int c = 2; c < 4; c++) tma_2d(sb + (c - 2) * OFF_X, &tm_w2, 64 * mod7(rk + 1 + c), 256 * rk, bar0);
        }
        bar_arrive(3, 384);
        const uint32_t ra = sb + OFF_B + B_AX + (16 * (tid >> 5) + (lane >> 2)) * 16;
        const float r0 = rcpf_(bf_hi(lds32(ra)) + bf_hi(lds32(ra + 8))), r1 = rcpf_(bf_hi(lds32(ra + 128)) + bf_hi(lds32(ra + 136)));
        p0 = 0.7978845608028654f * r0; q0 = 0.0356774081363001f * r0 * r0 * r0;
        p1 = 0.7978845608028654f * r1; q1 = 0.0356774081363001f * r1 * r1 * r1;
      }
      wg_wait<0>();
      fence_regs<128>(acc);
      TSTAMP(16);
      float hq[4];
#pragma unroll
      for (int i = 0; i < 64; i++) {
        const float pp = (i & 1) ? p1 : p0, qq = (i & 1) ? q1 : q0;
        const float a = acc[2 * i], c = acc[2 * i + 1];
        const float ta = tanhf_(a * fmaf(a * a, qq, pp)), tc = tanhf_(c * fmaf(c * c, qq, pp));
        if (i >= 2) H[i - 2] = pack_bf2v(hq[(i & 1) * 2], hq[(i & 1) * 2 + 1]);
        hq[(i & 1) * 2] = fmaf(a, ta, a); hq[(i & 1) * 2 + 1] = fmaf(c, tc, c);
      }
      H[62] = pack_bf2v(hq[0], hq[1]); H[63] = pack_bf2v(hq[2], hq[3]);
    }
    TSTAMP(3);
    float accA[32], accB[32];
    const uint32_t tag = lds32(ms + M_EP) & 1;
    auto issue2 = [&](int c, float* acc) {
      const uint32_t base = sb + ((0x0213021u >> (4 * c)) & 3) * 32768;
      if (c != 3) mbar_wait(bar0 + 8 * ((0x0210021u >> (4 * c)) & 3), (0x34 >> c) & 1);
      const uint64_t db = mkdesc(base, 8192, 1024, 1);
      wg_fence();
#pragma unroll
      for (int k = 0; k < 16; k++) wg_rs_bf16_n64(acc, H[4 * k], H[4 * k + 1], H[4 * k + 2], H[4 * k + 3], db + 128 * k, k != 0);
      wg_commit();
    };
    auto process = [&](int s, float* acc) {
      wg_wait<1>();
      fence_regs<32>(acc);
      const int tid = opaque(tid0);
      if (s < 3 && (tid & 31) == 0 && last_release(ms + M_REL + 4 * (8 + s))) {
        const int sl = (0x021u >> (4 * s)) & 3;
        mbar_expect(bar0 + 8 * sl, 32768);
        tma_2d(sb + sl * 32768, &tm_w2, 64 * mod7(mod7(rk + 5 + s)), 256 * rk, bar0 + 8 * sl);
      }
      send_part(p.s->part + ((size_t)(G * 7 + mod7(rk + 1 + s)) * 6 + s) * 1024 + tid, tag, acc);
      TSTAMP(10 + s);
    };
    issue2(0, accA);
#pragma unroll
    for (int s = 0; s < 6; s += 2) {
      issue2(s + 1, accB);
      process(s, accA);
      issue2(s + 2, accA);
      process(s + 1, accB);
    }
    TSTAMP(4);
    IDS
    const int g = lane >> 2, tq = lane & 3;
    uint32_t sw[16];
    {
      const uint4* sp = p.s->s2 + ((size_t)G * 224 + 32 * rk + tq) * 32 + w * 8 + g;
#pragma unroll 1
      for (int it = 0; it < RETRY_MAX; it++) {
        uint32_t bad = 0;
#pragma unroll
        for (int i = 0; i < 8; i++) {
          const uint4 v = ld_b128(sp + i * 4 * 32);
          bad |= ((v.x ^ tag) & 1) << i;
          sw[2 * i] = wg ? v.z : v.x; sw[2 * i + 1] = wg ? v.w : v.y;
        }
        const unsigned m = __ballot_sync(0xffffffffu, bad);
        if (!m) break;
        if (lane == __ffs(m) - 1) poll_tag((const unsigned*)(sp + (__ffs(bad) - 1) * 4 * 32), tag);
        __syncwarp();
      }
    }
    TSTAMP(5);
    uint32_t b2w[8];
#pragma unroll
    for (int i = 0; i < 8; i++) b2w[i] = __ldg((const uint32_t*)(p.b2 + 64 * rk) + 4 * i + tq);
    wg_wait<0>();
    fence_regs<32>(accA);
    TSTAMP(6);
    bar_sync(2, 384);
#pragma unroll
    for (int i = 0; i < 8; i++) {
      const uint4 v = lds128(sb + OFF_A + (i * 256 + tid) * 16);
      accA[4 * i] += __uint_as_float(v.x); accA[4 * i + 1] += __uint_as_float(v.y);
      accA[4 * i + 2] += __uint_as_float(v.z); accA[4 * i + 3] += __uint_as_float(v.w);
    }
    const uint32_t xa = sb + OFF_X + 2 * 16384 + (16 * (tid >> 5) + (lane & 15)) * 128;
    uint32_t xw[16];
#pragma unroll
    for (int q = 0; q < 4; q++) ldsm4(xa + (((2 * q + (lane >> 4)) ^ (lane & 7)) << 4), xw[4 * q], xw[4 * q + 1], xw[4 * q + 2], xw[4 * q + 3]);
    const uint32_t ra = sb + OFF_B + B_AX + (16 * (tid >> 5) + g) * 16;
    const float r0 = 0.5f * rcpf_(bf_hi(lds32(ra)) + bf_hi(lds32(ra + 8))), r1 = 0.5f * rcpf_(bf_hi(lds32(ra + 128)) + bf_hi(lds32(ra + 136)));
#pragma unroll 1
    for (int s = 4; s < 6; s++) recv_part<4, 256>(p.s->part + ((size_t)b * 6 + s) * 1024 + tid, tag, accA);
    TSTAMP(7);
#pragma unroll
    for (int k = 0; k < 16; k++) {
      const float rr = (k & 1) ? r1 : r0;
      const float o0 = fmaf(accA[2 * k], rr, bf_lo(b2w[k >> 1])), o1 = fmaf(accA[2 * k + 1], rr, bf_hi(b2w[k >> 1]));
      const float g0 = o0 * rcpf_(1.f + ex2f(o0 * -1.4426950408889634f)), g1 = o1 * rcpf_(1.f + ex2f(o1 * -1.4426950408889634f));
      xw[k] = pack_bf2(fmaf(bf_lo(sw[k]), g0, bf_lo(xw[k])), fmaf(bf_hi(sw[k]), g1, bf_hi(xw[k])));
    }
#pragma unroll
    for (int q = 0; q < 4; q++) stsm4(xa + (((2 * q + (lane >> 4)) ^ (lane & 7)) << 4), xw[4 * q], xw[4 * q + 1], xw[4 * q + 2], xw[4 * q + 3]);
    fence_async();
    __syncwarp();
    if (lane == 0) {
      tma_store_2d(&tm_out, sb + OFF_X + 2 * 16384 + (tid >> 5) * 2048, 64 * rk, 128 * G + 16 * (tid >> 5));
      bulk_commit();
      bulk_wait0_read();
    }
    TSTAMP(8);
    TSDUMP();
  }
}

typedef CUresult (*EncodeFn)(CUtensorMap*, CUtensorMapDataType, cuuint32_t, void*, const cuuint64_t*, const cuuint64_t*,
                             const cuuint32_t*, const cuuint32_t*, CUtensorMapInterleave, CUtensorMapSwizzle,
                             CUtensorMapL2promotion, CUtensorMapFloatOOBfill);

void make_map(EncodeFn fn, CUtensorMap* m, const void* ptr, int rank, const cuuint64_t* dims, const cuuint64_t* strides, const cuuint32_t* box) {
  const cuuint32_t es[3] = {1, 1, 1};
  fn(m, CU_TENSOR_MAP_DATA_TYPE_BFLOAT16, rank, const_cast<void*>(ptr), dims, strides, box, es, CU_TENSOR_MAP_INTERLEAVE_NONE,
     CU_TENSOR_MAP_SWIZZLE_128B, CU_TENSOR_MAP_L2_PROMOTION_L2_128B, CU_TENSOR_MAP_FLOAT_OOB_FILL_NONE);
}

}

extern "C" void kernel_launch(void* const* d_in, const int* in_sizes, int n_in, void* d_out, int out_size) {
  (void)in_sizes; (void)n_in; (void)out_size;
  void* fnp = nullptr;
  cudaDriverEntryPointQueryResult qr;
  cudaGetDriverEntryPoint("cuTensorMapEncodeTiled", &fnp, cudaEnableDefault, &qr);
  EncodeFn fn = (EncodeFn)fnp;
  Params p;
  p.x = (const __nv_bfloat16*)d_in[0];
  p.a_re = (const __nv_bfloat16*)d_in[1]; p.a_im = (const __nv_bfloat16*)d_in[2];
  p.b_re = (const __nv_bfloat16*)d_in[3]; p.b_im = (const __nv_bfloat16*)d_in[4];
  p.c_re = (const __nv_bfloat16*)d_in[5]; p.c_im = (const __nv_bfloat16*)d_in[6];
  p.log_dt = (const __nv_bfloat16*)d_in[7]; p.dskip = (const __nv_bfloat16*)d_in[8];
  p.w1 = (const __nv_bfloat16*)d_in[10]; p.b1 = (const __nv_bfloat16*)d_in[11];
  p.w2 = (const __nv_bfloat16*)d_in[12]; p.b2 = (const __nv_bfloat16*)d_in[13];
  void* sp = nullptr;
  cudaGetSymbolAddress(&sp, g_scr);
  p.s = (Scratch*)sp;
  CUtensorMap mx, mw1, mw2, mo;
  {
    const cuuint64_t dims[2] = {448, 2048}, str[1] = {896};
    const cuuint32_t box[2] = {64, 128}, boxo[2] = {64, 16};
    make_map(fn, &mx, p.x, 2, dims, str, box);
    make_map(fn, &mo, d_out, 2, dims, str, boxo);
  }
  {
    const cuuint64_t dims[3] = {64, 448, 28}, str[2] = {3584, 128};
    const cuuint32_t box[3] = {64, 64, 4};
    make_map(fn, &mw1, p.w1, 3, dims, str, box);
  }
  {
    const cuuint64_t dims[2] = {448, 1792}, str[1] = {896};
    const cuuint32_t box[2] = {64, 256};
    make_map(fn, &mw2, p.w2, 2, dims, str, box);
  }
  cudaFuncSetAttribute(fused_kernel, cudaFuncAttributeMaxDynamicSharedMemorySize, SMEM_BYTES);
  fused_kernel<<<NCTA, 384, SMEM_BYTES>>>(p, mx, mw1, mw2, mo);
}
```

```cpp
#include <cuda_runtime.h>
#include <cuda_bf16.h>
#include <cuda_fp16.h>
#include <cuda.h>
#include <stdint.h>

namespace {

constexpr int D_ = 448, NST = 256, F_ = 1792;
constexpr int NRK = 7, NMLP = 112, NCTA = 132;
constexpr int SPIN_MAX = 1 << 20, RETRY_MAX = 512;

struct Scratch {
  unsigned cntA, pad0[31], cntT, pad1[31], epoch, pad2[63];
  uint4 ax[2048];
  uint4 bx[7 * 512];
  uint4 tbl[112 * 329];
  uint4 xnT[224 * 512];
  uint4 s2[16 * 224 * 32];
  uint4 part[16 * 7 * 6 * 1024];
};
__device__ Scratch g_scr;
#define TSTAMP(i)
#define TSINIT()
#define TSDUMP()
extern __shared__ __align__(1024) uint8_t smem_raw[];

constexpr int TBL_SC = 5248, TBL = 5264;
constexpr int TBL_C1 = 2624;
constexpr int SIG = 19584;
constexpr int SIG_U = 0, U_LBO = 656, SIG_V3 = 6272, SIG_V5 = 10368, SIG_V7 = 13440, SIG_V9 = 15488, SIG_V2 = 17536;
constexpr int Y2B = 6528, Y3B = 4352;
constexpr int KREC = 160, KSTG = 32 * KREC;
constexpr int OFF_W = 0, OFF_X = 98304, OFF_A = 147456, OFF_B = OFF_A + 8 * KSTG + 2560, OFF_T = OFF_B + 4 * KSTG;
constexpr int OFF_M = OFF_T + 15872;
constexpr int B_AX = Y2B, B_BX = B_AX + 2048;
constexpr int M_BAR = 0, M_REL = 128, M_EP = 192, M_CSR = 256, M_LT = 1280, M_END = 1536;
constexpr int SMEM_BYTES = OFF_M + M_END + 384;
constexpr int S_WORK = 63232, S_WGB = 2 * SIG + Y2B + Y3B;
static_assert(S_WORK + 3 * S_WGB <= OFF_M && SMEM_BYTES <= 232448, "smem");

struct Params {
  const __nv_bfloat16 *x, *a_re, *a_im, *b_re, *b_im, *c_re, *c_im, *log_dt, *dskip, *w1, *b1, *w2, *b2;
  Scratch* s;
};

__device__ __forceinline__ int opaque(int x) { int v; asm volatile("mov.u32 %0, %1;" : "=r"(v) : "r"(x)); return v; }
__device__ __forceinline__ int rd_bid() { int v; asm volatile("mov.u32 %0, %%ctaid.x;" : "=r"(v)); return v; }
__device__ __forceinline__ uint32_t smem_u32(const void* p) { return (uint32_t)__cvta_generic_to_shared(p); }
__device__ __forceinline__ void mbar_init(uint32_t bar, int cnt) { asm volatile("mbarrier.init.shared::cta.b64 [%0], %1;" ::"r"(bar), "r"(cnt)); }
__device__ __forceinline__ void mbar_expect(uint32_t bar, uint32_t bytes) {
  asm volatile("mbarrier.arrive.expect_tx.shared::cta.b64 _, [%0], %1;" ::"r"(bar), "r"(bytes) : "memory");
}
__device__ __forceinline__ void mbar_wait(uint32_t bar, uint32_t parity) {
  uint32_t done = 0;
#pragma unroll 1
  for (int it = 0; it < SPIN_MAX; it++) {
    asm volatile("{.reg .pred p; mbarrier.try_wait.parity.shared::cta.b64 p, [%1], %2; selp.u32 %0,1,0,p;}"
                 : "=r"(done) : "r"(bar), "r"(parity) : "memory");
    if (done) break;
  }
}
__device__ __forceinline__ void tma_2d(uint32_t dst, const CUtensorMap* m, int c0, int c1, uint32_t bar) {
  asm volatile("cp.async.bulk.tensor.2d.shared::cluster.global.mbarrier::complete_tx::bytes [%0], [%1, {%3, %4}], [%2];"
               ::"r"(dst), "l"(m), "r"(bar), "r"(c0), "r"(c1) : "memory");
}
__device__ __forceinline__ void tma_3d(uint32_t dst, const CUtensorMap* m, int c0, int c1, int c2, uint32_t bar) {
  asm volatile("cp.async.bulk.tensor.3d.shared::cluster.global.mbarrier::complete_tx::bytes [%0], [%1, {%3, %4, %5}], [%2];"
               ::"r"(dst), "l"(m), "r"(bar), "r"(c0), "r"(c1), "r"(c2) : "memory");
}
__device__ __forceinline__ void tma_store_2d(const CUtensorMap* m, uint32_t src, int c0, int c1) {
  asm volatile("cp.async.bulk.tensor.2d.global.shared::cta.bulk_group [%0, {%2, %3}], [%1];"
               ::"l"(m), "r"(src), "r"(c0), "r"(c1) : "memory");
}
__device__ __forceinline__ void bulk_s2g(void* dst, uint32_t src, uint32_t bytes) {
  asm volatile("cp.async.bulk.global.shared::cta.bulk_group [%0], [%1], %2;" ::"l"(dst), "r"(src), "r"(bytes) : "memory");
}
__device__ __forceinline__ void bulk_g2s(uint32_t dst, const void* src, uint32_t bytes, uint32_t bar) {
  asm volatile("cp.async.bulk.shared::cluster.global.mbarrier::complete_tx::bytes [%0], [%1], %2, [%3];"
               ::"r"(dst), "l"(src), "r"(bytes), "r"(bar) : "memory");
}
__device__ __forceinline__ void bulk_commit() { asm volatile("cp.async.bulk.commit_group;" ::: "memory"); }
__device__ __forceinline__ void bulk_wait0() { asm volatile("cp.async.bulk.wait_group 0;" ::: "memory"); }
__device__ __forceinline__ void bulk_wait0_read() { asm volatile("cp.async.bulk.wait_group.read 0;" ::: "memory"); }
__device__ __forceinline__ void fence_async() { asm volatile("fence.proxy.async.shared::cta;" ::: "memory"); }
__device__ __forceinline__ void bar_sync(int id, int n) { asm volatile("bar.sync %0, %1;" ::"r"(id), "r"(n) : "memory"); }
__device__ __forceinline__ void bar_arrive(int id, int n) { asm volatile("bar.arrive %0, %1;" ::"r"(id), "r"(n) : "memory"); }
__device__ __forceinline__ void wg_fence() { asm volatile("wgmma.fence.sync.aligned;" ::: "memory"); }
__device__ __forceinline__ void wg_commit() { asm volatile("wgmma.commit_group.sync.aligned;" ::: "memory"); }
template <int N> __device__ __forceinline__ void wg_wait() { asm volatile("wgmma.wait_group.sync.aligned %0;" ::"n"(N) : "memory"); }
template <int N> __device__ __forceinline__ void fence_regs(float* d) {
#pragma unroll
  for (int i = 0; i < N; i++) asm volatile("" : "+f"(d[i])::"memory");
}
__device__ __forceinline__ uint64_t mkdesc(uint32_t addr, uint32_t lbo, uint32_t sbo, uint32_t sw) {
  return (uint64_t)((addr & 0x3FFFF) >> 4) | ((uint64_t)(lbo >> 4) << 16) | ((uint64_t)(sbo >> 4) << 32) | ((uint64_t)sw << 62);
}
__device__ __forceinline__ uint32_t lds32(uint32_t a) { uint32_t v; asm volatile("ld.shared.b32 %0, [%1];" : "=r"(v) : "r"(a) : "memory"); return v; }
__device__ __forceinline__ float lds32f(uint32_t a) { float v; asm volatile("ld.shared.f32 %0, [%1];" : "=f"(v) : "r"(a) : "memory"); return v; }
__device__ __forceinline__ float2 lds64f(uint32_t a) { float2 v; asm volatile("ld.shared.v2.f32 {%0,%1}, [%2];" : "=f"(v.x), "=f"(v.y) : "r"(a) : "memory"); return v; }
__device__ __forceinline__ uint4 lds128(uint32_t a) {
  uint4 v; asm volatile("ld.shared.v4.b32 {%0,%1,%2,%3}, [%4];" : "=r"(v.x), "=r"(v.y), "=r"(v.z), "=r"(v.w) : "r"(a) : "memory"); return v;
}
__device__ __forceinline__ void sts16(uint32_t a, uint16_t v) { asm volatile("st.shared.b16 [%0], %1;" ::"r"(a), "h"(v) : "memory"); }
__device__ __forceinline__ void sts32f(uint32_t a, float v) { asm volatile("st.shared.f32 [%0], %1;" ::"r"(a), "f"(v) : "memory"); }
__device__ __forceinline__ void sts64f(uint32_t a, float x, float y) { asm volatile("st.shared.v2.f32 [%0], {%1,%2};" ::"r"(a), "f"(x), "f"(y) : "memory"); }
__device__ __forceinline__ void sts128(uint32_t a, uint32_t x, uint32_t y, uint32_t z, uint32_t w) {
  asm volatile("st.shared.v4.b32 [%0], {%1,%2,%3,%4};" ::"r"(a), "r"(x), "r"(y), "r"(z), "r"(w) : "memory");
}
__device__ __forceinline__ void ldsm4(uint32_t a, uint32_t& r0, uint32_t& r1, uint32_t& r2, uint32_t& r3) {
  asm volatile("ldmatrix.sync.aligned.m8n8.x4.shared.b16 {%0,%1,%2,%3}, [%4];" : "=r"(r0), "=r"(r1), "=r"(r2), "=r"(r3) : "r"(a) : "memory");
}
__device__ __forceinline__ void ldsm4t(uint32_t a, uint32_t& r0, uint32_t& r1, uint32_t& r2, uint32_t& r3) {
  asm volatile("ldmatrix.sync.aligned.m8n8.x4.trans.shared.b16 {%0,%1,%2,%3}, [%4];" : "=r"(r0), "=r"(r1), "=r"(r2), "=r"(r3) : "r"(a) : "memory");
}
__device__ __forceinline__ void ldsm2t(uint32_t a, uint32_t& r0, uint32_t& r1) {
  asm volatile("ldmatrix.sync.aligned.m8n8.x2.trans.shared.b16 {%0,%1}, [%2];" : "=r"(r0), "=r"(r1) : "r"(a) : "memory");
}
__device__ __forceinline__ void stsm4(uint32_t a, uint32_t r0, uint32_t r1, uint32_t r2, uint32_t r3) {
  asm volatile("stmatrix.sync.aligned.m8n8.x4.shared.b16 [%0], {%1,%2,%3,%4};" ::"r"(a), "r"(r0), "r"(r1), "r"(r2), "r"(r3) : "memory");
}
__device__ __forceinline__ void mma_f16(float* c, uint32_t a0, uint32_t a1, uint32_t a2, uint32_t a3, uint32_t b0, uint32_t b1) {
  asm("mma.sync.aligned.m16n8k16.row.col.f32.f16.f16.f32 {%0,%1,%2,%3},{%4,%5,%6,%7},{%8,%9},{%0,%1,%2,%3};"
               : "+f"(c[0]), "+f"(c[1]), "+f"(c[2]), "+f"(c[3]) : "r"(a0), "r"(a1), "r"(a2), "r"(a3), "r"(b0), "r"(b1));
}
__device__ __forceinline__ uint4 ld_relaxed4(const void* p) {
  uint4 v; asm volatile("ld.relaxed.gpu.global.v4.b32 {%0,%1,%2,%3}, [%4];" : "=r"(v.x), "=r"(v.y), "=r"(v.z), "=r"(v.w) : "l"(p) : "memory"); return v;
}
__device__ __forceinline__ uint4 ld_2x64(const void* p) {
  uint4 v;
  asm volatile("{.reg .b64 a, c; ld.relaxed.gpu.global.v2.b64 {a, c}, [%4]; mov.b64 {%0,%1}, a; mov.b64 {%2,%3}, c;}"
               : "=r"(v.x), "=r"(v.y), "=r"(v.z), "=r"(v.w) : "l"(p) : "memory");
  return v;
}
__device__ __forceinline__ void st_relaxed2(void* p, uint32_t x, uint32_t y) {
  asm volatile("st.relaxed.gpu.global.v2.b32 [%0], {%1,%2};" ::"l"(p), "r"(x), "r"(y) : "memory");
}
__device__ __forceinline__ uint4 ld_b128(const void* p) {
  uint4 v;
  asm volatile("{.reg .b128 t; .reg .b64 a, c; ld.relaxed.gpu.global.b128 t, [%4]; mov.b128 {a, c}, t; mov.b64 {%0,%1}, a; mov.b64 {%2,%3}, c;}"
               : "=r"(v.x), "=r"(v.y), "=r"(v.z), "=r"(v.w) : "l"(p) : "memory");
  return v;
}
__device__ __forceinline__ void st_b128(void* p, uint32_t tag, uint32_t x, uint32_t y, uint32_t z, uint32_t w) {
  asm volatile("{.reg .b128 t; .reg .b64 a, c; mov.b64 a, {%1,%2}; mov.b64 c, {%3,%4}; mov.b128 t, {a, c}; st.relaxed.gpu.global.b128 [%0], t;}"
               ::"l"(p), "r"((x & ~1u) | tag), "r"(y), "r"(z), "r"(w) : "memory");
}
__device__ __forceinline__ unsigned ld_relaxed1(const unsigned* p) {
  unsigned v; asm volatile("ld.relaxed.gpu.global.u32 %0, [%1];" : "=r"(v) : "l"(p) : "memory"); return v;
}
__device__ __forceinline__ void red_relaxed(unsigned* p) {
  asm volatile("red.relaxed.gpu.global.add.u32 [%0], 1;" ::"l"(p) : "memory");
}
__device__ __forceinline__ void red_release(unsigned* p) {
  asm volatile("red.release.gpu.global.add.u32 [%0], 1;" ::"l"(p) : "memory");
}
__device__ __forceinline__ void wait_count(const unsigned* p, unsigned target) {
#pragma unroll 1
  for (int it = 0; it < SPIN_MAX; it++) {
    if ((int)(ld_relaxed1(p) - target) >= 0) break;
    __nanosleep(40);
  }
  asm volatile("fence.acq_rel.gpu;" ::: "memory");
}
__device__ __forceinline__ uint32_t pack_h2(float lo, float hi) { uint32_t r; asm("cvt.rn.f16x2.f32 %0, %1, %2;" : "=r"(r) : "f"(hi), "f"(lo)); return r; }
__device__ __forceinline__ uint32_t pack_bf2(float lo, float hi) { uint32_t r; asm("cvt.rn.bf16x2.f32 %0, %1, %2;" : "=r"(r) : "f"(hi), "f"(lo)); return r; }
__device__ __forceinline__ uint32_t pack_bf2v(float lo, float hi) { uint32_t r; asm volatile("cvt.rn.bf16x2.f32 %0, %1, %2;" : "=r"(r) : "f"(hi), "f"(lo)); return r; }
__device__ __forceinline__ float bf_lo(uint32_t w) { return __uint_as_float(w << 16); }
__device__ __forceinline__ float bf_hi(uint32_t w) { return __uint_as_float(w & 0xffff0000u); }
__device__ __forceinline__ float rbf(float v) { return __bfloat162float(__float2bfloat16_rn(v)); }
__device__ __forceinline__ float2 h2f(uint32_t w) { return __half22float2(*reinterpret_cast<__half2*>(&w)); }
__device__ __forceinline__ float ex2f(float v) { float r; asm("ex2.approx.ftz.f32 %0, %1;" : "=f"(r) : "f"(v)); return r; }
__device__ __forceinline__ float rcpf_(float v) { float r; asm("rcp.approx.f32 %0, %1;" : "=f"(r) : "f"(v)); return r; }
__device__ __forceinline__ float sqrtf_(float v) { float r; asm("sqrt.approx.f32 %0, %1;" : "=f"(r) : "f"(v)); return r; }
__device__ __forceinline__ float tanhf_(float v) { float r; asm volatile("tanh.approx.f32 %0, %1;" : "=f"(r) : "f"(v)); return r; }

__device__ __forceinline__ void wg_ss_bf16_n256(float* d, uint64_t da, uint64_t db, int sc) {
  asm volatile("{.reg .pred p; setp.ne.b32 p, %130, 0;\n"
    "wgmma.mma_async.sync.aligned.m64n256k16.f32.bf16.bf16 {%0, %1, %2, %3, %4, %5, %6, %7, %8, %9, %10, %11, %12, %13, %14, %15, %16, %17, %18, %19, %20, %21, %22, %23, %24, %25, %26, %27, %28, %29, %30, %31, %32, %33, %34, %35, %36, %37, %38, %39, %40, %41, %42, %43, %44, %45, %46, %47, %48, %49, %50, %51, %52, %53, %54, %55, %56, %57, %58, %59, %60, %61, %62, %63, %64, %65, %66, %67, %68, %69, %70, %71, %72, %73, %74, %75, %76, %77, %78, %79, %80, %81, %82, %83, %84, %85, %86, %87, %88, %89, %90, %91, %92, %93, %94, %95, %96, %97, %98, %99, %100, %101, %102, %103, %104, %105, %106, %107, %108, %109, %110, %111, %112, %113, %114, %115, %116, %117, %118, %119, %120, %121, %122, %123, %124, %125, %126, %127}, %128, %129, p, 1, 1, 0, 1;}\n"
    : "+f"(d[0]), "+f"(d[1]), "+f"(d[2]), "+f"(d[3]), "+f"(d[4]), "+f"(d[5]), "+f"(d[6]), "+f"(d[7]), "+f"(d[8]), "+f"(d[9]), "+f"(d[10]), "+f"(d[11]), "+f"(d[12]), "+f"(d[13]), "+f"(d[14]), "+f"(d[15]), "+f"(d[16]), "+f"(d[17]), "+f"(d[18]), "+f"(d[19]), "+f"(d[20]), "+f"(d[21]), "+f"(d[22]), "+f"(d[23]), "+f"(d[24]), "+f"(d[25]), "+f"(d[26]), "+f"(d[27]), "+f"(d[28]), "+f"(d[29]), "+f"(d[30]), "+f"(d[31]), "+f"(d[32]), "+f"(d[33]), "+f"(d[34]), "+f"(d[35]), "+f"(d[36]), "+f"(d[37]), "+f"(d[38]), "+f"(d[39]), "+f"(d[40]), "+f"(d[41]), "+f"(d[42]), "+f"(d[43]), "+f"(d[44]), "+f"(d[45]), "+f"(d[46]), "+f"(d[47]), "+f"(d[48]), "+f"(d[49]), "+f"(d[50]), "+f"(d[51]), "+f"(d[52]), "+f"(d[53]), "+f"(d[54]), "+f"(d[55]), "+f"(d[56]), "+f"(d[57]), "+f"(d[58]), "+f"(d[59]), "+f"(d[60]), "+f"(d[61]), "+f"(d[62]), "+f"(d[63]), "+f"(d[64]), "+f"(d[65]), "+f"(d[66]), "+f"(d[67]), "+f"(d[68]), "+f"(d[69]), "+f"(d[70]), "+f"(d[71]), "+f"(d[72]), "+f"(d[73]), "+f"(d[74]), "+f"(d[75]), "+f"(d[76]), "+f"(d[77]), "+f"(d[78]), "+f"(d[79]), "+f"(d[80]), "+f"(d[81]), "+f"(d[82]), "+f"(d[83]), "+f"(d[84]), "+f"(d[85]), "+f"(d[86]), "+f"(d[87]), "+f"(d[88]), "+f"(d[89]), "+f"(d[90]), "+f"(d[91]), "+f"(d[92]), "+f"(d[93]), "+f"(d[94]), "+f"(d[95]), "+f"(d[96]), "+f"(d[97]), "+f"(d[98]), "+f"(d[99]), "+f"(d[100]), "+f"(d[101]), "+f"(d[102]), "+f"(d[103]), "+f"(d[104]), "+f"(d[105]), "+f"(d[106]), "+f"(d[107]), "+f"(d[108]), "+f"(d[109]), "+f"(d[110]), "+f"(d[111]), "+f"(d[112]), "+f"(d[113]), "+f"(d[114]), "+f"(d[115]), "+f"(d[116]), "+f"(d[117]), "+f"(d[118]), "+f"(d[119]), "+f"(d[120]), "+f"(d[121]), "+f"(d[122]), "+f"(d[123]), "+f"(d[124]), "+f"(d[125]), "+f"(d[126]), "+f"(d[127])
    : "l"(da), "l"(db), "r"(sc));
}

__device__ __forceinline__ void wg_ss_bf16_n256k(float* d, uint64_t da, uint64_t db, int sc) {
  asm volatile("{.reg .pred p; setp.ne.b32 p, %130, 0;\n"
    "wgmma.mma_async.sync.aligned.m64n256k16.f32.bf16.bf16 {%0, %1, %2, %3, %4, %5, %6, %7, %8, %9, %10, %11, %12, %13, %14, %15, %16, %17, %18, %19, %20, %21, %22, %23, %24, %25, %26, %27, %28, %29, %30, %31, %32, %33, %34, %35, %36, %37, %38, %39, %40, %41, %42, %43, %44, %45, %46, %47, %48, %49, %50, %51, %52, %53, %54, %55, %56, %57, %58, %59, %60, %61, %62, %63, %64, %65, %66, %67, %68, %69, %70, %71, %72, %73, %74, %75, %76, %77, %78, %79, %80, %81, %82, %83, %84, %85, %86, %87, %88, %89, %90, %91, %92, %93, %94, %95, %96, %97, %98, %99, %100, %101, %102, %103, %104, %105, %106, %107, %108, %109, %110, %111, %112, %113, %114, %115, %116, %117, %118, %119, %120, %121, %122, %123, %124, %125, %126, %127}, %128, %129, p, 1, 1, 0, 0;}\n"
    : "+f"(d[0]), "+f"(d[1]), "+f"(d[2]), "+f"(d[3]), "+f"(d[4]), "+f"(d[5]), "+f"(d[6]), "+f"(d[7]), "+f"(d[8]), "+f"(d[9]), "+f"(d[10]), "+f"(d[11]), "+f"(d[12]), "+f"(d[13]), "+f"(d[14]), "+f"(d[15]), "+f"(d[16]), "+f"(d[17]), "+f"(d[18]), "+f"(d[19]), "+f"(d[20]), "+f"(d[21]), "+f"(d[22]), "+f"(d[23]), "+f"(d[24]), "+f"(d[25]), "+f"(d[26]), "+f"(d[27]), "+f"(d[28]), "+f"(d[29]), "+f"(d[30]), "+f"(d[31]), "+f"(d[32]), "+f"(d[33]), "+f"(d[34]), "+f"(d[35]), "+f"(d[36]), "+f"(d[37]), "+f"(d[38]), "+f"(d[39]), "+f"(d[40]), "+f"(d[41]), "+f"(d[42]), "+f"(d[43]), "+f"(d[44]), "+f"(d[45]), "+f"(d[46]), "+f"(d[47]), "+f"(d[48]), "+f"(d[49]), "+f"(d[50]), "+f"(d[51]), "+f"(d[52]), "+f"(d[53]), "+f"(d[54]), "+f"(d[55]), "+f"(d[56]), "+f"(d[57]), "+f"(d[58]), "+f"(d[59]), "+f"(d[60]), "+f"(d[61]), "+f"(d[62]), "+f"(d[63]), "+f"(d[64]), "+f"(d[65]), "+f"(d[66]), "+f"(d[67]), "+f"(d[68]), "+f"(d[69]), "+f"(d[70]), "+f"(d[71]), "+f"(d[72]), "+f"(d[73]), "+f"(d[74]), "+f"(d[75]), "+f"(d[76]), "+f"(d[77]), "+f"(d[78]), "+f"(d[79]), "+f"(d[80]), "+f"(d[81]), "+f"(d[82]), "+f"(d[83]), "+f"(d[84]), "+f"(d[85]), "+f"(d[86]), "+f"(d[87]), "+f"(d[88]), "+f"(d[89]), "+f"(d[90]), "+f"(d[91]), "+f"(d[92]), "+f"(d[93]), "+f"(d[94]), "+f"(d[95]), "+f"(d[96]), "+f"(d[97]), "+f"(d[98]), "+f"(d[99]), "+f"(d[100]), "+f"(d[101]), "+f"(d[102]), "+f"(d[103]), "+f"(d[104]), "+f"(d[105]), "+f"(d[106]), "+f"(d[107]), "+f"(d[108]), "+f"(d[109]), "+f"(d[110]), "+f"(d[111]), "+f"(d[112]), "+f"(d[113]), "+f"(d[114]), "+f"(d[115]), "+f"(d[116]), "+f"(d[117]), "+f"(d[118]), "+f"(d[119]), "+f"(d[120]), "+f"(d[121]), "+f"(d[122]), "+f"(d[123]), "+f"(d[124]), "+f"(d[125]), "+f"(d[126]), "+f"(d[127])
    : "l"(da), "l"(db), "r"(sc));
}

__device__ __forceinline__ void wg_rs_bf16_n64(float* d, uint32_t a0, uint32_t a1, uint32_t a2, uint32_t a3, uint64_t db, int sc) {
  asm volatile("{.reg .pred p; setp.ne.b32 p, %37, 0;\n"
    "wgmma.mma_async.sync.aligned.m64n64k16.f32.bf16.bf16 {%0, %1, %2, %3, %4, %5, %6, %7, %8, %9, %10, %11, %12, %13, %14, %15, %16, %17, %18, %19, %20, %21, %22, %23, %24, %25, %26, %27, %28, %29, %30, %31}, {%32,%33,%34,%35}, %36, p, 1, 1, 1;}\n"
    : "+f"(d[0]), "+f"(d[1]), "+f"(d[2]), "+f"(d[3]), "+f"(d[4]), "+f"(d[5]), "+f"(d[6]), "+f"(d[7]), "+f"(d[8]), "+f"(d[9]), "+f"(d[10]), "+f"(d[11]), "+f"(d[12]), "+f"(d[13]), "+f"(d[14]), "+f"(d[15]), "+f"(d[16]), "+f"(d[17]), "+f"(d[18]), "+f"(d[19]), "+f"(d[20]), "+f"(d[21]), "+f"(d[22]), "+f"(d[23]), "+f"(d[24]), "+f"(d[25]), "+f"(d[26]), "+f"(d[27]), "+f"(d[28]), "+f"(d[29]), "+f"(d[30]), "+f"(d[31])
    : "r"(a0), "r"(a1), "r"(a2), "r"(a3), "l"(db), "r"(sc));
}

__device__ __forceinline__ void wg_rs_f16_n32k(float* d, uint32_t a0, uint32_t a1, uint32_t a2, uint32_t a3, uint64_t db, int sc) {
  asm volatile("{.reg .pred p; setp.ne.b32 p, %21, 0;\n"
    "wgmma.mma_async.sync.aligned.m64n32k16.f32.f16.f16 {%0, %1, %2, %3, %4, %5, %6, %7, %8, %9, %10, %11, %12, %13, %14, %15}, {%16,%17,%18,%19}, %20, p, 1, 1, 0;}\n"
    : "+f"(d[0]), "+f"(d[1]), "+f"(d[2]), "+f"(d[3]), "+f"(d[4]), "+f"(d[5]), "+f"(d[6]), "+f"(d[7]), "+f"(d[8]), "+f"(d[9]), "+f"(d[10]), "+f"(d[11]), "+f"(d[12]), "+f"(d[13]), "+f"(d[14]), "+f"(d[15])
    : "r"(a0), "r"(a1), "r"(a2), "r"(a3), "l"(db), "r"(sc));
}

__device__ __forceinline__ void wg_rs_f16_n24t(float* d, uint32_t a0, uint32_t a1, uint32_t a2, uint32_t a3, uint64_t db, int sc) {
  asm volatile("{.reg .pred p; setp.ne.b32 p, %17, 0;\n"
    "wgmma.mma_async.sync.aligned.m64n24k16.f32.f16.f16 {%0, %1, %2, %3, %4, %5, %6, %7, %8, %9, %10, %11}, {%12,%13,%14,%15}, %16, p, 1, 1, 1;}\n"
    : "+f"(d[0]), "+f"(d[1]), "+f"(d[2]), "+f"(d[3]), "+f"(d[4]), "+f"(d[5]), "+f"(d[6]), "+f"(d[7]), "+f"(d[8]), "+f"(d[9]), "+f"(d[10]), "+f"(d[11])
    : "r"(a0), "r"(a1), "r"(a2), "r"(a3), "l"(db), "r"(sc));
}

__device__ __forceinline__ void wg_rs_f16_n16t(float* d, uint32_t a0, uint32_t a1, uint32_t a2, uint32_t a3, uint64_t db, int sc) {
  asm volatile("{.reg .pred p; setp.ne.b32 p, %13, 0;\n"
    "wgmma.mma_async.sync.aligned.m64n16k16.f32.f16.f16 {%0, %1, %2, %3, %4, %5, %6, %7}, {%8,%9,%10,%11}, %12, p, 1, 1, 1;}\n"
    : "+f"(d[0]), "+f"(d[1]), "+f"(d[2]), "+f"(d[3]), "+f"(d[4]), "+f"(d[5]), "+f"(d[6]), "+f"(d[7])
    : "r"(a0), "r"(a1), "r"(a2), "r"(a3), "l"(db), "r"(sc));
}

struct cf { float x, y; };
__device__ __forceinline__ cf cmul(cf a, cf b) { cf r; r.x = fmaf(a.x, b.x, -a.y * b.y); r.y = fmaf(a.x, b.y, a.y * b.x); return r; }
__device__ __forceinline__ cf zpow(float rho2, float phi, float e) {
  const float m = ex2f(rho2 * e), ang = phi * e;
  cf r; r.x = m * __cosf(ang); r.y = m * __sinf(ang); return r;
}
__device__ __forceinline__ __half2 H2(uint32_t v) { return *reinterpret_cast<__half2*>(&v); }
__device__ __forceinline__ uint32_t U32(__half2 v) { return *reinterpret_cast<uint32_t*>(&v); }
__device__ __forceinline__ uint32_t hprod(uint32_t v, uint32_t r, uint32_t rr) {
  return U32(__hfma2(__high2half2(H2(v)), H2(rr), __hmul2(__low2half2(H2(v)), H2(r))));
}
template <bool CONJ>
__device__ __forceinline__ void hprod2(uint32_t re, uint32_t im, uint32_t r, uint32_t& ore, uint32_t& oim) {
  const __half2 rx = __low2half2(H2(r)), ry = __high2half2(H2(r));
  if (CONJ) {
    ore = U32(__hfma2(H2(re), rx, __hmul2(H2(im), ry)));
    oim = U32(__hfma2(H2(im), rx, __hneg2(__hmul2(H2(re), ry))));
  } else {
    ore = U32(__hfma2(H2(re), rx, __hneg2(__hmul2(H2(im), ry))));
    oim = U32(__hfma2(H2(re), ry, __hmul2(H2(im), rx)));
  }
}
__device__ __forceinline__ cf csq(cf a) { cf r; r.x = fmaf(a.x, a.x, -a.y * a.y); r.y = (a.x + a.x) * a.y; return r; }
__device__ __forceinline__ cf cmulc(cf a, cf b) { cf r; r.x = fmaf(a.x, b.x, a.y * b.y); r.y = fmaf(a.y, b.x, -a.x * b.y); return r; }
__device__ __forceinline__ uint32_t pk(cf a) { return pack_h2(a.x, a.y); }
__device__ __forceinline__ uint32_t ldg32(const void* p, int o) { uint32_t v; asm volatile("ld.global.nc.b32 %0, [%1];" : "=r"(v) : "l"((const char*)p + o)); return v; }
__device__ __forceinline__ uint32_t rot90(uint32_t v) { return __byte_perm(v, 0, 0x1032) ^ 0x00008000u; }
__device__ __forceinline__ uint32_t hadd2u(uint32_t a, uint32_t b) { return U32(__hadd2(H2(a), H2(b))); }

struct KgIn { uint32_t cur[6], nxt[6], ldt, dk; bool odd; };
__device__ __forceinline__ float pow2_floor(float v) { return __uint_as_float(__float_as_uint(fminf(fmaxf(v, 1e-30f), 1e30f)) & 0x7f800000u); }
__device__ __forceinline__ void kgen_mma(float* acc, const uint32_t (*A)[4], const uint32_t (*B)[6], int csrc) {
#pragma unroll
  for (int ks = 0; ks < 4; ks++) {
    const uint32_t rl = __shfl_sync(0xffffffffu, B[ks][4], csrc), rh = __shfl_sync(0xffffffffu, B[ks][5], csrc);
    const uint32_t rlr = rot90(rl), rhr = rot90(rh);
    mma_f16(acc + 0, A[ks][0], A[ks][1], A[ks][2], A[ks][3], B[ks][0], B[ks][1]);
    mma_f16(acc + 4, A[ks][0], A[ks][1], A[ks][2], A[ks][3], B[ks][2], B[ks][3]);
    mma_f16(acc + 8, A[ks][0], A[ks][1], A[ks][2], A[ks][3], B[ks][4], B[ks][5]);
    const uint32_t c0 = hprod(A[ks][0], rl, rlr), c1 = hprod(A[ks][1], rl, rlr);
    const uint32_t c2 = hprod(A[ks][2], rh, rhr), c3 = hprod(A[ks][3], rh, rhr);
    mma_f16(acc + 12, c0, c1, c2, c3, B[ks][0], B[ks][1]);
    mma_f16(acc + 16, c0, c1, c2, c3, B[ks][2], B[ks][3]);
    mma_f16(acc + 20, c0, c1, c2, c3, B[ks][4], B[ks][5]);
  }
}
template <class Mid>
__device__ __forceinline__ void kgen_warp(KgIn& k, int nw, uint32_t stg, uint32_t tbl, int lane, Mid mid) {
  float dl, dt, sc, inv_sc;
  {
    const uint32_t M = 0x7fff7fffu;
    uint32_t mx[2];
#pragma unroll
    for (int i = 0; i < 2; i++) {
      const uint32_t m = __vmaxu2(__vmaxu2(k.cur[2 + 2 * i] & M, k.cur[3 + 2 * i] & M), __vmaxu2(k.nxt[2 + 2 * i] & M, k.nxt[3 + 2 * i] & M));
      mx[i] = __reduce_max_sync(0xffffffffu, max(m << 16, m & 0xffff0000u));
    }
    dt = rbf(ex2f((k.odd ? bf_hi(k.ldt) : bf_lo(k.ldt)) * 1.4426950408889634f));
    sc = pow2_floor(0.125f * __uint_as_float(mx[0]) * __uint_as_float(mx[1]));
    inv_sc = rcpf_(sc);
    if (lane == 0) sts64f(tbl + TBL_SC + 8, dt, (k.odd ? bf_hi(k.dk) : bf_lo(k.dk)) * rcpf_(dt));
    dl = dt * 1.4426950408889634f;
  }
  const uint32_t st0 = stg + lane * KREC + (((lane >> 2) & 1) << 4), st1 = st0 ^ 16;
  const int mat = lane >> 3, rowi = lane & 7;
  const uint32_t ldB = stg + (4 * (mat & 1) + (rowi >> 1)) * KREC + ((((mat >> 1) * 2 + (rowi & 1)) << 4) ^ ((mat & 1) << 4));
  const uint32_t ldA = stg + (4 * (mat >> 1) + (rowi >> 1)) * KREC + ((((mat & 1) * 2 + (rowi & 1)) << 4) ^ ((mat >> 1) << 4)) + 96;
  const int csrc = 20 + (lane & 3);
  float acc[24];
  uint32_t B[4][6], A[4][4];
#pragma unroll
  for (int i = 0; i < 24; i++) { acc[i] = 0.f; B[i / 6][i % 6] = 0u; }
#pragma unroll
  for (int i = 0; i < 16; i++) A[i / 4][i % 4] = 0u;
#pragma unroll 1
  for (int it = 0; it < 2 * nw; it++) {
    if (it == 1) mid();
    const uint32_t sel = (it & 1) ? 0x3244u : 0x1044u;
    float v[6];
#pragma unroll
    for (int i = 0; i < 6; i++) { v[i] = __uint_as_float(__byte_perm(k.cur[i], 0, sel)); if (it == 1) k.cur[i] = k.nxt[i]; }
    const float rho2 = v[0] * dl, phi = v[1] * dt;
    const cf bb = {v[2] * inv_sc, v[3] * -inv_sc}, cc = {v[4], v[5]};
    const cf X0 = cmulc(bb, cc);
    const cf z1 = zpow(rho2, phi, 1.f), z64 = zpow(rho2, phi, 64.f);
    kgen_mma(acc, A, B, csrc);
    const cf z2 = csq(z1), z3 = cmul(z2, z1), z4 = csq(z2), z8 = csq(z4), z16 = csq(z8), z24 = cmul(z16, z8), z32 = csq(z16);
    const cf z128 = csq(z64), y1 = csq(z128), y2 = csq(y1), y3 = cmul(y2, y1), y4 = csq(y2);
    const cf X4 = cmulc(X0, z4), W4 = cmulc(X0, y4), W8 = cmulc(W4, y4);
    uint32_t re[4], im[4], r2[4], i2[4];
    re[0] = pack_h2(X0.x, X4.x); im[0] = pack_h2(X0.y, X4.y);
    hprod2<true>(re[0], im[0], pk(z1), re[1], im[1]);
    hprod2<true>(re[0], im[0], pk(z2), re[2], im[2]);
    hprod2<true>(re[0], im[0], pk(z3), re[3], im[3]);
    sts128(st0, re[0], re[1], re[2], re[3]);
    sts128(st1, im[0], im[1], im[2], im[3]);
    const uint32_t hy1 = pk(y1), hy2 = pk(y2);
    hprod2<true>(re[0], im[0], hy1, r2[0], i2[0]);
    hprod2<true>(re[2], im[2], hy1, r2[1], i2[1]);
    hprod2<true>(re[0], im[0], hy2, r2[2], i2[2]);
    hprod2<true>(re[0], im[0], pk(y3), r2[3], i2[3]);
    sts128(st0 + 32, r2[0], r2[1], r2[2], r2[3]);
    sts128(st1 + 32, i2[0], i2[1], i2[2], i2[3]);
    const cf W5 = cmulc(W4, y1);
    re[0] = pack_h2(W4.x, W5.x); im[0] = pack_h2(W4.y, W5.y);
    hprod2<true>(re[0], im[0], hy2, re[1], im[1]);
    sts128(st0 + 64, re[0], re[1], pack_h2(W8.x, z128.x), hy1);
    sts128(st1 + 64, im[0], im[1], pack_h2(W8.y, z128.y), hy1);
    re[0] = pack_h2(1.f, z32.x); im[0] = pack_h2(0.f, z32.y);
    hprod2<false>(re[0], im[0], pk(z8), re[1], im[1]);
    hprod2<false>(re[0], im[0], pk(z16), re[2], im[2]);
    hprod2<false>(re[0], im[0], pk(z24), re[3], im[3]);
    const uint32_t h64 = pk(z64);
#pragma unroll
    for (int j = 0; j < 4; j++) hprod2<false>(re[j], im[j], h64, r2[j], i2[j]);
    sts128(st0 + 96, re[0], re[1], re[2], re[3]);
    sts128(st1 + 96, im[0], im[1], im[2], im[3]);
    sts128(st0 + 128, r2[0], r2[1], r2[2], r2[3]);
    sts128(st1 + 128, i2[0], i2[1], i2[2], i2[3]);
    __syncwarp();
#pragma unroll
    for (int ks = 0; ks < 4; ks++) {
      ldsm2t(ldB + ks * 8 * KREC + 64, B[ks][4], B[ks][5]);
      ldsm4t(ldA + ks * 8 * KREC, A[ks][0], A[ks][1], A[ks][2], A[ks][3]);
      ldsm4t(ldB + ks * 8 * KREC, B[ks][0], B[ks][1], B[ks][2], B[ks][3]);
    }
  }
  kgen_mma(acc, A, B, csrc);
#pragma unroll
  for (int q = 0; q < 4; q++)
#pragma unroll
    for (int nt = 0; nt < 3; nt++) {
      const float* a = acc + 12 * (q >> 1) + 4 * nt + 2 * (q & 1);
      sts64f(stg + (q * 3 + nt) * 256 + lane * 8, a[0] * sc, a[1] * sc);
    }
  if (lane == 0) sts32f(stg + 3072, sc);
}

__device__ __forceinline__ void tput(uint32_t tbl, int X, uint32_t h) {
  sts16(tbl + 2 * (1296 - X), (uint16_t)h);
  sts16(tbl + TBL_C1 + 2 * (1297 - X), (uint16_t)h);
}
__device__ __forceinline__ void ktab_build(uint32_t src, bool four, int q, uint32_t tbl, int lane) {
  const int tq = lane & 3, r = 8 * q + (lane >> 3) + ((lane >> 2) & 1) * 4;
  float v[6];
  const float2 dd = lds64f(tbl + TBL_SC + 8);
  float sc = fmaxf(fmaxf(lds32f(src + 3072), lds32f(src + 3072 + KSTG)), pow2_floor(fabsf(dd.y) * (1.f / 4096.f)));
  if (four) sc = fmaxf(sc, fmaxf(lds32f(src + 3072 + 2 * KSTG), lds32f(src + 3072 + 3 * KSTG)));
  const float inv = rcpf_(sc);
  src += q * 768 + lane * 8;
#pragma unroll
  for (int nt = 0; nt < 3; nt++) {
    const float2 a = lds64f(src + nt * 256), c = lds64f(src + nt * 256 + KSTG);
    v[2 * nt] = a.x + c.x; v[2 * nt + 1] = a.y + c.y;
  }
  if (four) {
#pragma unroll
    for (int nt = 0; nt < 3; nt++) {
      const float2 a = lds64f(src + nt * 256 + 2 * KSTG), c = lds64f(src + nt * 256 + 3 * KSTG);
      v[2 * nt] += a.x + c.x; v[2 * nt + 1] += a.y + c.y;
    }
  }
  const bool first = (r == 0);
  if (first && tq == 0) { v[0] += dd.y; sts64f(tbl + TBL_SC, v[4] * inv, dd.x * sc); }
  const uint32_t h0 = pack_h2(v[0] * inv, v[1] * inv), h1 = pack_h2(v[2] * inv, v[3] * inv), h2 = pack_h2(v[4] * inv, v[5] * inv);
  tput(tbl, 64 + 8 * r + tq, h0);
  tput(tbl, 68 + 8 * r + tq, h0 >> 16);
  const bool lo = tq < 2;
  const int k2 = 32 * (tq - 2) + r;
  const bool sp = first && tq == 2;
  const int Xa = lo ? 320 + 8 * r + 2 * tq : (sp ? 576 : 911 + k2), Xb = lo ? Xa + 4 : 720 + k2;
  tput(tbl, Xa, h1);
  tput(tbl, Xb, h1 >> 16);
  if (tq == 0 || sp) {
    tput(tbl, Xa + 1, h1);
    if (Xa != 320) tput(tbl, Xa - 1, h1);
    const uint32_t hb = sp ? h1 : h1 >> 16, hc = sp ? h2 : h1 >> 16;
    tput(tbl, sp ? 578 : Xb + 1, hb);
    tput(tbl, sp ? 1295 : Xb - 1, hc);
  }
  if (lo) {
    const int X3 = ((r & 1) ? 1104 : 1231) + 32 * tq + (r >> 1);
    tput(tbl, X3 == 1231 ? 975 : X3, h2);
    tput(tbl, X3 + 16, h2 >> 16);
  }
}

__device__ __forceinline__ void sig_windows(uint32_t sig, int t) {
  uint32_t U[20];
#pragma unroll
  for (int c = 0; c < 5; c++) {
    const int kap = 2 * t - 3 + c + 72;
    const uint4 v = lds128(sig + SIG_U + (kap & 7) * U_LBO + (kap >> 3) * 16);
    U[4 * c] = v.x; U[4 * c + 1] = v.y; U[4 * c + 2] = v.z; U[4 * c + 3] = v.w;
  }
  uint32_t O[19], A2[17], A4[17], V2[8], V5[8];
#pragma unroll
  for (int i = 3; i < 19; i++) O[i] = __byte_perm(U[i - 1], U[i], 0x5432);
#pragma unroll
  for (int i = 3; i < 17; i++) A2[i] = hadd2u(U[i], O[i]);
#pragma unroll
  for (int i = 4; i < 17; i++) A4[i] = hadd2u(A2[i], A2[i - 1]);
#pragma unroll
  for (int k = 0; k < 8; k++) { V2[k] = hadd2u(O[11 + k], U[10 + k]); V5[k] = hadd2u(A4[9 + k], U[7 + k]); }
#pragma unroll
  for (int h = 0; h < 2; h++) {
    sts128(sig + SIG_V3 + t * 32 + h * 16, hadd2u(V2[4 * h], O[10 + 4 * h]), hadd2u(V2[4 * h + 1], O[11 + 4 * h]),
           hadd2u(V2[4 * h + 2], O[12 + 4 * h]), hadd2u(V2[4 * h + 3], O[13 + 4 * h]));
    sts128(sig + SIG_V5 + t * 32 + h * 16, V5[4 * h], V5[4 * h + 1], V5[4 * h + 2], V5[4 * h + 3]);
  }
  if (t < 64) {
    uint32_t V7[8], V9[8];
#pragma unroll
    for (int k = 0; k < 8; k++) {
      V7[k] = hadd2u(V5[k], hadd2u(O[10 + k], O[7 + k]));
      V9[k] = hadd2u(hadd2u(A4[6 + k], A4[4 + k]), U[2 + k]);
    }
#pragma unroll
    for (int h = 0; h < 2; h++) {
      sts128(sig + SIG_V7 + h * 1024 + t * 16, V7[4 * h], V7[4 * h + 1], V7[4 * h + 2], V7[4 * h + 3]);
      sts128(sig + SIG_V9 + h * 1024 + t * 16, V9[4 * h], V9[4 * h + 1], V9[4 * h + 2], V9[4 * h + 3]);
      sts128(sig + SIG_V2 + h * 1024 + t * 16, V2[4 * h], V2[4 * h + 1], V2[4 * h + 2], V2[4 * h + 3]);
    }
  }
}

__device__ __forceinline__ void conv_channel(uint32_t tbl, uint32_t sig, uint32_t y2b, uint32_t y3b, float k1024,
                                             int w, int lane, int barid, float* res) {
  const int g = lane >> 2, tq = lane & 3;
  const uint32_t tb = tbl + ((g & 1) ? TBL_C1 + 2 : 0) + 2 * (1296 - (g - 2 * tq)) - 32 * w + 112;
  float a2[12], a3[8];
#pragma unroll
  for (int i = 0; i < 16; i++) res[i] = 0.f;
#pragma unroll
  for (int i = 0; i < 12; i++) a2[i] = 0.f;
#pragma unroll
  for (int q = 0; q < 4; q++) {
    const float2 f = h2f(lds32(sig + SIG_V2 + (q >> 1) * 1024 + (16 * w + 8 * (q & 1) + g) * 16 + tq * 4));
    a3[2 * q] = k1024 * f.x;
    a3[2 * q + 1] = k1024 * f.y;
  }
  const uint32_t sigu = __shfl_sync(0xffffffffu, opaque(sig), 0);
  const uint64_t dU = mkdesc(sigu + SIG_U, U_LBO, 128, 0);
  const uint64_t dV = mkdesc(sigu, 128, 1024, 0);
  fence_regs<16>(res); fence_regs<12>(a2); fence_regs<8>(a3);
  constexpr int LB = 2 * U_LBO / 16;
  uint32_t Rd[75], R2[2][17], R3[2][9];
  auto load_group = [&](int gi) {
    const int it = gi >> 1, hb = gi & 1;
    if (gi == 0) Rd[0] = lds32(tb - 128);
#pragma unroll
    for (int i = 1; i < (gi == 17 ? 7 : 5); i++) Rd[4 * gi + i] = lds32(tb - 128 - 16 * (4 * gi + i));
    if (gi < 16) {
      const int sg = it >> 2, n2 = gi & 7;
      if (n2 == 0) R2[sg][0] = lds32(tb - 1440 - 384 * sg);
      R2[sg][2 * n2 + 1] = lds32(tb - 1440 - 384 * sg - 16 * (2 * n2 + 1));
      R2[sg][2 * n2 + 2] = lds32(tb - 1440 - 384 * sg - 16 * (2 * n2 + 2));
      if (!hb) {
        const int n3 = it & 3;
        if (n3 == 0) R3[sg][0] = lds32(tb - 2208 - 256 * sg);
        R3[sg][2 * n3 + 1] = lds32(tb - 2208 - 256 * sg - 16 * (2 * n3 + 1));
        R3[sg][2 * n3 + 2] = lds32(tb - 2208 - 256 * sg - 16 * (2 * n3 + 2));
      }
    }
  };
  auto dense = [&](int n) {
    wg_rs_f16_n32k(res, Rd[2 * n + 1], Rd[2 * n + 2], Rd[2 * n], Rd[2 * n + 1], dU + ((3 - (n & 3)) * LB + 9 - (n >> 2)), 1);
  };
  load_group(0);
  load_group(1);
#pragma unroll
  for (int gi = 0; gi < 18; gi++) {
    const int it = gi >> 1, sg = it >> 2, n2 = gi & 7, n3 = it & 3;
    wg_fence();
    dense(2 * gi);
    if (gi < 16)
      wg_rs_f16_n24t(a2, R2[sg][2 * n2 + 1], R2[sg][2 * n2 + 2], R2[sg][2 * n2], R2[sg][2 * n2 + 1],
                     dV + ((SIG_V3 + 768) / 16 + 256 * sg - 16 * (n2 & 3) - 64 * (n2 >> 2)), 1);
    dense(2 * gi + 1);
    if (gi < 16 && !(gi & 1))
      wg_rs_f16_n16t(a3, R3[sg][2 * n3 + 1], R3[sg][2 * n3 + 2], R3[sg][2 * n3], R3[sg][2 * n3 + 1],
                     dV + ((SIG_V7 + 768) / 16 + 128 * sg - 16 * n3), 1);
    if (gi == 17) dense(36);
    wg_commit();
    if (gi < 16) { wg_wait<1>(); load_group(gi + 2); }
  }
  wg_wait<2>();
  fence_regs<12>(a2); fence_regs<8>(a3);
  bar_sync(barid, 128);
  {
    const uint32_t o2 = y2b + (136 * w + 8 * g + 2 * tq) * 4, o3 = y3b + (272 * w + 16 * g + 2 * tq) * 4;
#pragma unroll
    for (int q = 0; q < 6; q++) sts64f(o2 + (544 * (q >> 1) + 64 * (q & 1)) * 4, a2[2 * q], a2[2 * q + 1]);
#pragma unroll
    for (int q = 0; q < 4; q++) sts64f(o3 + (8 * (q >> 1) + 136 * (q & 1)) * 4, a3[2 * q], a3[2 * q + 1]);
  }
  bar_sync(barid, 128);
  const uint32_t go = (136 * tq + 16 * w + g) * 4;
  float ex[12];
#pragma unroll
  for (int i = 0; i < 12; i++) {
    const int o = 544 * (i >> 2) + 64 * (i & 1) + 8 * ((i >> 1) & 1);
    ex[i] = lds32f(y2b + go + o * 4);
    if (i >= 4) ex[i] += lds32f(y3b + go + (o - 544) * 4);
  }
  wg_wait<0>();
  fence_regs<16>(res);
#pragma unroll
  for (int i = 0; i < 12; i++) res[4 + i] += ex[i];
}

__device__ __forceinline__ void red16x2(float& a, float& c) {
#pragma unroll
  for (int o = 1; o < 16; o <<= 1) { a += __shfl_xor_sync(0xffffffffu, a, o); c += __shfl_xor_sync(0xffffffffu, c, o); }
}
__device__ __forceinline__ void ln_rows(uint32_t* u, uint32_t term, uint32_t stg_row, int lane) {
  const int j = lane & 15;
  const float piv = __shfl_sync(0xffffffffu, bf_lo(u[0]), lane & 16);
  float s0 = 0.f, s1 = 0.f, q0 = 0.f, q1 = 0.f;
#pragma unroll
  for (int i = 0; i < 14; i++) {
    const float a = bf_lo(u[i]) - piv, c = bf_hi(u[i]) - piv;
    s0 += a; s1 += c; q0 = fmaf(a, a, q0); q1 = fmaf(c, c, q1);
  }
  float s = s0 + s1, q = q0 + q1;
  red16x2(s, q);
  s *= (1.f / D_); q *= (1.f / D_);
  const __nv_bfloat16 m1b = __float2bfloat16_rn(s + piv);
  const __nv_bfloat162 m1v = __halves2bfloat162(m1b, m1b);
  const float den = rbf(sqrtf_(rbf(rbf(fmaxf(fmaf(-s, s, q), 0.f)) + 1e-5f)));
  const float rden = rcpf_(den);
  s0 = s1 = q0 = q1 = 0.f;
#pragma unroll
  for (int i = 0; i < 14; i++) {
    const __nv_bfloat162 cv = __hsub2(*reinterpret_cast<__nv_bfloat162*>(&u[i]), m1v);
    const uint32_t c = *reinterpret_cast<const uint32_t*>(&cv);
    const uint32_t n = pack_bf2(bf_lo(c) * rden, bf_hi(c) * rden);
    const float a = bf_lo(n), e = bf_hi(n);
    s0 += a; s1 += e; q0 = fmaf(a, a, q0); q1 = fmaf(e, e, q1);
    u[i] = pack_h2(a, e);
  }
#pragma unroll
  for (int i = 0; i < 7; i++)
    asm volatile("st.shared.v2.b32 [%0], {%1,%2};" ::"r"(stg_row + (j + 16 * i) * 8), "r"(u[2 * i]), "r"(u[2 * i + 1]) : "memory");
  s = s0 + s1; q = q0 + q1;
  red16x2(s, q);
  s *= (1.f / D_); q *= (1.f / D_);
  const float den2 = rbf(sqrtf_(rbf(rbf(fmaxf(fmaf(-s, s, q), 0.f)) + 1e-5f)));
  if (j == 0) {
    const float ir = den * den2, mu = fmaf(rbf(s), den, __bfloat162float(m1b));
    const float ih = rbf(ir), mh = rbf(mu);
    const uint32_t mm = pack_bf2(mh, mh);
    sts128(term, pack_bf2(mu - mh, ih), mm, pack_bf2(mu - mh, ir - ih), mm);
  }
}

__device__ __forceinline__ void poll_tag(const unsigned* p, uint32_t tag) {
#pragma unroll 1
  for (int it = 0; it < 4096; it++) {
    if (!((ld_relaxed1(p) ^ tag) & 1)) break;
    __nanosleep(32);
  }
}
template <int NV, int STRIDE>
__device__ __forceinline__ void recv_part(const uint4* src, uint32_t tag, float* pre) {
  uint4 v[NV];
#pragma unroll 1
  for (int it = 0; it < RETRY_MAX; it++) {
    uint32_t bad = 0;
#pragma unroll
    for (int q = 0; q < NV; q++) v[q] = ld_b128(src + q * STRIDE);
#pragma unroll
    for (int q = 0; q < NV; q++) bad |= v[q].x ^ tag;
    const unsigned m = __ballot_sync(0xffffffffu, bad & 1);
    if (!m) break;
    if ((threadIdx.x & 31) == __ffs(m) - 1) poll_tag((const unsigned*)(src + (NV - 1) * STRIDE), tag);
    __syncwarp();
  }
#pragma unroll
  for (int q = 0; q < NV; q++) {
    const uint32_t u[4] = {v[q].x, v[q].y, v[q].z, v[q].w};
#pragma unroll
    for (int k = 0; k < 4; k++) { pre[8 * q + 2 * k] += bf_lo(u[k]); pre[8 * q + 2 * k + 1] += bf_hi(u[k]); }
  }
}
__device__ __forceinline__ void send_part(uint4* dst, uint32_t tag, const float* a) {
#pragma unroll
  for (int q = 0; q < 4; q++)
    st_b128(dst + q * 256, tag, pack_bf2(a[8 * q], a[8 * q + 1]), pack_bf2(a[8 * q + 2], a[8 * q + 3]),
            pack_bf2(a[8 * q + 4], a[8 * q + 5]), pack_bf2(a[8 * q + 6], a[8 * q + 7]));
}
__device__ __forceinline__ bool last_release(uint32_t cnt) {
  unsigned old;
  asm volatile("atom.relaxed.cta.shared.inc.u32 %0, [%1], 7;" : "=r"(old) : "r"(cnt) : "memory");
  return old == 7;
}
__device__ __forceinline__ int mod7(int v) { return v >= 7 ? v - 7 : v; }

#define IDS const int tid = opaque(tid0), lane = tid & 31, t = tid & 127, wg = tid >> 7, w = (tid >> 5) & 3; \
            (void)lane; (void)t; (void)wg; (void)w;

__global__ void __launch_bounds__(384, 1)
fused_kernel(const Params p, const __grid_constant__ CUtensorMap tm_x, const __grid_constant__ CUtensorMap tm_w1,
             const __grid_constant__ CUtensorMap tm_w2, const __grid_constant__ CUtensorMap tm_out) {
  const uint32_t sb = smem_u32(smem_raw);
  const uint32_t ms = sb + OFF_M;
  const uint32_t bar0 = ms + M_BAR;
  const int tid0 = threadIdx.x;
  const int b = blockIdx.x;
  const bool is_ssm = b >= NMLP;
  const int G = b / NRK, rk = b - G * NRK;
  const int kc0 = (G + rk) % 7;
  TSINIT();
  TSTAMP(0);
  {
    IDS
    TSTAMP(28);
    uint4 ld[7];
    KgIn kin;
    unsigned ep = 0;
    uint32_t b1w;
    const int rl = 2 * (tid >> 5) + (lane >> 4);
    {
      const int d = is_ssm ? 2 * (112 + 3 * (b - NMLP) + wg) + (w >> 1) : (wg < 2 ? 2 * b + wg : 336 + b);
      const int off = d * NST + 64 * (is_ssm ? 2 * (w & 1) : w) + 2 * lane;
      const __nv_bfloat16* P[10] = {p.a_re + off, p.a_im + off, p.b_re + off, p.b_im + off, p.c_re + off, p.c_im + off,
                                    p.log_dt + (d & ~1), p.dskip + (d & ~1), p.b1 + 64 * (is_ssm ? 0 : b >> 2) + (t & 62),
                                    wg < 2 ? p.x + (size_t)(16 * (b & 127) + rl) * D_ + 4 * (lane & 15)
                                           : p.w1 + (size_t)(112 * (b & 3) + (t >> 3)) * F_ + 64 * (is_ssm ? 0 : b >> 2) + 8 * (t & 7)};
      const unsigned* pe = &p.s->epoch;
      asm volatile("" : "+l"(P[0]), "+l"(P[1]), "+l"(P[2]), "+l"(P[3]), "+l"(P[4]), "+l"(P[5]), "+l"(P[6]), "+l"(P[7]), "+l"(P[8]), "+l"(P[9]), "+l"(pe));
#pragma unroll
      for (int i = 0; i < 6; i++) kin.cur[i] = ldg32(P[i], 0);
      kin.ldt = ldg32(P[6], 0); kin.dk = ldg32(P[7], 0); b1w = ldg32(P[8], 0);
      if (tid == 256 + 32) ep = ld_relaxed1(pe);
#pragma unroll
      for (int i = 0; i < 6; i++) kin.nxt[i] = 0u;
      if (is_ssm) {
#pragma unroll
        for (int i = 0; i < 6; i++) kin.nxt[i] = ldg32(P[i], 128);
      }
      if (wg < 2) {
#pragma unroll
        for (int i = 0; i < 7; i++) asm volatile("ld.global.nc.v2.b32 {%0,%1}, [%2];" : "=r"(ld[i].x), "=r"(ld[i].y) : "l"(P[9] + 64 * i));
      } else {
#pragma unroll
        for (int i = 0; i < 7; i++)
          asm volatile("ld.global.nc.v4.b32 {%0,%1,%2,%3}, [%4];" : "=r"(ld[i].x), "=r"(ld[i].y), "=r"(ld[i].z), "=r"(ld[i].w) : "l"(P[9] + (size_t)i * 16 * F_));
      }
      asm volatile("" :: "l"(P[0]), "l"(P[1]), "l"(P[2]), "l"(P[3]), "l"(P[4]), "l"(P[5]), "l"(P[6]), "l"(P[7]), "l"(P[8]), "l"(P[9]), "l"(pe));
      kin.odd = d & 1;
    }
    const uint32_t tbl = is_ssm ? sb + (4 * wg + (w >> 1)) * TBL : sb + OFF_T + wg * TBL;
#pragma unroll 1
    for (int i = is_ssm ? t & 63 : t; i < TBL_SC / 16; i += is_ssm ? 64 : 128) sts128(tbl + i * 16, 0u, 0u, 0u, 0u);
    const uint32_t lns = is_ssm ? sb + S_WORK + 2 * S_WGB + 4 * KSTG : sb + OFF_X + 2 * 16384;
    const int wi = __shfl_sync(0xffffffffu, tid >> 5, 0);
    if (wi < 4 && lane == 0) {
      if (wi < 3) mbar_init(bar0 + 8 * wi, 1);
      asm volatile("fence.mbarrier_init.release.cluster;" ::: "memory");
      if (!is_ssm) asm volatile("prefetch.tensormap [%0];" ::"l"(wi == 0 ? &tm_x : wi == 1 ? &tm_w1 : wi == 2 ? &tm_w2 : &tm_out) : "memory");
    }
    __syncwarp();
    if (wi == 4 && lane < 16) asm volatile("st.shared.b32 [%0], 0;" ::"r"(ms + M_REL + 4 * lane) : "memory");
    TSTAMP(31);
    auto mid = [&]() {
    TSTAMP(30);
    if (wg < 2) {
      uint32_t u[14];
#pragma unroll
      for (int i = 0; i < 7; i++) { u[2 * i] = ld[i].x; u[2 * i + 1] = ld[i].y; }
      ln_rows(u, ms + M_LT + rl * 16, lns + ((rl & 1) | ((rl >> 2) << 1) | ((rl & 2) << 2)) * 912, lane);
      bar_arrive(7, 384);
    } else {
      float cs[8];
#pragma unroll
      for (int k = 0; k < 8; k++) cs[k] = 0.f;
#pragma unroll
      for (int i = 0; i < 7; i++) {
        const uint32_t uu[4] = {ld[i].x, ld[i].y, ld[i].z, ld[i].w};
#pragma unroll
        for (int k = 0; k < 4; k++) { cs[2 * k] += bf_lo(uu[k]); cs[2 * k + 1] += bf_hi(uu[k]); }
      }
#pragma unroll
      for (int st = 0; st < 2; st++) {
        const int n = 4 >> st;
        const bool up = (lane >> (4 - st)) & 1;
#pragma unroll
        for (int k = 0; k < n; k++) {
          const float give = up ? cs[k] : cs[k + n], keep = up ? cs[k + n] : cs[k];
          cs[k] = keep + __shfl_xor_sync(0xffffffffu, give, 16 >> st);
        }
      }
      sts64f(ms + M_CSR + (w * 64 + (lane & 7) * 8 + (lane >> 3) * 2) * 4, cs[0], cs[1]);
      if (t == 32) { asm volatile("st.shared.b32 [%0], %1;" ::"r"(ms + M_EP), "r"(ep + 1) : "memory"); red_relaxed(&p.s->cntA); }
      bar_sync(7, 384);
      const uint32_t la = lns + (lane & 15) * 912 + (lane >> 4) * 16 + w * 224;
      uint2* dst = (uint2*)(p.s->xnT + (size_t)(56 * w + (lane >> 3)) * 512 + 4 * b) + (lane & 7);
      uint32_t r[28];
#pragma unroll
      for (int k = 0; k < 7; k++) ldsm4t(la + k * 32, r[4 * k], r[4 * k + 1], r[4 * k + 2], r[4 * k + 3]);
      const uint32_t tag = lds32(ms + M_EP) & 1;
      fence_async();
      bar_sync(6, 128);
      if (b < 128) {
#pragma unroll
        for (int k = 0; k < 14; k++) st_relaxed2(dst + k * 4096, (r[2 * k] & ~1u) | tag, (r[2 * k + 1] & ~1u) | tag);
      }
      if (t < 64 && !is_ssm) {
        const uint32_t a = ms + M_CSR + t * 4;
        const float c = -((lds32f(a) + lds32f(a + 256)) + (lds32f(a + 512) + lds32f(a + 768)));
        const float ch = rbf(c);
        uint2* dx = (uint2*)(p.s->bx + (b >> 4) * 512 + ((b >> 1) & 1) * 256 + ((b >> 2) & 3) * 64 + t) + (b & 1);
        const float b1v = (b & 2) ? 0.f : ((t & 1) ? bf_hi(b1w) : bf_lo(b1w));
        asm volatile("{.reg .b64 a; mov.b64 a, {%1,%2}; st.relaxed.gpu.global.b64 [%0], a;}"
                     ::"l"(dx), "r"(pack_bf2(ch, b1v)), "r"((pack_bf2(c - ch, ch) & ~1u) | tag) : "memory");
      }
      if (t >= 64 && t < 80 && b < 128) {
        const uint4 a = lds128(ms + M_LT + (t - 64) * 16);
        st_b128(p.s->ax + 16 * b + t - 64, tag, a.x, a.y, a.z, a.w);
      }
    }
    if ((wi == 0 || wi == 1 || wi == 10) && lane == 0 && !is_ssm) {
      const int i = wi & 3, kc = mod7(kc0 + i);
      mbar_expect(bar0 + 8 * i, 49152);
      tma_2d(sb + OFF_X + i * 16384, &tm_x, 64 * kc, 128 * G, bar0 + 8 * i);
      tma_3d(sb + OFF_W + i * 32768, &tm_w1, 0, 64 * kc, 4 * rk, bar0 + 8 * i);
    }
    __syncwarp();
    TSTAMP(29);
    };
    const uint32_t stg = is_ssm ? sb + S_WORK + wg * S_WGB + w * KSTG : sb + (wg < 2 ? OFF_A + 4 * wg * KSTG : OFF_B) + w * KSTG;
    kgen_warp(kin, is_ssm ? 2 : 1, stg, tbl, lane, mid);
  }
  TSTAMP(1);
  uint4 v[4], tv[5];
  {
    IDS
    bar_sync(4 + wg, 128);
    if (!is_ssm && wg == 2) {
#pragma unroll
      for (int q = 0; q < 4; q++) tv[q] = ld_2x64(p.s->bx + 512 * rk + q * 128 + t);
      tv[4] = ld_b128(p.s->ax + 128 * G + t);
    }
    if (is_ssm || wg == 2) {
      const uint4* src = p.s->xnT + (size_t)(is_ssm ? 112 + 3 * (b - NMLP) + wg : b) * 512 + t;
#pragma unroll
      for (int q = 0; q < 4; q++) v[q] = ld_relaxed4(src + q * 128);
    }
#pragma unroll 1
    for (int c = is_ssm ? 1 : 0; c >= 0; c--) {
      const uint32_t src = is_ssm ? sb + S_WORK + wg * S_WGB + 2 * c * KSTG : sb + (wg < 2 ? OFF_A + 4 * wg * KSTG : OFF_B);
      ktab_build(src, !is_ssm, w, is_ssm ? sb + (4 * wg + c) * TBL : sb + OFF_T + wg * TBL, lane);
    }
    fence_async();
  }
  TSTAMP(2);
  __syncthreads();

  if (is_ssm || __shfl_sync(0xffffffffu, tid0 >> 7, 0) == 2) {
    asm volatile("setmaxnreg.dec.sync.aligned.u32 136;");
    if (!is_ssm) {
      IDS
      const unsigned ep1 = lds32(ms + M_EP);
#pragma unroll 1
      for (int it = 0; it < 16 * RETRY_MAX; it++) {
        uint32_t bad = tv[4].x ^ ep1;
#pragma unroll
        for (int q = 0; q < 4; q++) bad |= (tv[q].y ^ ep1) | (tv[q].w ^ ep1);
        if (!__any_sync(0xffffffffu, bad & 1)) break;
        __nanosleep(200);
#pragma unroll
        for (int q = 0; q < 4; q++) tv[q] = ld_2x64(p.s->bx + 512 * rk + q * 128 + t);
        tv[4] = ld_b128(p.s->ax + 128 * G + t);
      }
#pragma unroll
      for (int q = 0; q < 5; q++) sts128(sb + OFF_B + (q < 4 ? B_BX + q * 2048 : B_AX) + t * 16, tv[q].x, tv[q].y, tv[q].z, tv[q].w);
      fence_async();
      bar_arrive(1, 384);
      if (t == 96) { bulk_s2g(p.s->tbl + b * (TBL / 16), sb + OFF_T + 2 * TBL, TBL); bulk_commit(); }
      if (t == 64)
        asm volatile("cp.async.bulk.prefetch.L2.global [%0], %1;" ::"l"(p.w2 + (size_t)(256 * rk + 16 * G) * D_), "r"(16 * D_ * 2) : "memory");
    }
#pragma unroll 1
    for (int pi = opaque(0); ; pi++) {
      {
        IDS
        const unsigned ep1 = lds32(ms + M_EP);
        const int pair = !is_ssm ? b : (pi == 0 ? 112 + 3 * (b - NMLP) : (b < NMLP + 12 ? 172 + 3 * (b - NMLP) : 184 + 2 * (b - NMLP))) + wg;
        const uint32_t work = is_ssm ? sb + S_WORK + wg * S_WGB : sb + OFF_A;
        const uint32_t z = work + SIG_V3 - 1024 + (t >> 6) * 4096 + (t & 63) * 16;
        sts128(z, 0u, 0u, 0u, 0u); sts128(z + SIG, 0u, 0u, 0u, 0u);
        if (t < 72) {
          const uint32_t zu = work + SIG_U + (t & 7) * U_LBO + (t >> 3) * 16;
          sts128(zu, 0u, 0u, 0u, 0u); sts128(zu + SIG, 0u, 0u, 0u, 0u);
        }
        const uint4* src = p.s->xnT + (size_t)pair * 512 + t;
#pragma unroll 1
        for (int it = 0; it < RETRY_MAX; it++) {
          uint32_t bad = 0;
#pragma unroll
          for (int q = 0; q < 4; q++) bad |= (((v[q].x ^ ep1) | (v[q].y ^ ep1) | (v[q].z ^ ep1) | (v[q].w ^ ep1)) & 1) << q;
          const unsigned m = __ballot_sync(0xffffffffu, bad);
          if (!m) break;
          if (lane == __ffs(m) - 1) poll_tag((const unsigned*)(src + (__ffs(bad) - 1) * 128) + 3, ep1);
          __syncwarp();
#pragma unroll
          for (int q = 0; q < 4; q++) v[q] = ld_relaxed4(src + q * 128);
        }
        TSTAMP(5);
        const uint32_t a = work + ((t >> 1) & 1) * SIG + SIG_U + (2 * ((t >> 2) & 3) + (t & 1)) * U_LBO + ((t >> 4) + 9) * 16;
#pragma unroll
        for (int q = 0; q < 4; q++) sts128(a + q * 128, v[q].x & ~1u, v[q].y & ~1u, v[q].z & ~1u, v[q].w & ~1u);
        bar_sync(4 + wg, 128);
#pragma unroll 1
        for (int k = w; k < 6; k += 4) sig_windows(work + (k & 1) * SIG, (k >> 1) * 32 + lane);
        fence_async();
        if (t == 96 && !is_ssm) { bulk_wait0(); red_release(&p.s->cntT); }
        if (pi == 1) mbar_wait(bar0 + 8 * wg, 0);
        TSTAMP(6);
        bar_sync(is_ssm ? 4 + wg : 3, is_ssm ? 128 : 384);
        TSTAMP(7);
      }
      uint32_t keep[8];
      float res[16];
#pragma unroll 1
      for (int c = 0; c < 2; c++) {
        IDS
        const int wgu = __shfl_sync(0xffffffffu, wg, 0);
        const uint32_t work = is_ssm ? sb + S_WORK + wgu * S_WGB : sb + OFF_A;
        const uint32_t tbl = (is_ssm ? sb + (4 * wgu + 2 * pi) * TBL : sb + OFF_T) + c * TBL;
        conv_channel(tbl, work + c * SIG, is_ssm ? work + 2 * SIG + Y3B : sb + OFF_B, work + 2 * SIG, lds32f(tbl + TBL_SC), w, lane, 4 + wgu, res);
        TSTAMP(16 + 2 * pi + c);
        const float os = lds32f(tbl + TBL_SC + 4);
        if (c == 0) {
#pragma unroll
          for (int i = 0; i < 8; i++) keep[i] = pack_bf2(res[2 * i] * os, res[2 * i + 1] * os);
          if (is_ssm && pi == 0 && t == 96 && (b < NMLP + 12 || wg < 2)) {
            wait_count(&p.s->cntT, lds32(ms + M_EP) * NMLP);
            asm volatile("fence.proxy.async;" ::: "memory");
            mbar_expect(bar0 + 8 * wg, 2 * TBL);
            bulk_g2s(sb + (4 * wg + 2) * TBL, p.s->tbl + (2 * ((b < NMLP + 12 ? 172 + 3 * (b - NMLP) : 184 + 2 * (b - NMLP)) + wg) - 336) * (TBL / 16),
                     2 * TBL, bar0 + 8 * wg);
          }
          __syncwarp();
        } else {
          const int pair = !is_ssm ? b : (pi == 0 ? 112 + 3 * (b - NMLP) : (b < NMLP + 12 ? 172 + 3 * (b - NMLP) : 184 + 2 * (b - NMLP))) + wg;
          uint4* dst = p.s->s2 + ((size_t)(lane & 3) * 224 + pair) * 32 + w * 8 + (lane >> 2);
          const uint32_t tag = lds32(ms + M_EP) & 1;
#pragma unroll
          for (int nt = 0; nt < 4; nt++) {
            const uint32_t n0 = pack_bf2(res[4 * nt] * os, res[4 * nt + 1] * os), n1 = pack_bf2(res[4 * nt + 2] * os, res[4 * nt + 3] * os);
            st_b128(dst + nt * 4 * 224 * 32, tag, __byte_perm(keep[2 * nt], n0, 0x5410), __byte_perm(keep[2 * nt + 1], n1, 0x5410),
                    __byte_perm(keep[2 * nt], n0, 0x7632), __byte_perm(keep[2 * nt + 1], n1, 0x7632));
          }
        }
      }
      TSTAMP(8 + pi);
      {
        IDS
        if (pi == 1 || !is_ssm || (b >= NMLP + 12 && wg == 2)) break;
        const uint4* src = p.s->xnT + (size_t)((b < NMLP + 12 ? 172 + 3 * (b - NMLP) : 184 + 2 * (b - NMLP)) + wg) * 512 + t;
#pragma unroll
        for (int q = 0; q < 4; q++) v[q] = ld_relaxed4(src + q * 128);
      }
    }
    if (!is_ssm) {
      IDS
      const uint32_t tag = lds32(ms + M_EP) & 1;
      float pre[64];
#pragma unroll
      for (int i = 0; i < 64; i++) pre[i] = 0.f;
#pragma unroll 1
      for (int s = 0; s < 4; s++) recv_part<8, 128>(p.s->part + ((size_t)b * 6 + s) * 1024 + t, tag, pre);
      bar_sync(6, 128);
#pragma unroll
      for (int i = 0; i < 16; i++)
        sts128(sb + OFF_A + ((2 * (i >> 2) + (i & 1)) * 256 + ((i >> 1) & 1) * 128 + t) * 16, __float_as_uint(pre[4 * i]),
               __float_as_uint(pre[4 * i + 1]), __float_as_uint(pre[4 * i + 2]), __float_as_uint(pre[4 * i + 3]));
      bar_arrive(2, 384);
      if (b == 0 && t == 0) {
        const unsigned ep1 = lds32(ms + M_EP);
        wait_count(&p.s->cntA, ep1 * NCTA);
        *(volatile unsigned*)&p.s->epoch = ep1;
      }
      TSTAMP(12);
    }
    TSDUMP();
  } else {
    bar_arrive(1, 384);
    asm volatile("setmaxnreg.inc.sync.aligned.u32 192;");
    bar_sync(7, 384);
    uint32_t H[64];
    {
      float acc[128];
      float p0, q0, p1, q1;
      {
        IDS
        const int wgu = __shfl_sync(0xffffffffu, wg, 0);
        int sl = 0;
#pragma unroll 1
        for (int s = 0; s < 7; s++) {
          mbar_wait(bar0 + 8 * sl, (s >= 3 && s < 6));
          TSTAMP(17 + s);
          const uint64_t da = mkdesc(sb + OFF_X + sl * 16384 + wgu * 8192, 16, 1024, 1);
          const uint64_t db = mkdesc(sb + OFF_W + sl * 32768, 8192, 1024, 1);
          wg_fence();
#pragma unroll
          for (int k = 0; k < 4; k++) wg_ss_bf16_n256(acc, da + 2 * k, db + 128 * k, (s | k) != 0);
          wg_commit();
          wg_wait<1>();
          const int pl = sl == 0 ? 2 : sl - 1;
          sl = sl == 2 ? 0 : sl + 1;
          if (s > 0 && lane == 0 && last_release(ms + M_REL + 4 * s)) {
            mbar_expect(bar0 + 8 * pl, s == 5 ? 32768 : 49152);
            if (s < 5) tma_3d(sb + OFF_W + pl * 32768, &tm_w1, 0, 64 * mod7(kc0 + s + 2), 4 * rk, bar0 + 8 * pl);
            else tma_2d(sb + OFF_W + pl * 32768, &tm_w2, 64 * mod7(rk + s - 4), 256 * rk, bar0 + 8 * pl);
            if (s != 5) tma_2d(sb + OFF_X + pl * 16384, &tm_x, 64 * (s < 5 ? mod7(kc0 + s + 2) : rk), 128 * G, bar0 + 8 * pl);
          }
        }
        TSTAMP(9);
        bar_sync(1, 384);
        wg_fence();
        wg_ss_bf16_n256k(acc, mkdesc(sb + OFF_B + B_AX + wgu * 1024, 0, 128, 0), mkdesc(sb + OFF_B + B_BX, 4096, 128, 0), 1);
        wg_commit();
        wg_wait<1>();
        if (lane == 0 && last_release(ms + M_REL + 4 * 7)) {
          mbar_expect(bar0, 65536);
#pragma unroll 1
          for (int c = 2; c < 4; c++) tma_2d(sb + (c - 2) * OFF_X, &tm_w2, 64 * mod7(rk + 1 + c), 256 * rk, bar0);
        }
        bar_arrive(3, 384);
        const uint32_t ra = sb + OFF_B + B_AX + (16 * (tid >> 5) + (lane >> 2)) * 16;
        const float r0 = rcpf_(bf_hi(lds32(ra)) + bf_hi(lds32(ra + 8))), r1 = rcpf_(bf_hi(lds32(ra + 128)) + bf_hi(lds32(ra + 136)));
        p0 = 0.7978845608028654f * r0; q0 = 0.0356774081363001f * r0 * r0 * r0;
        p1 = 0.7978845608028654f * r1; q1 = 0.0356774081363001f * r1 * r1 * r1;
      }
      wg_wait<0>();
      fence_regs<128>(acc);
      TSTAMP(16);
      float hq[4];
#pragma unroll
      for (int i = 0; i < 64; i++) {
        const float pp = (i & 1) ? p1 : p0, qq = (i & 1) ? q1 : q0;
        const float a = acc[2 * i], c = acc[2 * i + 1];
        const float ta = tanhf_(a * fmaf(a * a, qq, pp)), tc = tanhf_(c * fmaf(c * c, qq, pp));
        if (i >= 2) H[i - 2] = pack_bf2v(hq[(i & 1) * 2], hq[(i & 1) * 2 + 1]);
        hq[(i & 1) * 2] = fmaf(a, ta, a); hq[(i & 1) * 2 + 1] = fmaf(c, tc, c);
      }
      H[62] = pack_bf2v(hq[0], hq[1]); H[63] = pack_bf2v(hq[2], hq[3]);
    }
    TSTAMP(3);
    float accA[32], accB[32];
    const uint32_t tag = lds32(ms + M_EP) & 1;
    auto issue2 = [&](int c, float* acc) {
      const uint32_t base = sb + ((0x0213021u >> (4 * c)) & 3) * 32768;
      if (c != 3) mbar_wait(bar0 + 8 * ((0x0210021u >> (4 * c)) & 3), (0x34 >> c) & 1);
      const uint64_t db = mkdesc(base, 8192, 1024, 1);
      wg_fence();
#pragma unroll
      for (int k = 0; k < 16; k++) wg_rs_bf16_n64(acc, H[4 * k], H[4 * k + 1], H[4 * k + 2], H[4 * k + 3], db + 128 * k, k != 0);
      wg_commit();
    };
    auto process = [&](int s, float* acc) {
      wg_wait<1>();
      fence_regs<32>(acc);
      const int tid = opaque(tid0);
      if (s < 3 && (tid & 31) == 0 && last_release(ms + M_REL + 4 * (8 + s))) {
        const int sl = (0x021u >> (4 * s)) & 3;
        mbar_expect(bar0 + 8 * sl, 32768);
        tma_2d(sb + sl * 32768, &tm_w2, 64 * mod7(mod7(rk + 5 + s)), 256 * rk, bar0 + 8 * sl);
      }
      send_part(p.s->part + ((size_t)(G * 7 + mod7(rk + 1 + s)) * 6 + s) * 1024 + tid, tag, acc);
      TSTAMP(10 + s);
    };
    issue2(0, accA);
#pragma unroll
    for (int s = 0; s < 6; s += 2) {
      issue2(s + 1, accB);
      process(s, accA);
      issue2(s + 2, accA);
      process(s + 1, accB);
    }
    TSTAMP(4);
    IDS
    const int g = lane >> 2, tq = lane & 3;
    uint32_t sw[16];
    {
      const uint4* sp = p.s->s2 + ((size_t)G * 224 + 32 * rk + tq) * 32 + w * 8 + g;
#pragma unroll 1
      for (int it = 0; it < RETRY_MAX; it++) {
        uint32_t bad = 0;
#pragma unroll
        for (int i = 0; i < 8; i++) {
          const uint4 v = ld_b128(sp + i * 4 * 32);
          bad |= ((v.x ^ tag) & 1) << i;
          sw[2 * i] = wg ? v.z : v.x; sw[2 * i + 1] = wg ? v.w : v.y;
        }
        const unsigned m = __ballot_sync(0xffffffffu, bad);
        if (!m) break;
        if (lane == __ffs(m) - 1) poll_tag((const unsigned*)(sp + (__ffs(bad) - 1) * 4 * 32), tag);
        __syncwarp();
      }
    }
    TSTAMP(5);
    uint32_t b2w[8];
#pragma unroll
    for (int i = 0; i < 8; i++) b2w[i] = __ldg((const uint32_t*)(p.b2 + 64 * rk) + 4 * i + tq);
    wg_wait<0>();
    fence_regs<32>(accA);
    TSTAMP(6);
    bar_sync(2, 384);
#pragma unroll
    for (int i = 0; i < 8; i++) {
      const uint4 v = lds128(sb + OFF_A + (i * 256 + tid) * 16);
      accA[4 * i] += __uint_as_float(v.x); accA[4 * i + 1] += __uint_as_float(v.y);
      accA[4 * i + 2] += __uint_as_float(v.z); accA[4 * i + 3] += __uint_as_float(v.w);
    }
    const uint32_t xa = sb + OFF_X + 2 * 16384 + (16 * (tid >> 5) + (lane & 15)) * 128;
    uint32_t xw[16];
#pragma unroll
    for (int q = 0; q < 4; q++) ldsm4(xa + (((2 * q + (lane >> 4)) ^ (lane & 7)) << 4), xw[4 * q], xw[4 * q + 1], xw[4 * q + 2], xw[4 * q + 3]);
    const uint32_t ra = sb + OFF_B + B_AX + (16 * (tid >> 5) + g) * 16;
    const float r0 = 0.5f * rcpf_(bf_hi(lds32(ra)) + bf_hi(lds32(ra + 8))), r1 = 0.5f * rcpf_(bf_hi(lds32(ra + 128)) + bf_hi(lds32(ra + 136)));
#pragma unroll 1
    for (int s = 4; s < 6; s++) recv_part<4, 256>(p.s->part + ((size_t)b * 6 + s) * 1024 + tid, tag, accA);
    TSTAMP(7);
#pragma unroll
    for (int k = 0; k < 16; k++) {
      const float rr = (k & 1) ? r1 : r0;
      const float o0 = fmaf(accA[2 * k], rr, bf_lo(b2w[k >> 1])), o1 = fmaf(accA[2 * k + 1], rr, bf_hi(b2w[k >> 1]));
      const float g0 = o0 * rcpf_(1.f + ex2f(o0 * -1.4426950408889634f)), g1 = o1 * rcpf_(1.f + ex2f(o1 * -1.4426950408889634f));
      xw[k] = pack_bf2(fmaf(bf_lo(sw[k]), g0, bf_lo(xw[k])), fmaf(bf_hi(sw[k]), g1, bf_hi(xw[k])));
    }
#pragma unroll
    for (int q = 0; q < 4; q++) stsm4(xa + (((2 * q + (lane >> 4)) ^ (lane & 7)) << 4), xw[4 * q], xw[4 * q + 1], xw[4 * q + 2], xw[4 * q + 3]);
    fence_async();
    __syncwarp();
    if (lane == 0) {
      tma_store_2d(&tm_out, sb + OFF_X + 2 * 16384 + (tid >> 5) * 2048, 64 * rk, 128 * G + 16 * (tid >> 5));
      bulk_commit();
      bulk_wait0_read();
    }
    TSTAMP(8);
    TSDUMP();
  }
}

typedef CUresult (*EncodeFn)(CUtensorMap*, CUtensorMapDataType, cuuint32_t, void*, const cuuint64_t*, const cuuint64_t*,
                             const cuuint32_t*, const cuuint32_t*, CUtensorMapInterleave, CUtensorMapSwizzle,
                             CUtensorMapL2promotion, CUtensorMapFloatOOBfill);

void make_map(EncodeFn fn, CUtensorMap* m, const void* ptr, int rank, const cuuint64_t* dims, const cuuint64_t* strides, const cuuint32_t* box) {
  const cuuint32_t es[3] = {1, 1, 1};
  fn(m, CU_TENSOR_MAP_DATA_TYPE_BFLOAT16, rank, const_cast<void*>(ptr), dims, strides, box, es, CU_TENSOR_MAP_INTERLEAVE_NONE,
     CU_TENSOR_MAP_SWIZZLE_128B, CU_TENSOR_MAP_L2_PROMOTION_L2_128B, CU_TENSOR_MAP_FLOAT_OOB_FILL_NONE);
}

}

extern "C" void kernel_launch(void* const* d_in, const int* in_sizes, int n_in, void* d_out, int out_size) {
  (void)in_sizes; (void)n_in; (void)out_size;
  void* fnp = nullptr;
  cudaDriverEntryPointQueryResult qr;
  cudaGetDriverEntryPoint("cuTensorMapEncodeTiled", &fnp, cudaEnableDefault, &qr);
  EncodeFn fn = (EncodeFn)fnp;
  Params p;
  p.x = (const __nv_bfloat16*)d_in[0];
  p.a_re = (const __nv_bfloat16*)d_in[1]; p.a_im = (const __nv_bfloat16*)d_in[2];
  p.b_re = (const __nv_bfloat16*)d_in[3]; p.b_im = (const __nv_bfloat16*)d_in[4];
  p.c_re = (const __nv_bfloat16*)d_in[5]; p.c_im = (const __nv_bfloat16*)d_in[6];
  p.log_dt = (const __nv_bfloat16*)d_in[7]; p.dskip = (const __nv_bfloat16*)d_in[8];
  p.w1 = (const __nv_bfloat16*)d_in[10]; p.b1 = (const __nv_bfloat16*)d_in[11];
  p.w2 = (const __nv_bfloat16*)d_in[12]; p.b2 = (const __nv_bfloat16*)d_in[13];
  void* sp = nullptr;
  cudaGetSymbolAddress(&sp, g_scr);
  p.s = (Scratch*)sp;
  CUtensorMap mx, mw1, mw2, mo;
  {
    const cuuint64_t dims[2] = {448, 2048}, str[1] = {896};
    const cuuint32_t box[2] = {64, 128}, boxo[2] = {64, 16};
    make_map(fn, &mx, p.x, 2, dims, str, box);
    make_map(fn, &mo, d_out, 2, dims, str, boxo);
  }
  {
    const cuuint64_t dims[3] = {64, 448, 28}, str[2] = {3584, 128};
    const cuuint32_t box[3] = {64, 64, 4};
    make_map(fn, &mw1, p.w1, 3, dims, str, box);
  }
  {
    const cuuint64_t dims[2] = {448, 1792}, str[1] = {896};
    const cuuint32_t box[2] = {64, 256};
    make_map(fn, &mw2, p.w2, 2, dims, str, box);
  }
  cudaFuncSetAttribute(fused_kernel, cudaFuncAttributeMaxDynamicSharedMemorySize, SMEM_BYTES);
  fused_kernel<<<NCTA, 384, SMEM_BYTES>>>(p, mx, mw1, mw2, mo);
}
```

```cpp
#include <cuda_runtime.h>
#include <cuda_bf16.h>
#include <cuda_fp16.h>
#include <cuda.h>
#include <stdint.h>

namespace {

constexpr int D_ = 448, NST = 256, F_ = 1792;
constexpr int NRK = 7, NMLP = 112, NCTA = 132;
constexpr int SPIN_MAX = 1 << 20, RETRY_MAX = 512;

struct Scratch {
  unsigned cntA, pad0[31], cntT, pad1[31], epoch, pad2[63];
  uint4 ax[2048];
  uint4 bx[7 * 512];
  uint4 tbl[112 * 329];
  uint4 xnT[224 * 512];
  uint4 s2[16 * 224 * 32];
  uint4 part[16 * 7 * 6 * 1024];
};
__device__ Scratch g_scr;
#define TSTAMP(i)
#define TSINIT()
#define TSDUMP()
extern __shared__ __align__(1024) uint8_t smem_raw[];

constexpr int TBL_SC = 5248, TBL = 5264;
constexpr int TBL_C1 = 2624;
constexpr int SIG = 19584;
constexpr int SIG_U = 0, U_LBO = 656, SIG_V3 = 6272, SIG_V5 = 10368, SIG_V7 = 13440, SIG_V9 = 15488, SIG_V2 = 17536;
constexpr int Y2B = 6528, Y3B = 4352;
constexpr int KREC = 160, KSTG = 32 * KREC;
constexpr int OFF_W = 0, OFF_X = 98304, OFF_A = 147456, OFF_B = OFF_A + 8 * KSTG + 2560, OFF_T = OFF_B + 4 * KSTG;
constexpr int OFF_M = OFF_T + 15872;
constexpr int B_AX = Y2B, B_BX = B_AX + 2048;
constexpr int M_BAR = 0, M_REL = 128, M_EP = 192, M_CSR = 256, M_LT = 1280, M_END = 1536;
constexpr int SMEM_BYTES = OFF_M + M_END + 384;
constexpr int S_WORK = 63232, S_WGB = 2 * SIG + Y2B + Y3B;
static_assert(S_WORK + 3 * S_WGB <= OFF_M && SMEM_BYTES <= 232448, "smem");

struct Params {
  const __nv_bfloat16 *x, *a_re, *a_im, *b_re, *b_im, *c_re, *c_im, *log_dt, *dskip, *w1, *b1, *w2, *b2;
  Scratch* s;
};

__device__ __forceinline__ int opaque(int x) { int v; asm volatile("mov.u32 %0, %1;" : "=r"(v) : "r"(x)); return v; }
__device__ __forceinline__ int rd_bid() { int v; asm volatile("mov.u32 %0, %%ctaid.x;" : "=r"(v)); return v; }
__device__ __forceinline__ uint32_t smem_u32(const void* p) { return (uint32_t)__cvta_generic_to_shared(p); }
__device__ __forceinline__ void mbar_init(uint32_t bar, int cnt) { asm volatile("mbarrier.init.shared::cta.b64 [%0], %1;" ::"r"(bar), "r"(cnt)); }
__device__ __forceinline__ void mbar_expect(uint32_t bar, uint32_t bytes) {
  asm volatile("mbarrier.arrive.expect_tx.shared::cta.b64 _, [%0], %1;" ::"r"(bar), "r"(bytes) : "memory");
}
__device__ __forceinline__ void mbar_wait(uint32_t bar, uint32_t parity) {
  uint32_t done = 0;
#pragma unroll 1
  for (int it = 0; it < SPIN_MAX; it++) {
    asm volatile("{.reg .pred p; mbarrier.try_wait.parity.shared::cta.b64 p, [%1], %2; selp.u32 %0,1,0,p;}"
                 : "=r"(done) : "r"(bar), "r"(parity) : "memory");
    if (done) break;
  }
}
__device__ __forceinline__ void tma_2d(uint32_t dst, const CUtensorMap* m, int c0, int c1, uint32_t bar) {
  asm volatile("cp.async.bulk.tensor.2d.shared::cluster.global.mbarrier::complete_tx::bytes [%0], [%1, {%3, %4}], [%2];"
               ::"r"(dst), "l"(m), "r"(bar), "r"(c0), "r"(c1) : "memory");
}
__device__ __forceinline__ void tma_3d(uint32_t dst, const CUtensorMap* m, int c0, int c1, int c2, uint32_t bar) {
  asm volatile("cp.async.bulk.tensor.3d.shared::cluster.global.mbarrier::complete_tx::bytes [%0], [%1, {%3, %4, %5}], [%2];"
               ::"r"(dst), "l"(m), "r"(bar), "r"(c0), "r"(c1), "r"(c2) : "memory");
}
__device__ __forceinline__ void tma_store_2d(const CUtensorMap* m, uint32_t src, int c0, int c1) {
  asm volatile("cp.async.bulk.tensor.2d.global.shared::cta.bulk_group [%0, {%2, %3}], [%1];"
               ::"l"(m), "r"(src), "r"(c0), "r"(c1) : "memory");
}
__device__ __forceinline__ void bulk_s2g(void* dst, uint32_t src, uint32_t bytes) {
  asm volatile("cp.async.bulk.global.shared::cta.bulk_group [%0], [%1], %2;" ::"l"(dst), "r"(src), "r"(bytes) : "memory");
}
__device__ __forceinline__ void bulk_g2s(uint32_t dst, const void* src, uint32_t bytes, uint32_t bar) {
  asm volatile("cp.async.bulk.shared::cluster.global.mbarrier::complete_tx::bytes [%0], [%1], %2, [%3];"
               ::"r"(dst), "l"(src), "r"(bytes), "r"(bar) : "memory");
}
__device__ __forceinline__ void bulk_commit() { asm volatile("cp.async.bulk.commit_group;" ::: "memory"); }
__device__ __forceinline__ void bulk_wait0() { asm volatile("cp.async.bulk.wait_group 0;" ::: "memory"); }
__device__ __forceinline__ void bulk_wait0_read() { asm volatile("cp.async.bulk.wait_group.read 0;" ::: "memory"); }
__device__ __forceinline__ void fence_async() { asm volatile("fence.proxy.async.shared::cta;" ::: "memory"); }
__device__ __forceinline__ void bar_sync(int id, int n) { asm volatile("bar.sync %0, %1;" ::"r"(id), "r"(n) : "memory"); }
__device__ __forceinline__ void bar_arrive(int id, int n) { asm volatile("bar.arrive %0, %1;" ::"r"(id), "r"(n) : "memory"); }
__device__ __forceinline__ void wg_fence() { asm volatile("wgmma.fence.sync.aligned;" ::: "memory"); }
__device__ __forceinline__ void wg_commit() { asm volatile("wgmma.commit_group.sync.aligned;" ::: "memory"); }
template <int N> __device__ __forceinline__ void wg_wait() { asm volatile("wgmma.wait_group.sync.aligned %0;" ::"n"(N) : "memory"); }
template <int N> __device__ __forceinline__ void fence_regs(float* d) {
#pragma unroll
  for (int i = 0; i < N; i++) asm volatile("" : "+f"(d[i])::"memory");
}
__device__ __forceinline__ uint64_t mkdesc(uint32_t addr, uint32_t lbo, uint32_t sbo, uint32_t sw) {
  return (uint64_t)((addr & 0x3FFFF) >> 4) | ((uint64_t)(lbo >> 4) << 16) | ((uint64_t)(sbo >> 4) << 32) | ((uint64_t)sw << 62);
}
__device__ __forceinline__ uint32_t lds32(uint32_t a) { uint32_t v; asm volatile("ld.shared.b32 %0, [%1];" : "=r"(v) : "r"(a) : "memory"); return v; }
__device__ __forceinline__ float lds32f(uint32_t a) { float v; asm volatile("ld.shared.f32 %0, [%1];" : "=f"(v) : "r"(a) : "memory"); return v; }
__device__ __forceinline__ float2 lds64f(uint32_t a) { float2 v; asm volatile("ld.shared.v2.f32 {%0,%1}, [%2];" : "=f"(v.x), "=f"(v.y) : "r"(a) : "memory"); return v; }
__device__ __forceinline__ uint4 lds128(uint32_t a) {
  uint4 v; asm volatile("ld.shared.v4.b32 {%0,%1,%2,%3}, [%4];" : "=r"(v.x), "=r"(v.y), "=r"(v.z), "=r"(v.w) : "r"(a) : "memory"); return v;
}
__device__ __forceinline__ void sts16(uint32_t a, uint16_t v) { asm volatile("st.shared.b16 [%0], %1;" ::"r"(a), "h"(v) : "memory"); }
__device__ __forceinline__ void sts32f(uint32_t a, float v) { asm volatile("st.shared.f32 [%0], %1;" ::"r"(a), "f"(v) : "memory"); }
__device__ __forceinline__ void sts64f(uint32_t a, float x, float y) { asm volatile("st.shared.v2.f32 [%0], {%1,%2};" ::"r"(a), "f"(x), "f"(y) : "memory"); }
__device__ __forceinline__ void sts128(uint32_t a, uint32_t x, uint32_t y, uint32_t z, uint32_t w) {
  asm volatile("st.shared.v4.b32 [%0], {%1,%2,%3,%4};" ::"r"(a), "r"(x), "r"(y), "r"(z), "r"(w) : "memory");
}
__device__ __forceinline__ void ldsm4(uint32_t a, uint32_t& r0, uint32_t& r1, uint32_t& r2, uint32_t& r3) {
  asm volatile("ldmatrix.sync.aligned.m8n8.x4.shared.b16 {%0,%1,%2,%3}, [%4];" : "=r"(r0), "=r"(r1), "=r"(r2), "=r"(r3) : "r"(a) : "memory");
}
__device__ __forceinline__ void ldsm4t(uint32_t a, uint32_t& r0, uint32_t& r1, uint32_t& r2, uint32_t& r3) {
  asm volatile("ldmatrix.sync.aligned.m8n8.x4.trans.shared.b16 {%0,%1,%2,%3}, [%4];" : "=r"(r0), "=r"(r1), "=r"(r2), "=r"(r3) : "r"(a) : "memory");
}
__device__ __forceinline__ void ldsm2t(uint32_t a, uint32_t& r0, uint32_t& r1) {
  asm volatile("ldmatrix.sync.aligned.m8n8.x2.trans.shared.b16 {%0,%1}, [%2];" : "=r"(r0), "=r"(r1) : "r"(a) : "memory");
}
__device__ __forceinline__ void stsm4(uint32_t a, uint32_t r0, uint32_t r1, uint32_t r2, uint32_t r3) {
  asm volatile("stmatrix.sync.aligned.m8n8.x4.shared.b16 [%0], {%1,%2,%3,%4};" ::"r"(a), "r"(r0), "r"(r1), "r"(r2), "r"(r3) : "memory");
}
__device__ __forceinline__ void mma_f16(float* c, uint32_t a0, uint32_t a1, uint32_t a2, uint32_t a3, uint32_t b0, uint32_t b1) {
  asm("mma.sync.aligned.m16n8k16.row.col.f32.f16.f16.f32 {%0,%1,%2,%3},{%4,%5,%6,%7},{%8,%9},{%0,%1,%2,%3};"
               : "+f"(c[0]), "+f"(c[1]), "+f"(c[2]), "+f"(c[3]) : "r"(a0), "r"(a1), "r"(a2), "r"(a3), "r"(b0), "r"(b1));
}
__device__ __forceinline__ void mma_bf16(float* c, uint32_t a0, uint32_t a1, uint32_t a2, uint32_t a3, uint32_t b0, uint32_t b1) {
  asm("mma.sync.aligned.m16n8k16.row.col.f32.bf16.bf16.f32 {%0,%1,%2,%3},{%4,%5,%6,%7},{%8,%9},{%0,%1,%2,%3};"
      : "+f"(c[0]), "+f"(c[1]), "+f"(c[2]), "+f"(c[3]) : "r"(a0), "r"(a1), "r"(a2), "r"(a3), "r"(b0), "r"(b1));
}
__device__ __forceinline__ uint4 ld_relaxed4(const void* p) {
  uint4 v; asm volatile("ld.relaxed.gpu.global.v4.b32 {%0,%1,%2,%3}, [%4];" : "=r"(v.x), "=r"(v.y), "=r"(v.z), "=r"(v.w) : "l"(p) : "memory"); return v;
}
__device__ __forceinline__ uint4 ld_2x64(const void* p) {
  uint4 v;
  asm volatile("{.reg .b64 a, c; ld.relaxed.gpu.global.v2.b64 {a, c}, [%4]; mov.b64 {%0,%1}, a; mov.b64 {%2,%3}, c;}"
               : "=r"(v.x), "=r"(v.y), "=r"(v.z), "=r"(v.w) : "l"(p) : "memory");
  return v;
}
__device__ __forceinline__ void st_relaxed2(void* p, uint32_t x, uint32_t y) {
  asm volatile("st.relaxed.gpu.global.v2.b32 [%0], {%1,%2};" ::"l"(p), "r"(x), "r"(y) : "memory");
}
__device__ __forceinline__ uint4 ld_b128(const void* p) {
  uint4 v;
  asm volatile("{.reg .b128 t; .reg .b64 a, c; ld.relaxed.gpu.global.b128 t, [%4]; mov.b128 {a, c}, t; mov.b64 {%0,%1}, a; mov.b64 {%2,%3}, c;}"
               : "=r"(v.x), "=r"(v.y), "=r"(v.z), "=r"(v.w) : "l"(p) : "memory");
  return v;
}
__device__ __forceinline__ void st_b128(void* p, uint32_t tag, uint32_t x, uint32_t y, uint32_t z, uint32_t w) {
  asm volatile("{.reg .b128 t; .reg .b64 a, c; mov.b64 a, {%1,%2}; mov.b64 c, {%3,%4}; mov.b128 t, {a, c}; st.relaxed.gpu.global.b128 [%0], t;}"
               ::"l"(p), "r"((x & ~1u) | tag), "r"(y), "r"(z), "r"(w) : "memory");
}
__device__ __forceinline__ unsigned ld_relaxed1(const unsigned* p) {
  unsigned v; asm volatile("ld.relaxed.gpu.global.u32 %0, [%1];" : "=r"(v) : "l"(p) : "memory"); return v;
}
__device__ __forceinline__ void red_relaxed(unsigned* p) {
  asm volatile("red.relaxed.gpu.global.add.u32 [%0], 1;" ::"l"(p) : "memory");
}
__device__ __forceinline__ void red_release(unsigned* p) {
  asm volatile("red.release.gpu.global.add.u32 [%0], 1;" ::"l"(p) : "memory");
}
__device__ __forceinline__ void wait_count(const unsigned* p, unsigned target) {
#pragma unroll 1
  for (int it = 0; it < SPIN_MAX; it++) {
    if ((int)(ld_relaxed1(p) - target) >= 0) break;
    __nanosleep(40);
  }
  asm volatile("fence.acq_rel.gpu;" ::: "memory");
}
__device__ __forceinline__ uint32_t pack_h2(float lo, float hi) { uint32_t r; asm("cvt.rn.f16x2.f32 %0, %1, %2;" : "=r"(r) : "f"(hi), "f"(lo)); return r; }
__device__ __forceinline__ uint32_t pack_bf2(float lo, float hi) { uint32_t r; asm("cvt.rn.bf16x2.f32 %0, %1, %2;" : "=r"(r) : "f"(hi), "f"(lo)); return r; }
__device__ __forceinline__ float bf_lo(uint32_t w) { return __uint_as_float(w << 16); }
__device__ __forceinline__ float bf_hi(uint32_t w) { return __uint_as_float(w & 0xffff0000u); }
__device__ __forceinline__ float rbf(float v) { return __bfloat162float(__float2bfloat16_rn(v)); }
__device__ __forceinline__ float2 h2f(uint32_t w) { return __half22float2(*reinterpret_cast<__half2*>(&w)); }
__device__ __forceinline__ float ex2f(float v) { float r; asm("ex2.approx.ftz.f32 %0, %1;" : "=f"(r) : "f"(v)); return r; }
__device__ __forceinline__ float rcpf_(float v) { float r; asm("rcp.approx.f32 %0, %1;" : "=f"(r) : "f"(v)); return r; }
__device__ __forceinline__ float sqrtf_(float v) { float r; asm("sqrt.approx.f32 %0, %1;" : "=f"(r) : "f"(v)); return r; }
__device__ __forceinline__ float tanhf_(float v) { float r; asm volatile("tanh.approx.f32 %0, %1;" : "=f"(r) : "f"(v)); return r; }

__device__ __forceinline__ void wg_ss_bf16_n256(float* d, uint64_t da, uint64_t db, int sc) {
  asm volatile("{.reg .pred p; setp.ne.b32 p, %130, 0;\n"
    "wgmma.mma_async.sync.aligned.m64n256k16.f32.bf16.bf16 {%0, %1, %2, %3, %4, %5, %6, %7, %8, %9, %10, %11, %12, %13, %14, %15, %16, %17, %18, %19, %20, %21, %22, %23, %24, %25, %26, %27, %28, %29, %30, %31, %32, %33, %34, %35, %36, %37, %38, %39, %40, %41, %42, %43, %44, %45, %46, %47, %48, %49, %50, %51, %52, %53, %54, %55, %56, %57, %58, %59, %60, %61, %62, %63, %64, %65, %66, %67, %68, %69, %70, %71, %72, %73, %74, %75, %76, %77, %78, %79, %80, %81, %82, %83, %84, %85, %86, %87, %88, %89, %90, %91, %92, %93, %94, %95, %96, %97, %98, %99, %100, %101, %102, %103, %104, %105, %106, %107, %108, %109, %110, %111, %112, %113, %114, %115, %116, %117, %118, %119, %120, %121, %122, %123, %124, %125, %126, %127}, %128, %129, p, 1, 1, 0, 1;}\n"
    : "+f"(d[0]), "+f"(d[1]), "+f"(d[2]), "+f"(d[3]), "+f"(d[4]), "+f"(d[5]), "+f"(d[6]), "+f"(d[7]), "+f"(d[8]), "+f"(d[9]), "+f"(d[10]), "+f"(d[11]), "+f"(d[12]), "+f"(d[13]), "+f"(d[14]), "+f"(d[15]), "+f"(d[16]), "+f"(d[17]), "+f"(d[18]), "+f"(d[19]), "+f"(d[20]), "+f"(d[21]), "+f"(d[22]), "+f"(d[23]), "+f"(d[24]), "+f"(d[25]), "+f"(d[26]), "+f"(d[27]), "+f"(d[28]), "+f"(d[29]), "+f"(d[30]), "+f"(d[31]), "+f"(d[32]), "+f"(d[33]), "+f"(d[34]), "+f"(d[35]), "+f"(d[36]), "+f"(d[37]), "+f"(d[38]), "+f"(d[39]), "+f"(d[40]), "+f"(d[41]), "+f"(d[42]), "+f"(d[43]), "+f"(d[44]), "+f"(d[45]), "+f"(d[46]), "+f"(d[47]), "+f"(d[48]), "+f"(d[49]), "+f"(d[50]), "+f"(d[51]), "+f"(d[52]), "+f"(d[53]), "+f"(d[54]), "+f"(d[55]), "+f"(d[56]), "+f"(d[57]), "+f"(d[58]), "+f"(d[59]), "+f"(d[60]), "+f"(d[61]), "+f"(d[62]), "+f"(d[63]), "+f"(d[64]), "+f"(d[65]), "+f"(d[66]), "+f"(d[67]), "+f"(d[68]), "+f"(d[69]), "+f"(d[70]), "+f"(d[71]), "+f"(d[72]), "+f"(d[73]), "+f"(d[74]), "+f"(d[75]), "+f"(d[76]), "+f"(d[77]), "+f"(d[78]), "+f"(d[79]), "+f"(d[80]), "+f"(d[81]), "+f"(d[82]), "+f"(d[83]), "+f"(d[84]), "+f"(d[85]), "+f"(d[86]), "+f"(d[87]), "+f"(d[88]), "+f"(d[89]), "+f"(d[90]), "+f"(d[91]), "+f"(d[92]), "+f"(d[93]), "+f"(d[94]), "+f"(d[95]), "+f"(d[96]), "+f"(d[97]), "+f"(d[98]), "+f"(d[99]), "+f"(d[100]), "+f"(d[101]), "+f"(d[102]), "+f"(d[103]), "+f"(d[104]), "+f"(d[105]), "+f"(d[106]), "+f"(d[107]), "+f"(d[108]), "+f"(d[109]), "+f"(d[110]), "+f"(d[111]), "+f"(d[112]), "+f"(d[113]), "+f"(d[114]), "+f"(d[115]), "+f"(d[116]), "+f"(d[117]), "+f"(d[118]), "+f"(d[119]), "+f"(d[120]), "+f"(d[121]), "+f"(d[122]), "+f"(d[123]), "+f"(d[124]), "+f"(d[125]), "+f"(d[126]), "+f"(d[127])
    : "l"(da), "l"(db), "r"(sc));
}

__device__ __forceinline__ void wg_ss_bf16_n256k(float* d, uint64_t da, uint64_t db, int sc) {
  asm volatile("{.reg .pred p; setp.ne.b32 p, %130, 0;\n"
    "wgmma.mma_async.sync.aligned.m64n256k16.f32.bf16.bf16 {%0, %1, %2, %3, %4, %5, %6, %7, %8, %9, %10, %11, %12, %13, %14, %15, %16, %17, %18, %19, %20, %21, %22, %23, %24, %25, %26, %27, %28, %29, %30, %31, %32, %33, %34, %35, %36, %37, %38, %39, %40, %41, %42, %43, %44, %45, %46, %47, %48, %49, %50, %51, %52, %53, %54, %55, %56, %57, %58, %59, %60, %61, %62, %63, %64, %65, %66, %67, %68, %69, %70, %71, %72, %73, %74, %75, %76, %77, %78, %79, %80, %81, %82, %83, %84, %85, %86, %87, %88, %89, %90, %91, %92, %93, %94, %95, %96, %97, %98, %99, %100, %101, %102, %103, %104, %105, %106, %107, %108, %109, %110, %111, %112, %113, %114, %115, %116, %117, %118, %119, %120, %121, %122, %123, %124, %125, %126, %127}, %128, %129, p, 1, 1, 0, 0;}\n"
    : "+f"(d[0]), "+f"(d[1]), "+f"(d[2]), "+f"(d[3]), "+f"(d[4]), "+f"(d[5]), "+f"(d[6]), "+f"(d[7]), "+f"(d[8]), "+f"(d[9]), "+f"(d[10]), "+f"(d[11]), "+f"(d[12]), "+f"(d[13]), "+f"(d[14]), "+f"(d[15]), "+f"(d[16]), "+f"(d[17]), "+f"(d[18]), "+f"(d[19]), "+f"(d[20]), "+f"(d[21]), "+f"(d[22]), "+f"(d[23]), "+f"(d[24]), "+f"(d[25]), "+f"(d[26]), "+f"(d[27]), "+f"(d[28]), "+f"(d[29]), "+f"(d[30]), "+f"(d[31]), "+f"(d[32]), "+f"(d[33]), "+f"(d[34]), "+f"(d[35]), "+f"(d[36]), "+f"(d[37]), "+f"(d[38]), "+f"(d[39]), "+f"(d[40]), "+f"(d[41]), "+f"(d[42]), "+f"(d[43]), "+f"(d[44]), "+f"(d[45]), "+f"(d[46]), "+f"(d[47]), "+f"(d[48]), "+f"(d[49]), "+f"(d[50]), "+f"(d[51]), "+f"(d[52]), "+f"(d[53]), "+f"(d[54]), "+f"(d[55]), "+f"(d[56]), "+f"(d[57]), "+f"(d[58]), "+f"(d[59]), "+f"(d[60]), "+f"(d[61]), "+f"(d[62]), "+f"(d[63]), "+f"(d[64]), "+f"(d[65]), "+f"(d[66]), "+f"(d[67]), "+f"(d[68]), "+f"(d[69]), "+f"(d[70]), "+f"(d[71]), "+f"(d[72]), "+f"(d[73]), "+f"(d[74]), "+f"(d[75]), "+f"(d[76]), "+f"(d[77]), "+f"(d[78]), "+f"(d[79]), "+f"(d[80]), "+f"(d[81]), "+f"(d[82]), "+f"(d[83]), "+f"(d[84]), "+f"(d[85]), "+f"(d[86]), "+f"(d[87]), "+f"(d[88]), "+f"(d[89]), "+f"(d[90]), "+f"(d[91]), "+f"(d[92]), "+f"(d[93]), "+f"(d[94]), "+f"(d[95]), "+f"(d[96]), "+f"(d[97]), "+f"(d[98]), "+f"(d[99]), "+f"(d[100]), "+f"(d[101]), "+f"(d[102]), "+f"(d[103]), "+f"(d[104]), "+f"(d[105]), "+f"(d[106]), "+f"(d[107]), "+f"(d[108]), "+f"(d[109]), "+f"(d[110]), "+f"(d[111]), "+f"(d[112]), "+f"(d[113]), "+f"(d[114]), "+f"(d[115]), "+f"(d[116]), "+f"(d[117]), "+f"(d[118]), "+f"(d[119]), "+f"(d[120]), "+f"(d[121]), "+f"(d[122]), "+f"(d[123]), "+f"(d[124]), "+f"(d[125]), "+f"(d[126]), "+f"(d[127])
    : "l"(da), "l"(db), "r"(sc));
}

__device__ __forceinline__ void wg_rs_bf16_n64(float* d, uint32_t a0, uint32_t a1, uint32_t a2, uint32_t a3, uint64_t db, int sc) {
  asm volatile("{.reg .pred p; setp.ne.b32 p, %37, 0;\n"
    "wgmma.mma_async.sync.aligned.m64n64k16.f32.bf16.bf16 {%0, %1, %2, %3, %4, %5, %6, %7, %8, %9, %10, %11, %12, %13, %14, %15, %16, %17, %18, %19, %20, %21, %22, %23, %24, %25, %26, %27, %28, %29, %30, %31}, {%32,%33,%34,%35}, %36, p, 1, 1, 1;}\n"
    : "+f"(d[0]), "+f"(d[1]), "+f"(d[2]), "+f"(d[3]), "+f"(d[4]), "+f"(d[5]), "+f"(d[6]), "+f"(d[7]), "+f"(d[8]), "+f"(d[9]), "+f"(d[10]), "+f"(d[11]), "+f"(d[12]), "+f"(d[13]), "+f"(d[14]), "+f"(d[15]), "+f"(d[16]), "+f"(d[17]), "+f"(d[18]), "+f"(d[19]), "+f"(d[20]), "+f"(d[21]), "+f"(d[22]), "+f"(d[23]), "+f"(d[24]), "+f"(d[25]), "+f"(d[26]), "+f"(d[27]), "+f"(d[28]), "+f"(d[29]), "+f"(d[30]), "+f"(d[31])
    : "r"(a0), "r"(a1), "r"(a2), "r"(a3), "l"(db), "r"(sc));
}

__device__ __forceinline__ void wg_rs_f16_n32k(float* d, uint32_t a0, uint32_t a1, uint32_t a2, uint32_t a3, uint64_t db, int sc) {
  asm volatile("{.reg .pred p; setp.ne.b32 p, %21, 0;\n"
    "wgmma.mma_async.sync.aligned.m64n32k16.f32.f16.f16 {%0, %1, %2, %3, %4, %5, %6, %7, %8, %9, %10, %11, %12, %13, %14, %15}, {%16,%17,%18,%19}, %20, p, 1, 1, 0;}\n"
    : "+f"(d[0]), "+f"(d[1]), "+f"(d[2]), "+f"(d[3]), "+f"(d[4]), "+f"(d[5]), "+f"(d[6]), "+f"(d[7]), "+f"(d[8]), "+f"(d[9]), "+f"(d[10]), "+f"(d[11]), "+f"(d[12]), "+f"(d[13]), "+f"(d[14]), "+f"(d[15])
    : "r"(a0), "r"(a1), "r"(a2), "r"(a3), "l"(db), "r"(sc));
}

__device__ __forceinline__ void wg_rs_f16_n24t(float* d, uint32_t a0, uint32_t a1, uint32_t a2, uint32_t a3, uint64_t db, int sc) {
  asm volatile("{.reg .pred p; setp.ne.b32 p, %17, 0;\n"
    "wgmma.mma_async.sync.aligned.m64n24k16.f32.f16.f16 {%0, %1, %2, %3, %4, %5, %6, %7, %8, %9, %10, %11}, {%12,%13,%14,%15}, %16, p, 1, 1, 1;}\n"
    : "+f"(d[0]), "+f"(d[1]), "+f"(d[2]), "+f"(d[3]), "+f"(d[4]), "+f"(d[5]), "+f"(d[6]), "+f"(d[7]), "+f"(d[8]), "+f"(d[9]), "+f"(d[10]), "+f"(d[11])
    : "r"(a0), "r"(a1), "r"(a2), "r"(a3), "l"(db), "r"(sc));
}

__device__ __forceinline__ void wg_rs_f16_n16t(float* d, uint32_t a0, uint32_t a1, uint32_t a2, uint32_t a3, uint64_t db, int sc) {
  asm volatile("{.reg .pred p; setp.ne.b32 p, %13, 0;\n"
    "wgmma.mma_async.sync.aligned.m64n16k16.f32.f16.f16 {%0, %1, %2, %3, %4, %5, %6, %7}, {%8,%9,%10,%11}, %12, p, 1, 1, 1;}\n"
    : "+f"(d[0]), "+f"(d[1]), "+f"(d[2]), "+f"(d[3]), "+f"(d[4]), "+f"(d[5]), "+f"(d[6]), "+f"(d[7])
    : "r"(a0), "r"(a1), "r"(a2), "r"(a3), "l"(db), "r"(sc));
}

struct cf { float x, y; };
__device__ __forceinline__ cf cmul(cf a, cf b) { cf r; r.x = fmaf(a.x, b.x, -a.y * b.y); r.y = fmaf(a.x, b.y, a.y * b.x); return r; }
__device__ __forceinline__ cf zpow(float rho2, float phi, float e) {
  const float m = ex2f(rho2 * e), ang = phi * e;
  cf r; r.x = m * __cosf(ang); r.y = m * __sinf(ang); return r;
}
__device__ __forceinline__ __half2 H2(uint32_t v) { return *reinterpret_cast<__half2*>(&v); }
__device__ __forceinline__ uint32_t U32(__half2 v) { return *reinterpret_cast<uint32_t*>(&v); }
__device__ __forceinline__ uint32_t hprod(uint32_t v, uint32_t r, uint32_t rr) {
  return U32(__hfma2(__high2half2(H2(v)), H2(rr), __hmul2(__low2half2(H2(v)), H2(r))));
}
template <bool CONJ>
__device__ __forceinline__ void hprod2(uint32_t re, uint32_t im, uint32_t r, uint32_t& ore, uint32_t& oim) {
  const __half2 rx = __low2half2(H2(r)), ry = __high2half2(H2(r));
  if (CONJ) {
    ore = U32(__hfma2(H2(re), rx, __hmul2(H2(im), ry)));
    oim = U32(__hfma2(H2(im), rx, __hneg2(__hmul2(H2(re), ry))));
  } else {
    ore = U32(__hfma2(H2(re), rx, __hneg2(__hmul2(H2(im), ry))));
    oim = U32(__hfma2(H2(re), ry, __hmul2(H2(im), rx)));
  }
}
__device__ __forceinline__ cf csq(cf a) { cf r; r.x = fmaf(a.x, a.x, -a.y * a.y); r.y = (a.x + a.x) * a.y; return r; }
__device__ __forceinline__ cf cmulc(cf a, cf b) { cf r; r.x = fmaf(a.x, b.x, a.y * b.y); r.y = fmaf(a.y, b.x, -a.x * b.y); return r; }
__device__ __forceinline__ uint32_t pk(cf a) { return pack_h2(a.x, a.y); }
__device__ __forceinline__ uint32_t ldg32(const void* p, int o) { uint32_t v; asm volatile("ld.global.nc.b32 %0, [%1];" : "=r"(v) : "l"((const char*)p + o)); return v; }
__device__ __forceinline__ uint32_t rot90(uint32_t v) { return __byte_perm(v, 0, 0x1032) ^ 0x00008000u; }
__device__ __forceinline__ uint32_t hadd2u(uint32_t a, uint32_t b) { return U32(__hadd2(H2(a), H2(b))); }

struct KgIn { uint32_t cur[6], nxt[6], ldt, dk; bool odd; };
__device__ __forceinline__ float pow2_floor(float v) { return __uint_as_float(__float_as_uint(fminf(fmaxf(v, 1e-30f), 1e30f)) & 0x7f800000u); }
__device__ __forceinline__ void kgen_mma(float* acc, const uint32_t (*A)[4], const uint32_t (*B)[6], int csrc) {
#pragma unroll
  for (int ks = 0; ks < 4; ks++) {
    const uint32_t rl = __shfl_sync(0xffffffffu, B[ks][4], csrc), rh = __shfl_sync(0xffffffffu, B[ks][5], csrc);
    const uint32_t rlr = rot90(rl), rhr = rot90(rh);
    mma_f16(acc + 0, A[ks][0], A[ks][1], A[ks][2], A[ks][3], B[ks][0], B[ks][1]);
    mma_f16(acc + 4, A[ks][0], A[ks][1], A[ks][2], A[ks][3], B[ks][2], B[ks][3]);
    mma_f16(acc + 8, A[ks][0], A[ks][1], A[ks][2], A[ks][3], B[ks][4], B[ks][5]);
    const uint32_t c0 = hprod(A[ks][0], rl, rlr), c1 = hprod(A[ks][1], rl, rlr);
    const uint32_t c2 = hprod(A[ks][2], rh, rhr), c3 = hprod(A[ks][3], rh, rhr);
    mma_f16(acc + 12, c0, c1, c2, c3, B[ks][0], B[ks][1]);
    mma_f16(acc + 16, c0, c1, c2, c3, B[ks][2], B[ks][3]);
    mma_f16(acc + 20, c0, c1, c2, c3, B[ks][4], B[ks][5]);
  }
}
template <class Mid>
__device__ __forceinline__ void kgen_warp(KgIn& k, int nw, uint32_t stg, uint32_t tbl, int lane, Mid mid) {
  float dl, dt, sc, inv_sc;
  {
    const uint32_t M = 0x7fff7fffu;
    uint32_t mx[2];
#pragma unroll
    for (int i = 0; i < 2; i++) {
      const uint32_t m = __vmaxu2(__vmaxu2(k.cur[2 + 2 * i] & M, k.cur[3 + 2 * i] & M), __vmaxu2(k.nxt[2 + 2 * i] & M, k.nxt[3 + 2 * i] & M));
      mx[i] = __reduce_max_sync(0xffffffffu, max(m << 16, m & 0xffff0000u));
    }
    dt = rbf(ex2f((k.odd ? bf_hi(k.ldt) : bf_lo(k.ldt)) * 1.4426950408889634f));
    sc = pow2_floor(0.125f * __uint_as_float(mx[0]) * __uint_as_float(mx[1]));
    inv_sc = rcpf_(sc);
    if (lane == 0) sts64f(tbl + TBL_SC + 8, dt, (k.odd ? bf_hi(k.dk) : bf_lo(k.dk)) * rcpf_(dt));
    dl = dt * 1.4426950408889634f;
  }
  const uint32_t st0 = stg + lane * KREC + (((lane >> 2) & 1) << 4), st1 = st0 ^ 16;
  const int mat = lane >> 3, rowi = lane & 7;
  const uint32_t ldB = stg + (4 * (mat & 1) + (rowi >> 1)) * KREC + ((((mat >> 1) * 2 + (rowi & 1)) << 4) ^ ((mat & 1) << 4));
  const uint32_t ldA = stg + (4 * (mat >> 1) + (rowi >> 1)) * KREC + ((((mat & 1) * 2 + (rowi & 1)) << 4) ^ ((mat >> 1) << 4)) + 96;
  const int csrc = 20 + (lane & 3);
  float acc[24];
  uint32_t B[4][6], A[4][4];
#pragma unroll
  for (int i = 0; i < 24; i++) { acc[i] = 0.f; B[i / 6][i % 6] = 0u; }
#pragma unroll
  for (int i = 0; i < 16; i++) A[i / 4][i % 4] = 0u;
#pragma unroll 1
  for (int it = 0; it < 2 * nw; it++) {
    if (it == 1) mid();
    const uint32_t sel = (it & 1) ? 0x3244u : 0x1044u;
    float v[6];
#pragma unroll
    for (int i = 0; i < 6; i++) { v[i] = __uint_as_float(__byte_perm(k.cur[i], 0, sel)); if (it == 1) k.cur[i] = k.nxt[i]; }
    const float rho2 = v[0] * dl, phi = v[1] * dt;
    const cf bb = {v[2] * inv_sc, v[3] * -inv_sc}, cc = {v[4], v[5]};
    const cf X0 = cmulc(bb, cc);
    const cf z1 = zpow(rho2, phi, 1.f), z64 = zpow(rho2, phi, 64.f);
    kgen_mma(acc, A, B, csrc);
    const cf z2 = csq(z1), z3 = cmul(z2, z1), z4 = csq(z2), z8 = csq(z4), z16 = csq(z8), z24 = cmul(z16, z8), z32 = csq(z16);
    const cf z128 = csq(z64), y1 = csq(z128), y2 = csq(y1), y3 = cmul(y2, y1), y4 = csq(y2);
    const cf X4 = cmulc(X0, z4), W4 = cmulc(X0, y4), W8 = cmulc(W4, y4);
    uint32_t re[4], im[4], r2[4], i2[4];
    re[0] = pack_h2(X0.x, X4.x); im[0] = pack_h2(X0.y, X4.y);
    hprod2<true>(re[0], im[0], pk(z1), re[1], im[1]);
    hprod2<true>(re[0], im[0], pk(z2), re[2], im[2]);
    hprod2<true>(re[0], im[0], pk(z3), re[3], im[3]);
    sts128(st0, re[0], re[1], re[2], re[3]);
    sts128(st1, im[0], im[1], im[2], im[3]);
    const uint32_t hy1 = pk(y1), hy2 = pk(y2);
    hprod2<true>(re[0], im[0], hy1, r2[0], i2[0]);
    hprod2<true>(re[2], im[2], hy1, r2[1], i2[1]);
    hprod2<true>(re[0], im[0], hy2, r2[2], i2[2]);
    hprod2<true>(re[0], im[0], pk(y3), r2[3], i2[3]);
    sts128(st0 + 32, r2[0], r2[1], r2[2], r2[3]);
    sts128(st1 + 32, i2[0], i2[1], i2[2], i2[3]);
    const cf W5 = cmulc(W4, y1);
    re[0] = pack_h2(W4.x, W5.x); im[0] = pack_h2(W4.y, W5.y);
    hprod2<true>(re[0], im[0], hy2, re[1], im[1]);
    sts128(st0 + 64, re[0], re[1], pack_h2(W8.x, z128.x), hy1);
    sts128(st1 + 64, im[0], im[1], pack_h2(W8.y, z128.y), hy1);
    re[0] = pack_h2(1.f, z32.x); im[0] = pack_h2(0.f, z32.y);
    hprod2<false>(re[0], im[0], pk(z8), re[1], im[1]);
    hprod2<false>(re[0], im[0], pk(z16), re[2], im[2]);
    hprod2<false>(re[0], im[0], pk(z24), re[3], im[3]);
    const uint32_t h64 = pk(z64);
#pragma unroll
    for (int j = 0; j < 4; j++) hprod2<false>(re[j], im[j], h64, r2[j], i2[j]);
    sts128(st0 + 96, re[0], re[1], re[2], re[3]);
    sts128(st1 + 96, im[0], im[1], im[2], im[3]);
    sts128(st0 + 128, r2[0], r2[1], r2[2], r2[3]);
    sts128(st1 + 128, i2[0], i2[1], i2[2], i2[3]);
    __syncwarp();
#pragma unroll
    for (int ks = 0; ks < 4; ks++) {
      ldsm2t(ldB + ks * 8 * KREC + 64, B[ks][4], B[ks][5]);
      ldsm4t(ldA + ks * 8 * KREC, A[ks][0], A[ks][1], A[ks][2], A[ks][3]);
      ldsm4t(ldB + ks * 8 * KREC, B[ks][0], B[ks][1], B[ks][2], B[ks][3]);
    }
  }
  kgen_mma(acc, A, B, csrc);
#pragma unroll
  for (int q = 0; q < 4; q++)
#pragma unroll
    for (int nt = 0; nt < 3; nt++) {
      const float* a = acc + 12 * (q >> 1) + 4 * nt + 2 * (q & 1);
      sts64f(stg + (q * 3 + nt) * 256 + lane * 8, a[0] * sc, a[1] * sc);
    }
  if (lane == 0) sts32f(stg + 3072, sc);
}

__device__ __forceinline__ void tput(uint32_t tbl, int X, uint32_t h) {
  sts16(tbl + 2 * (1296 - X), (uint16_t)h);
  sts16(tbl + TBL_C1 + 2 * (1297 - X), (uint16_t)h);
}
__device__ __forceinline__ void ktab_build(uint32_t src, bool four, int q, uint32_t tbl, int lane) {
  const int tq = lane & 3, r = 8 * q + (lane >> 3) + ((lane >> 2) & 1) * 4;
  float v[6];
  const float2 dd = lds64f(tbl + TBL_SC + 8);
  float sc = fmaxf(fmaxf(lds32f(src + 3072), lds32f(src + 3072 + KSTG)), pow2_floor(fabsf(dd.y) * (1.f / 4096.f)));
  if (four) sc = fmaxf(sc, fmaxf(lds32f(src + 3072 + 2 * KSTG), lds32f(src + 3072 + 3 * KSTG)));
  const float inv = rcpf_(sc);
  src += q * 768 + lane * 8;
#pragma unroll
  for (int nt = 0; nt < 3; nt++) {
    const float2 a = lds64f(src + nt * 256), c = lds64f(src + nt * 256 + KSTG);
    v[2 * nt] = a.x + c.x; v[2 * nt + 1] = a.y + c.y;
  }
  if (four) {
#pragma unroll
    for (int nt = 0; nt < 3; nt++) {
      const float2 a = lds64f(src + nt * 256 + 2 * KSTG), c = lds64f(src + nt * 256 + 3 * KSTG);
      v[2 * nt] += a.x + c.x; v[2 * nt + 1] += a.y + c.y;
    }
  }
  const bool first = (r == 0);
  if (first && tq == 0) { v[0] += dd.y; sts64f(tbl + TBL_SC, v[4] * inv, dd.x * sc); }
  const uint32_t h0 = pack_h2(v[0] * inv, v[1] * inv), h1 = pack_h2(v[2] * inv, v[3] * inv), h2 = pack_h2(v[4] * inv, v[5] * inv);
  tput(tbl, 64 + 8 * r + tq, h0);
  tput(tbl, 68 + 8 * r + tq, h0 >> 16);
  const bool lo = tq < 2;
  const int k2 = 32 * (tq - 2) + r;
  const bool sp = first && tq == 2;
  const int Xa = lo ? 320 + 8 * r + 2 * tq : (sp ? 576 : 911 + k2), Xb = lo ? Xa + 4 : 720 + k2;
  tput(tbl, Xa, h1);
  tput(tbl, Xb, h1 >> 16);
  if (tq == 0 || sp) {
    tput(tbl, Xa + 1, h1);
    if (Xa != 320) tput(tbl, Xa - 1, h1);
    const uint32_t hb = sp ? h1 : h1 >> 16, hc = sp ? h2 : h1 >> 16;
    tput(tbl, sp ? 578 : Xb + 1, hb);
    tput(tbl, sp ? 1295 : Xb - 1, hc);
  }
  if (lo) {
    const int X3 = ((r & 1) ? 1104 : 1231) + 32 * tq + (r >> 1);
    tput(tbl, X3 == 1231 ? 975 : X3, h2);
    tput(tbl, X3 + 16, h2 >> 16);
  }
}

__device__ __forceinline__ void sig_windows(uint32_t sig, int t) {
  uint32_t U[20];
#pragma unroll
  for (int c = 0; c < 5; c++) {
    const int kap = 2 * t - 3 + c + 72;
    const uint4 v = lds128(sig + SIG_U + (kap & 7) * U_LBO + (kap >> 3) * 16);
    U[4 * c] = v.x; U[4 * c + 1] = v.y; U[4 * c + 2] = v.z; U[4 * c + 3] = v.w;
  }
  uint32_t O[19], A2[17], A4[17], V2[8], V5[8];
#pragma unroll
  for (int i = 3; i < 19; i++) O[i] = __byte_perm(U[i - 1], U[i], 0x5432);
#pragma unroll
  for (int i = 3; i < 17; i++) A2[i] = hadd2u(U[i], O[i]);
#pragma unroll
  for (int i = 4; i < 17; i++) A4[i] = hadd2u(A2[i], A2[i - 1]);
#pragma unroll
  for (int k = 0; k < 8; k++) { V2[k] = hadd2u(O[11 + k], U[10 + k]); V5[k] = hadd2u(A4[9 + k], U[7 + k]); }
#pragma unroll
  for (int h = 0; h < 2; h++) {
    sts128(sig + SIG_V3 + t * 32 + h * 16, hadd2u(V2[4 * h], O[10 + 4 * h]), hadd2u(V2[4 * h + 1], O[11 + 4 * h]),
           hadd2u(V2[4 * h + 2], O[12 + 4 * h]), hadd2u(V2[4 * h + 3], O[13 + 4 * h]));
    sts128(sig + SIG_V5 + t * 32 + h * 16, V5[4 * h], V5[4 * h + 1], V5[4 * h + 2], V5[4 * h + 3]);
  }
  if (t < 64) {
    uint32_t V7[8], V9[8];
#pragma unroll
    for (int k = 0; k < 8; k++) {
      V7[k] = hadd2u(V5[k], hadd2u(O[10 + k], O[7 + k]));
      V9[k] = hadd2u(hadd2u(A4[6 + k], A4[4 + k]), U[2 + k]);
    }
#pragma unroll
    for (int h = 0; h < 2; h++) {
      sts128(sig + SIG_V7 + h * 1024 + t * 16, V7[4 * h], V7[4 * h + 1], V7[4 * h + 2], V7[4 * h + 3]);
      sts128(sig + SIG_V9 + h * 1024 + t * 16, V9[4 * h], V9[4 * h + 1], V9[4 * h + 2], V9[4 * h + 3]);
      sts128(sig + SIG_V2 + h * 1024 + t * 16, V2[4 * h], V2[4 * h + 1], V2[4 * h + 2], V2[4 * h + 3]);
    }
  }
}

__device__ __forceinline__ void conv_channel(uint32_t tbl, uint32_t sig, uint32_t y2b, uint32_t y3b, float k1024,
                                             int w, int lane, int barid, float* res) {
  const int g = lane >> 2, tq = lane & 3;
  const uint32_t tb = tbl + ((g & 1) ? TBL_C1 + 2 : 0) + 2 * (1296 - (g - 2 * tq)) - 32 * w + 112;
  float a2[12], a3[8];
#pragma unroll
  for (int i = 0; i < 16; i++) res[i] = 0.f;
#pragma unroll
  for (int i = 0; i < 12; i++) a2[i] = 0.f;
#pragma unroll
  for (int q = 0; q < 4; q++) {
    const float2 f = h2f(lds32(sig + SIG_V2 + (q >> 1) * 1024 + (16 * w + 8 * (q & 1) + g) * 16 + tq * 4));
    a3[2 * q] = k1024 * f.x;
    a3[2 * q + 1] = k1024 * f.y;
  }
  const uint32_t sigu = __shfl_sync(0xffffffffu, opaque(sig), 0);
  const uint64_t dU = mkdesc(sigu + SIG_U, U_LBO, 128, 0);
  const uint64_t dV = mkdesc(sigu, 128, 1024, 0);
  fence_regs<16>(res); fence_regs<12>(a2); fence_regs<8>(a3);
  constexpr int LB = 2 * U_LBO / 16;
  uint32_t Rd[43], R2[22], R3[12];
  uint32_t td = tb - 128, t2 = tb - 1440, t3 = tb - 2208;
  uint64_t dd = dU + 9, d2 = dV + (SIG_V3 + 768) / 16, d3 = dV + (SIG_V7 + 768) / 16;
  auto load_group = [&](int gi) {
#pragma unroll
    for (int i = 1; i < 5; i++) Rd[4 * gi + i] = lds32(td - 16 * (4 * gi + i));
    const int e = gi >> 3;
    if ((gi & 7) == 0) { R2[2 * gi + e] = lds32(t2 - 384 * e); R3[gi + e] = lds32(t3 - 256 * e); }
    R2[2 * gi + e + 1] = lds32(t2 - 384 * e - 16 * (2 * (gi & 7) + 1));
    R2[2 * gi + e + 2] = lds32(t2 - 384 * e - 16 * (2 * (gi & 7) + 2));
    if (!(gi & 1)) {
      R3[gi + e + 1] = lds32(t3 - 256 * e - 16 * ((gi & 7) + 1));
      R3[gi + e + 2] = lds32(t3 - 256 * e - 16 * ((gi & 7) + 2));
    }
  };
  auto dense = [&](int n) {
    wg_rs_f16_n32k(res, Rd[2 * n + 1], Rd[2 * n + 2], Rd[2 * n], Rd[2 * n + 1], dd + ((3 - (n & 3)) * LB + 8 - (n >> 2)) - 8, 1);
  };
  Rd[0] = lds32(td);
  load_group(0);
  load_group(1);
#pragma unroll 1
  for (int sg = 0; sg < 2; sg++) {
#pragma unroll
    for (int gi = 0; gi < 8; gi++) {
      wg_fence();
      dense(2 * gi);
      wg_rs_f16_n24t(a2, R2[2 * gi + 1], R2[2 * gi + 2], R2[2 * gi], R2[2 * gi + 1], d2 - (16 * (gi & 3) + 64 * (gi >> 2)), 1);
      dense(2 * gi + 1);
      if (!(gi & 1)) wg_rs_f16_n16t(a3, R3[gi + 1], R3[gi + 2], R3[gi], R3[gi + 1], d3 - 8 * gi, 1);
      wg_commit();
      wg_wait<1>();
      load_group(gi + 2);
    }
#pragma unroll
    for (int i = 0; i < 9; i++) Rd[i] = Rd[32 + i];
#pragma unroll
    for (int i = 0; i < 5; i++) R2[i] = R2[17 + i];
#pragma unroll
    for (int i = 0; i < 3; i++) R3[i] = R3[9 + i];
    td -= 512; t2 -= 384; t3 -= 256;
    dd -= 4; d2 += 256; d3 += 128;
  }
  Rd[9] = lds32(td - 144); Rd[10] = lds32(td - 160);
  wg_fence();
#pragma unroll
  for (int n = 0; n < 5; n++) dense(n);
  wg_commit();
  wg_wait<1>();
  fence_regs<12>(a2); fence_regs<8>(a3);
  bar_sync(barid, 128);
  {
    const uint32_t o2 = y2b + (136 * w + 8 * g + 2 * tq) * 4, o3 = y3b + (272 * w + 16 * g + 2 * tq) * 4;
#pragma unroll
    for (int q = 0; q < 6; q++) sts64f(o2 + (544 * (q >> 1) + 64 * (q & 1)) * 4, a2[2 * q], a2[2 * q + 1]);
#pragma unroll
    for (int q = 0; q < 4; q++) sts64f(o3 + (8 * (q >> 1) + 136 * (q & 1)) * 4, a3[2 * q], a3[2 * q + 1]);
  }
  bar_sync(barid, 128);
  const uint32_t go = (136 * tq + 16 * w + g) * 4;
  float ex[12];
#pragma unroll
  for (int i = 0; i < 12; i++) {
    const int o = 544 * (i >> 2) + 64 * (i & 1) + 8 * ((i >> 1) & 1);
    ex[i] = lds32f(y2b + go + o * 4);
    if (i >= 4) ex[i] += lds32f(y3b + go + (o - 544) * 4);
  }
  wg_wait<0>();
  fence_regs<16>(res);
#pragma unroll
  for (int i = 0; i < 12; i++) res[4 + i] += ex[i];
}

__device__ __forceinline__ void red16x2(float& a, float& c) {
#pragma unroll
  for (int o = 1; o < 16; o <<= 1) { a += __shfl_xor_sync(0xffffffffu, a, o); c += __shfl_xor_sync(0xffffffffu, c, o); }
}
__device__ __forceinline__ void ln_rows(uint32_t* u, uint32_t term, uint32_t stg_row, int lane) {
  const int j = lane & 15;
  const float piv = __shfl_sync(0xffffffffu, bf_lo(u[0]), lane & 16);
  float s0 = 0.f, s1 = 0.f, q0 = 0.f, q1 = 0.f;
#pragma unroll
  for (int i = 0; i < 14; i++) {
    const float a = bf_lo(u[i]) - piv, c = bf_hi(u[i]) - piv;
    s0 += a; s1 += c; q0 = fmaf(a, a, q0); q1 = fmaf(c, c, q1);
  }
  float s = s0 + s1, q = q0 + q1;
  red16x2(s, q);
  s *= (1.f / D_); q *= (1.f / D_);
  const __nv_bfloat16 m1b = __float2bfloat16_rn(s + piv);
  const __nv_bfloat162 m1v = __halves2bfloat162(m1b, m1b);
  const float den = rbf(sqrtf_(rbf(rbf(fmaxf(fmaf(-s, s, q), 0.f)) + 1e-5f)));
  const float rden = rcpf_(den);
  s0 = s1 = q0 = q1 = 0.f;
#pragma unroll
  for (int i = 0; i < 14; i++) {
    const __nv_bfloat162 cv = __hsub2(*reinterpret_cast<__nv_bfloat162*>(&u[i]), m1v);
    const uint32_t c = *reinterpret_cast<const uint32_t*>(&cv);
    const uint32_t n = pack_bf2(bf_lo(c) * rden, bf_hi(c) * rden);
    const float a = bf_lo(n), e = bf_hi(n);
    s0 += a; s1 += e; q0 = fmaf(a, a, q0); q1 = fmaf(e, e, q1);
    u[i] = pack_h2(a, e);
  }
#pragma unroll
  for (int i = 0; i < 7; i++)
    asm volatile("st.shared.v2.b32 [%0], {%1,%2};" ::"r"(stg_row + (j + 16 * i) * 8), "r"(u[2 * i]), "r"(u[2 * i + 1]) : "memory");
  s = s0 + s1; q = q0 + q1;
  red16x2(s, q);
  s *= (1.f / D_); q *= (1.f / D_);
  const float den2 = rbf(sqrtf_(rbf(rbf(fmaxf(fmaf(-s, s, q), 0.f)) + 1e-5f)));
  if (j == 0) {
    const float ir = den * den2, mu = fmaf(rbf(s), den, __bfloat162float(m1b));
    const float ih = rbf(ir), mh = rbf(mu);
    const uint32_t mm = pack_bf2(mh, mh);
    sts128(term, pack_bf2(mu - mh, ih), mm, pack_bf2(mu - mh, ir - ih), mm);
  }
}

__device__ __forceinline__ void poll_tag(const unsigned* p, uint32_t tag) {
#pragma unroll 1
  for (int it = 0; it < 4096; it++) {
    if (!((ld_relaxed1(p) ^ tag) & 1)) break;
    __nanosleep(32);
  }
}
__device__ __forceinline__ bool last_release(uint32_t cnt) {
  unsigned old;
  asm volatile("atom.relaxed.cta.shared.inc.u32 %0, [%1], 7;" : "=r"(old) : "r"(cnt) : "memory");
  return old == 7;
}
__device__ __forceinline__ int mod7(int v) { return v >= 7 ? v - 7 : v; }

#define IDS const int tid = opaque(tid0), lane = tid & 31, t = tid & 127, wg = tid >> 7, w = (tid >> 5) & 3; \
            (void)lane; (void)t; (void)wg; (void)w;

__global__ void __launch_bounds__(384, 1)
fused_kernel(const Params p, const __grid_constant__ CUtensorMap tm_x, const __grid_constant__ CUtensorMap tm_w1,
             const __grid_constant__ CUtensorMap tm_w2, const __grid_constant__ CUtensorMap tm_out) {
  const uint32_t sb = smem_u32(smem_raw);
  const uint32_t ms = sb + OFF_M;
  const uint32_t bar0 = ms + M_BAR;
  const int tid0 = threadIdx.x;
  const int b = blockIdx.x;
  const bool is_ssm = b >= NMLP;
  const int G = b / NRK, rk = b - G * NRK;
  const int kc0 = (G + rk) % 7;
  TSINIT();
  TSTAMP(0);
  {
    IDS
    TSTAMP(28);
    uint4 ld[7];
    KgIn kin;
    unsigned ep = 0;
    uint32_t b1w;
    const int rl = 2 * (tid >> 5) + (lane >> 4);
    {
      const int d = is_ssm ? 2 * (112 + 3 * (b - NMLP) + wg) + (w >> 1) : (wg < 2 ? 2 * b + wg : 336 + b);
      const int off = d * NST + 64 * (is_ssm ? 2 * (w & 1) : w) + 2 * lane;
      const __nv_bfloat16* P[10] = {p.a_re + off, p.a_im + off, p.b_re + off, p.b_im + off, p.c_re + off, p.c_im + off,
                                    p.log_dt + (d & ~1), p.dskip + (d & ~1), p.b1 + 64 * (is_ssm ? 0 : b >> 2) + (t & 62),
                                    wg < 2 ? p.x + (size_t)(16 * (b & 127) + rl) * D_ + 4 * (lane & 15)
                                           : p.w1 + (size_t)(112 * (b & 3) + 4 * w + (lane & 3)) * F_ + 64 * (is_ssm ? 0 : b >> 2) + 8 * (lane >> 2)};
      const unsigned* pe = &p.s->epoch;
      asm volatile("" : "+l"(P[0]), "+l"(P[1]), "+l"(P[2]), "+l"(P[3]), "+l"(P[4]), "+l"(P[5]), "+l"(P[6]), "+l"(P[7]), "+l"(P[8]), "+l"(P[9]), "+l"(pe));
#pragma unroll
      for (int i = 0; i < 6; i++) kin.cur[i] = ldg32(P[i], 0);
      kin.ldt = ldg32(P[6], 0); kin.dk = ldg32(P[7], 0); b1w = ldg32(P[8], 0);
      if (tid == 256 + 32) ep = ld_relaxed1(pe);
#pragma unroll
      for (int i = 0; i < 6; i++) kin.nxt[i] = 0u;
      if (is_ssm) {
#pragma unroll
        for (int i = 0; i < 6; i++) kin.nxt[i] = ldg32(P[i], 128);
      }
      if (wg < 2) {
#pragma unroll
        for (int i = 0; i < 7; i++) asm volatile("ld.global.nc.v2.b32 {%0,%1}, [%2];" : "=r"(ld[i].x), "=r"(ld[i].y) : "l"(P[9] + 64 * i));
      } else {
#pragma unroll
        for (int i = 0; i < 7; i++)
          asm volatile("ld.global.nc.v4.b32 {%0,%1,%2,%3}, [%4];" : "=r"(ld[i].x), "=r"(ld[i].y), "=r"(ld[i].z), "=r"(ld[i].w) : "l"(P[9] + (size_t)i * 16 * F_));
      }
      asm volatile("" :: "l"(P[0]), "l"(P[1]), "l"(P[2]), "l"(P[3]), "l"(P[4]), "l"(P[5]), "l"(P[6]), "l"(P[7]), "l"(P[8]), "l"(P[9]), "l"(pe));
      kin.odd = d & 1;
    }
    const uint32_t tbl = is_ssm ? sb + (4 * wg + (w >> 1)) * TBL : sb + OFF_T + wg * TBL;
#pragma unroll 1
    for (int i = is_ssm ? t & 63 : t; i < TBL_SC / 16; i += is_ssm ? 64 : 128) sts128(tbl + i * 16, 0u, 0u, 0u, 0u);
    const uint32_t lns = is_ssm ? sb + S_WORK + 2 * S_WGB + 4 * KSTG : sb + OFF_X + 2 * 16384;
    const int wi = __shfl_sync(0xffffffffu, tid >> 5, 0);
    if (wi < 4 && lane == 0) {
      if (wi < 3) mbar_init(bar0 + 8 * wi, 1);
      asm volatile("fence.mbarrier_init.release.cluster;" ::: "memory");
      if (!is_ssm) asm volatile("prefetch.tensormap [%0];" ::"l"(wi == 0 ? &tm_x : wi == 1 ? &tm_w1 : wi == 2 ? &tm_w2 : &tm_out) : "memory");
    }
    __syncwarp();
    if (wi == 4 && lane < 16) asm volatile("st.shared.b32 [%0], 0;" ::"r"(ms + M_REL + 4 * lane) : "memory");
    TSTAMP(31);
    auto mid = [&]() {
    TSTAMP(30);
    if (wg < 2) {
      uint32_t u[14];
#pragma unroll
      for (int i = 0; i < 7; i++) { u[2 * i] = ld[i].x; u[2 * i + 1] = ld[i].y; }
      ln_rows(u, ms + M_LT + rl * 16, lns + ((rl & 1) | ((rl >> 2) << 1) | ((rl & 2) << 2)) * 912, lane);
      bar_arrive(7, 384);
    } else {
      float cs[4] = {0.f, 0.f, 0.f, 0.f};
      const int g = lane >> 2;
      const uint32_t one = (g & 1) ? 0x3f800000u : 0x00003f80u;
      const uint32_t s0 = (g >> 1) == 0 ? one : 0u, s1 = (g >> 1) == 1 ? one : 0u, s2 = (g >> 1) == 2 ? one : 0u, s3 = (g >> 1) == 3 ? one : 0u;
#pragma unroll
      for (int i = 0; i < 7; i++) {
        mma_bf16(cs, s0, 0u, s1, 0u, ld[i].x, ld[i].y);
        mma_bf16(cs, s2, 0u, s3, 0u, ld[i].z, ld[i].w);
      }
      sts32f(ms + M_CSR + (w * 64 + (lane & 3) * 16 + g) * 4, cs[0]);
      sts32f(ms + M_CSR + (w * 64 + (lane & 3) * 16 + g + 8) * 4, cs[1]);
      if (t == 32) { asm volatile("st.shared.b32 [%0], %1;" ::"r"(ms + M_EP), "r"(ep + 1) : "memory"); red_relaxed(&p.s->cntA); }
      bar_sync(7, 384);
      const uint32_t la = lns + (lane & 15) * 912 + (lane >> 4) * 16 + w * 224;
      uint2* dst = (uint2*)(p.s->xnT + (size_t)(56 * w + (lane >> 3)) * 512 + 4 * b) + (lane & 7);
      uint32_t r[28];
#pragma unroll
      for (int k = 0; k < 7; k++) ldsm4t(la + k * 32, r[4 * k], r[4 * k + 1], r[4 * k + 2], r[4 * k + 3]);
      const uint32_t tag = lds32(ms + M_EP) & 1;
      fence_async();
      bar_sync(6, 128);
      if (b < 128) {
#pragma unroll
        for (int k = 0; k < 14; k++) st_relaxed2(dst + k * 4096, (r[2 * k] & ~1u) | tag, (r[2 * k + 1] & ~1u) | tag);
      }
      if (t < 64 && !is_ssm) {
        const uint32_t a = ms + M_CSR + t * 4;
        const float c = -((lds32f(a) + lds32f(a + 256)) + (lds32f(a + 512) + lds32f(a + 768)));
        const float ch = rbf(c);
        uint2* dx = (uint2*)(p.s->bx + (b >> 4) * 512 + ((b >> 1) & 1) * 256 + ((b >> 2) & 3) * 64 + t) + (b & 1);
        const float b1v = (b & 2) ? 0.f : ((t & 1) ? bf_hi(b1w) : bf_lo(b1w));
        asm volatile("{.reg .b64 a; mov.b64 a, {%1,%2}; st.relaxed.gpu.global.b64 [%0], a;}"
                     ::"l"(dx), "r"(pack_bf2(ch, b1v)), "r"((pack_bf2(c - ch, ch) & ~1u) | tag) : "memory");
      }
      if (t >= 64 && t < 80 && b < 128) {
        const uint4 a = lds128(ms + M_LT + (t - 64) * 16);
        st_b128(p.s->ax + 16 * b + t - 64, tag, a.x, a.y, a.z, a.w);
      }
    }
    if ((wi == 0 || wi == 1 || wi == 10) && lane == 0 && !is_ssm) {
      const int i = wi & 3, kc = mod7(kc0 + i);
      mbar_expect(bar0 + 8 * i, 49152);
      tma_2d(sb + OFF_X + i * 16384, &tm_x, 64 * kc, 128 * G, bar0 + 8 * i);
      tma_3d(sb + OFF_W + i * 32768, &tm_w1, 0, 64 * kc, 4 * rk, bar0 + 8 * i);
    }
    __syncwarp();
    TSTAMP(29);
    };
    const uint32_t stg = is_ssm ? sb + S_WORK + wg * S_WGB + w * KSTG : sb + (wg < 2 ? OFF_A + 4 * wg * KSTG : OFF_B) + w * KSTG;
    kgen_warp(kin, is_ssm ? 2 : 1, stg, tbl, lane, mid);
  }
  TSTAMP(1);
  uint4 v[4], tv[5];
  {
    IDS
    bar_sync(4 + wg, 128);
    if (!is_ssm && wg == 2) {
#pragma unroll
      for (int q = 0; q < 4; q++) tv[q] = ld_2x64(p.s->bx + 512 * rk + q * 128 + t);
      tv[4] = ld_b128(p.s->ax + 128 * G + t);
    }
    if (is_ssm || wg == 2) {
      const uint4* src = p.s->xnT + (size_t)(is_ssm ? 112 + 3 * (b - NMLP) + wg : b) * 512 + t;
#pragma unroll
      for (int q = 0; q < 4; q++) v[q] = ld_relaxed4(src + q * 128);
    }
#pragma unroll 1
    for (int c = is_ssm ? 1 : 0; c >= 0; c--) {
      const uint32_t src = is_ssm ? sb + S_WORK + wg * S_WGB + 2 * c * KSTG : sb + (wg < 2 ? OFF_A + 4 * wg * KSTG : OFF_B);
      ktab_build(src, !is_ssm, w, is_ssm ? sb + (4 * wg + c) * TBL : sb + OFF_T + wg * TBL, lane);
    }
    fence_async();
  }
  TSTAMP(2);
  __syncthreads();

  if (is_ssm || __shfl_sync(0xffffffffu, tid0 >> 7, 0) == 2) {
    asm volatile("setmaxnreg.dec.sync.aligned.u32 136;");
    if (!is_ssm) {
      IDS
      const unsigned ep1 = lds32(ms + M_EP);
#pragma unroll 1
      for (int it = 0; it < 16 * RETRY_MAX; it++) {
        uint32_t bad = tv[4].x ^ ep1;
#pragma unroll
        for (int q = 0; q < 4; q++) bad |= (tv[q].y ^ ep1) | (tv[q].w ^ ep1);
        if (!__any_sync(0xffffffffu, bad & 1)) break;
        __nanosleep(200);
#pragma unroll
        for (int q = 0; q < 4; q++) tv[q] = ld_2x64(p.s->bx + 512 * rk + q * 128 + t);
        tv[4] = ld_b128(p.s->ax + 128 * G + t);
      }
#pragma unroll
      for (int q = 0; q < 5; q++) sts128(sb + OFF_B + (q < 4 ? B_BX + q * 2048 : B_AX) + t * 16, tv[q].x, tv[q].y, tv[q].z, tv[q].w);
      if (t < 64) sts32f(ms + M_CSR + t * 4, 0.5f * __bfloat162float(p.b2[64 * rk + t]));
      fence_async();
      bar_arrive(1, 384);
      if (t == 96) { bulk_s2g(p.s->tbl + b * (TBL / 16), sb + OFF_T + 2 * TBL, TBL); bulk_commit(); }
      if (t == 64)
        asm volatile("cp.async.bulk.prefetch.L2.global [%0], %1;" ::"l"(p.w2 + (size_t)(256 * rk + 16 * G) * D_), "r"(16 * D_ * 2) : "memory");
    }
#pragma unroll 1
    for (int pi = opaque(0); ; pi++) {
      {
        IDS
        const unsigned ep1 = lds32(ms + M_EP);
        const int pair = !is_ssm ? b : (pi == 0 ? 112 + 3 * (b - NMLP) : (b < NMLP + 12 ? 172 + 3 * (b - NMLP) : 184 + 2 * (b - NMLP))) + wg;
        const uint32_t work = is_ssm ? sb + S_WORK + wg * S_WGB : sb + OFF_A;
        const uint32_t z = work + SIG_V3 - 1024 + (t >> 6) * 4096 + (t & 63) * 16;
        sts128(z, 0u, 0u, 0u, 0u); sts128(z + SIG, 0u, 0u, 0u, 0u);
        if (t < 72) {
          const uint32_t zu = work + SIG_U + (t & 7) * U_LBO + (t >> 3) * 16;
          sts128(zu, 0u, 0u, 0u, 0u); sts128(zu + SIG, 0u, 0u, 0u, 0u);
        }
        const uint4* src = p.s->xnT + (size_t)pair * 512 + t;
#pragma unroll 1
        for (int it = 0; it < RETRY_MAX; it++) {
          uint32_t bad = 0;
#pragma unroll
          for (int q = 0; q < 4; q++) bad |= (((v[q].x ^ ep1) | (v[q].y ^ ep1) | (v[q].z ^ ep1) | (v[q].w ^ ep1)) & 1) << q;
          const unsigned m = __ballot_sync(0xffffffffu, bad);
          if (!m) break;
          if (lane == __ffs(m) - 1) poll_tag((const unsigned*)(src + (__ffs(bad) - 1) * 128) + 3, ep1);
          __syncwarp();
#pragma unroll
          for (int q = 0; q < 4; q++) v[q] = ld_relaxed4(src + q * 128);
        }
        TSTAMP(5);
        const uint32_t a = work + ((t >> 1) & 1) * SIG + SIG_U + (2 * ((t >> 2) & 3) + (t & 1)) * U_LBO + ((t >> 4) + 9) * 16;
#pragma unroll
        for (int q = 0; q < 4; q++) sts128(a + q * 128, v[q].x & ~1u, v[q].y & ~1u, v[q].z & ~1u, v[q].w & ~1u);
        bar_sync(4 + wg, 128);
#pragma unroll 1
        for (int k = w; k < 6; k += 4) sig_windows(work + (k & 1) * SIG, (k >> 1) * 32 + lane);
        fence_async();
        if (t == 96 && !is_ssm) { bulk_wait0(); red_release(&p.s->cntT); }
        if (pi == 1) mbar_wait(bar0 + 8 * wg, 0);
        TSTAMP(6);
        bar_sync(is_ssm ? 4 + wg : 3, is_ssm ? 128 : 384);
        TSTAMP(7);
      }
      uint32_t keep[8];
      float res[16];
#pragma unroll 1
      for (int c = 0; c < 2; c++) {
        IDS
        const int wgu = __shfl_sync(0xffffffffu, wg, 0);
        const uint32_t work = is_ssm ? sb + S_WORK + wgu * S_WGB : sb + OFF_A;
        const uint32_t tbl = (is_ssm ? sb + (4 * wgu + 2 * pi) * TBL : sb + OFF_T) + c * TBL;
        conv_channel(tbl, work + c * SIG, is_ssm ? work + 2 * SIG + Y3B : sb + OFF_B, work + 2 * SIG, lds32f(tbl + TBL_SC), w, lane, 4 + wgu, res);
        TSTAMP(16 + 2 * pi + c);
        const float os = lds32f(tbl + TBL_SC + 4);
        if (c == 0) {
#pragma unroll
          for (int i = 0; i < 8; i++) keep[i] = pack_bf2(res[2 * i] * os, res[2 * i + 1] * os);
          if (is_ssm && pi == 0 && t == 96 && (b < NMLP + 12 || wg < 2)) {
            wait_count(&p.s->cntT, lds32(ms + M_EP) * NMLP);
            asm volatile("fence.proxy.async;" ::: "memory");
            mbar_expect(bar0 + 8 * wg, 2 * TBL);
            bulk_g2s(sb + (4 * wg + 2) * TBL, p.s->tbl + (2 * ((b < NMLP + 12 ? 172 + 3 * (b - NMLP) : 184 + 2 * (b - NMLP)) + wg) - 336) * (TBL / 16),
                     2 * TBL, bar0 + 8 * wg);
          }
          __syncwarp();
        } else {
          const int pair = !is_ssm ? b : (pi == 0 ? 112 + 3 * (b - NMLP) : (b < NMLP + 12 ? 172 + 3 * (b - NMLP) : 184 + 2 * (b - NMLP))) + wg;
          uint4* dst = p.s->s2 + ((size_t)(lane & 3) * 224 + pair) * 32 + w * 8 + (lane >> 2);
          const uint32_t tag = (lds32(ms + M_EP) & 1) * 0x10001u;
#pragma unroll
          for (int nt = 0; nt < 4; nt++) {
            const uint32_t n0 = pack_bf2(res[4 * nt] * os, res[4 * nt + 1] * os), n1 = pack_bf2(res[4 * nt + 2] * os, res[4 * nt + 3] * os);
            const uint32_t k0 = (keep[2 * nt] & 0xfffefffeu) | tag;
            asm volatile("{.reg .b64 a, c; mov.b64 a, {%1,%2}; mov.b64 c, {%3,%4}; st.relaxed.gpu.global.v2.b64 [%0], {a, c};}"
                         ::"l"(dst + nt * 4 * 224 * 32), "r"(__byte_perm(k0, n0, 0x5410)), "r"(__byte_perm(keep[2 * nt + 1], n1, 0x5410)),
                         "r"(__byte_perm(k0, n0, 0x7632)), "r"(__byte_perm(keep[2 * nt + 1], n1, 0x7632)) : "memory");
          }
        }
      }
      TSTAMP(8 + pi);
      {
        IDS
        if (pi == 1 || !is_ssm || (b >= NMLP + 12 && wg == 2)) break;
        const uint4* src = p.s->xnT + (size_t)((b < NMLP + 12 ? 172 + 3 * (b - NMLP) : 184 + 2 * (b - NMLP)) + wg) * 512 + t;
#pragma unroll
        for (int q = 0; q < 4; q++) v[q] = ld_relaxed4(src + q * 128);
      }
    }
    if (b == 0 && tid0 == 256) {
      const unsigned ep1 = lds32(ms + M_EP);
      wait_count(&p.s->cntA, ep1 * NCTA);
      *(volatile unsigned*)&p.s->epoch = ep1;
    }
    TSDUMP();
  } else {
    bar_arrive(1, 384);
    asm volatile("setmaxnreg.inc.sync.aligned.u32 192;");
    bar_sync(7, 384);
    uint32_t H[64];
    {
      float acc[128];
      float p0, q0, p1, q1;
      {
        IDS
        const int wgu = __shfl_sync(0xffffffffu, wg, 0);
        int sl = 0;
#pragma unroll 1
        for (int s = 0; s < 7; s++) {
          mbar_wait(bar0 + 8 * sl, (s >= 3 && s < 6));
          TSTAMP(17 + s);
          const uint64_t da = mkdesc(sb + OFF_X + sl * 16384 + wgu * 8192, 16, 1024, 1);
          const uint64_t db = mkdesc(sb + OFF_W + sl * 32768, 8192, 1024, 1);
          wg_fence();
#pragma unroll
          for (int k = 0; k < 4; k++) wg_ss_bf16_n256(acc, da + 2 * k, db + 128 * k, (s | k) != 0);
          wg_commit();
          wg_wait<1>();
          const int pl = sl == 0 ? 2 : sl - 1;
          sl = sl == 2 ? 0 : sl + 1;
          if (s > 0 && lane == 0 && last_release(ms + M_REL + 4 * s)) {
            mbar_expect(bar0 + 8 * pl, s == 5 ? 32768 : 49152);
            if (s < 5) tma_3d(sb + OFF_W + pl * 32768, &tm_w1, 0, 64 * mod7(kc0 + s + 2), 4 * rk, bar0 + 8 * pl);
            else tma_2d(sb + OFF_W + pl * 32768, &tm_w2, 64 * mod7(rk + s - 4), 256 * rk, bar0 + 8 * pl);
            if (s != 5) tma_2d(sb + OFF_X + pl * 16384, &tm_x, 64 * (s < 5 ? mod7(kc0 + s + 2) : rk), 128 * G, bar0 + 8 * pl);
          }
        }
        TSTAMP(15);
        bar_sync(1, 384);
        wg_fence();
        wg_ss_bf16_n256k(acc, mkdesc(sb + OFF_B + B_AX + wgu * 1024, 0, 128, 0), mkdesc(sb + OFF_B + B_BX, 4096, 128, 0), 1);
        wg_commit();
        wg_wait<1>();
        if (lane == 0 && last_release(ms + M_REL + 4 * 7)) {
          mbar_expect(bar0, 65536);
#pragma unroll 1
          for (int c = 2; c < 4; c++) tma_2d(sb + (c - 2) * OFF_X, &tm_w2, 64 * mod7(rk + 1 + c), 256 * rk, bar0);
        }
        bar_arrive(3, 384);
        const uint32_t ra = sb + OFF_B + B_AX + (16 * (tid >> 5) + (lane >> 2)) * 16;
        const float r0 = rcpf_(bf_hi(lds32(ra)) + bf_hi(lds32(ra + 8))), r1 = rcpf_(bf_hi(lds32(ra + 128)) + bf_hi(lds32(ra + 136)));
        p0 = 0.7978845608028654f * r0; q0 = 0.0356774081363001f * r0 * r0 * r0;
        p1 = 0.7978845608028654f * r1; q1 = 0.0356774081363001f * r1 * r1 * r1;
      }
      wg_wait<0>();
      fence_regs<128>(acc);
      TSTAMP(16);
#pragma unroll 1
      for (int hf = 0; hf < 2; hf++) {
        float th[8];
#pragma unroll
        for (int i = 0; i < 35; i++) {
          if (i < 32) {
            const float pp = (i & 1) ? p1 : p0, qq = (i & 1) ? q1 : q0;
            const float a = acc[2 * i], c = acc[2 * i + 1];
            th[2 * (i & 3)] = tanhf_(a * fmaf(a * a, qq, pp)); th[2 * (i & 3) + 1] = tanhf_(c * fmaf(c * c, qq, pp));
          }
          if (i >= 3) {
            const int j = i - 3;
            asm volatile("{.reg .f32 x, y; fma.rn.f32 x, %0, %5, %0; fma.rn.f32 y, %1, %6, %1; mov.f32 %0, %3; mov.f32 %1, %4;\n"
                         ".reg .b32 h; cvt.rn.bf16x2.f32 h, y, x; mov.b32 %2, h;}"
                         : "+f"(acc[2 * j]), "+f"(acc[2 * j + 1]), "=f"(acc[64 + j])
                         : "f"(acc[64 + 2 * j]), "f"(acc[65 + 2 * j]), "f"(th[2 * (j & 3)]), "f"(th[2 * (j & 3) + 1]));
          }
        }
      }
#pragma unroll
      for (int i = 0; i < 32; i++) { H[i] = __float_as_uint(acc[i]); H[32 + i] = __float_as_uint(acc[64 + i]); }
    }
    TSTAMP(3);
    IDS
    float acc[32], pre[32];
    uint32_t pk[16];
#pragma unroll
    for (int i = 0; i < 32; i++) pre[i] = 0.f;
    const uint32_t tag = lds32(ms + M_EP) & 1;
    const uint4* inbox = p.s->part + (size_t)b * 6 * 1024 + tid;
    auto recv = [&](int slot) {
      const uint4* src = inbox + slot * 1024;
      uint4 v[4];
#pragma unroll 1
      for (int it = 0; it < RETRY_MAX; it++) {
#pragma unroll
        for (int q = 0; q < 4; q++) v[q] = ld_b128(src + q * 256);
        const unsigned m = __ballot_sync(0xffffffffu, ((v[0].x ^ tag) | (v[1].x ^ tag) | (v[2].x ^ tag) | (v[3].x ^ tag)) & 1);
        if (!m) break;
        if (lane == __ffs(m) - 1) poll_tag((const unsigned*)(src + 768), tag);
        __syncwarp();
      }
#pragma unroll
      for (int q = 0; q < 4; q++) {
        const uint32_t u[4] = {v[q].x, v[q].y, v[q].z, v[q].w};
#pragma unroll
        for (int k = 0; k < 4; k++) { pre[8 * q + 2 * k] += bf_lo(u[k]); pre[8 * q + 2 * k + 1] += bf_hi(u[k]); }
      }
    };
#pragma unroll 1
    for (int s = 0; s < 7; s++) {
      if (s != 3) mbar_wait(bar0 + 8 * ((0x0210021u >> (4 * s)) & 3), (0x34 >> s) & 1);
      const uint64_t db = mkdesc(sb + ((0x0213021u >> (4 * s)) & 3) * 32768, 8192, 1024, 1);
      wg_fence();
#pragma unroll
      for (int k = 0; k < 16; k++) wg_rs_bf16_n64(acc, H[4 * k], H[4 * k + 1], H[4 * k + 2], H[4 * k + 3], db + 128 * k, k != 0);
      wg_commit();
      if (s > 0) {
        uint4* dst = p.s->part + ((size_t)(G * 7 + mod7(rk + s)) * 6 + s - 1) * 1024 + tid;
#pragma unroll
        for (int q = 0; q < 4; q++) st_b128(dst + q * 256, tag, pk[4 * q], pk[4 * q + 1], pk[4 * q + 2], pk[4 * q + 3]);
        if (s < 4 && lane == 0 && last_release(ms + M_REL + 4 * (7 + s))) {
          const int sl = (0x0210u >> (4 * s)) & 3;
          mbar_expect(bar0 + 8 * sl, 32768);
          tma_2d(sb + sl * 32768, &tm_w2, 64 * mod7(mod7(rk + 4 + s)), 256 * rk, bar0 + 8 * sl);
        }
        __syncwarp();
      }
      if (s >= 3) recv(s - 3);
      wg_wait<0>();
      fence_regs<32>(acc);
#pragma unroll
      for (int k = 0; k < 16; k++) pk[k] = pack_bf2(acc[2 * k], acc[2 * k + 1]);
      TSTAMP(4 + s);
    }
    {
      const uint2* sp = (const uint2*)(p.s->s2 + ((size_t)G * 224 + 32 * rk + (lane & 3)) * 32 + w * 8 + (lane >> 2)) + wg;
#pragma unroll 1
      for (int it = 0; it < RETRY_MAX; it++) {
#pragma unroll
        for (int i = 0; i < 8; i++)
          asm volatile("{.reg .b64 a; ld.relaxed.gpu.global.b64 a, [%2]; mov.b64 {%0,%1}, a;}"
                       : "=r"(pk[2 * i]), "=r"(pk[2 * i + 1]) : "l"(sp + i * 4 * 64) : "memory");
#pragma unroll 1
        for (int s = it ? 6 : 4; s < 6; s++) recv(s);
        uint32_t bad = 0;
#pragma unroll
        for (int i = 0; i < 8; i++) bad |= ((pk[2 * i] ^ tag) & 1) << i;
        const unsigned m = __ballot_sync(0xffffffffu, bad);
        if (!m) break;
        if (lane == __ffs(m) - 1) poll_tag((const unsigned*)(sp + (__ffs(bad) - 1) * 4 * 64), tag);
        __syncwarp();
      }
    }
    TSTAMP(12);
    const int g = lane >> 2, tq = lane & 3;
    const uint32_t xa = sb + OFF_X + 2 * 16384 + (16 * (tid >> 5) + (lane & 15)) * 128;
    uint32_t xw[16];
#pragma unroll
    for (int q = 0; q < 4; q++) ldsm4(xa + (((2 * q + (lane >> 4)) ^ (lane & 7)) << 4), xw[4 * q], xw[4 * q + 1], xw[4 * q + 2], xw[4 * q + 3]);
    const uint32_t ra = sb + OFF_B + B_AX + (16 * (tid >> 5) + g) * 16;
    const float r0 = 0.25f * rcpf_(bf_hi(lds32(ra)) + bf_hi(lds32(ra + 8))), r1 = 0.25f * rcpf_(bf_hi(lds32(ra + 128)) + bf_hi(lds32(ra + 136)));
#pragma unroll
    for (int i = 0; i < 8; i++) {
      const float2 bb = lds64f(ms + M_CSR + (8 * i + 2 * tq) * 4);
#pragma unroll
      for (int e = 0; e < 2; e++) {
        const int k = 2 * i + e;
        const float h0 = fmaf(acc[2 * k] + pre[2 * k], e ? r1 : r0, bb.x), h1 = fmaf(acc[2 * k + 1] + pre[2 * k + 1], e ? r1 : r0, bb.y);
        const uint32_t gw = pack_bf2(fmaf(h0, tanhf_(h0), h0), fmaf(h1, tanhf_(h1), h1));
        asm("fma.rn.bf16x2 %0, %1, %2, %0;" : "+r"(xw[k]) : "r"(pk[k]), "r"(gw));
      }
    }
#pragma unroll
    for (int q = 0; q < 4; q++) stsm4(xa + (((2 * q + (lane >> 4)) ^ (lane & 7)) << 4), xw[4 * q], xw[4 * q + 1], xw[4 * q + 2], xw[4 * q + 3]);
    fence_async();
    __syncwarp();
    if (lane == 0) {
      tma_store_2d(&tm_out, sb + OFF_X + 2 * 16384 + (tid >> 5) * 2048, 64 * rk, 128 * G + 16 * (tid >> 5));
      bulk_commit();
      bulk_wait0_read();
    }
    TSTAMP(13);
    TSDUMP();
  }
}

typedef CUresult (*EncodeFn)(CUtensorMap*, CUtensorMapDataType, cuuint32_t, void*, const cuuint64_t*, const cuuint64_t*,
                             const cuuint32_t*, const cuuint32_t*, CUtensorMapInterleave, CUtensorMapSwizzle,
                             CUtensorMapL2promotion, CUtensorMapFloatOOBfill);

void make_map(EncodeFn fn, CUtensorMap* m, const void* ptr, int rank, const cuuint64_t* dims, const cuuint64_t* strides, const cuuint32_t* box) {
  const cuuint32_t es[3] = {1, 1, 1};
  fn(m, CU_TENSOR_MAP_DATA_TYPE_BFLOAT16, rank, const_cast<void*>(ptr), dims, strides, box, es, CU_TENSOR_MAP_INTERLEAVE_NONE,
     CU_TENSOR_MAP_SWIZZLE_128B, CU_TENSOR_MAP_L2_PROMOTION_L2_128B, CU_TENSOR_MAP_FLOAT_OOB_FILL_NONE);
}

}

extern "C" void kernel_launch(void* const* d_in, const int* in_sizes, int n_in, void* d_out, int out_size) {
  (void)in_sizes; (void)n_in; (void)out_size;
  void* fnp = nullptr;
  cudaDriverEntryPointQueryResult qr;
  cudaGetDriverEntryPoint("cuTensorMapEncodeTiled", &fnp, cudaEnableDefault, &qr);
  EncodeFn fn = (EncodeFn)fnp;
  Params p;
  p.x = (const __nv_bfloat16*)d_in[0];
  p.a_re = (const __nv_bfloat16*)d_in[1]; p.a_im = (const __nv_bfloat16*)d_in[2];
  p.b_re = (const __nv_bfloat16*)d_in[3]; p.b_im = (const __nv_bfloat16*)d_in[4];
  p.c_re = (const __nv_bfloat16*)d_in[5]; p.c_im = (const __nv_bfloat16*)d_in[6];
  p.log_dt = (const __nv_bfloat16*)d_in[7]; p.dskip = (const __nv_bfloat16*)d_in[8];
  p.w1 = (const __nv_bfloat16*)d_in[10]; p.b1 = (const __nv_bfloat16*)d_in[11];
  p.w2 = (const __nv_bfloat16*)d_in[12]; p.b2 = (const __nv_bfloat16*)d_in[13];
  void* sp = nullptr;
  cudaGetSymbolAddress(&sp, g_scr);
  p.s = (Scratch*)sp;
  CUtensorMap mx, mw1, mw2, mo;
  {
    const cuuint64_t dims[2] = {448, 2048}, str[1] = {896};
    const cuuint32_t box[2] = {64, 128}, boxo[2] = {64, 16};
    make_map(fn, &mx, p.x, 2, dims, str, box);
    make_map(fn, &mo, d_out, 2, dims, str, boxo);
  }
  {
    const cuuint64_t dims[3] = {64, 448, 28}, str[2] = {3584, 128};
    const cuuint32_t box[3] = {64, 64, 4};
    make_map(fn, &mw1, p.w1, 3, dims, str, box);
  }
  {
    const cuuint64_t dims[2] = {448, 1792}, str[1] = {896};
    const cuuint32_t box[2] = {64, 256};
    make_map(fn, &mw2, p.w2, 2, dims, str, box);
  }
  cudaFuncSetAttribute(fused_kernel, cudaFuncAttributeMaxDynamicSharedMemorySize, SMEM_BYTES);
  fused_kernel<<<NCTA, 384, SMEM_BYTES>>>(p, mx, mw1, mw2, mo);
}
```

```cpp
#include <cuda_runtime.h>
#include <cuda_bf16.h>
#include <cuda_fp16.h>
#include <cuda.h>
#include <stdint.h>

namespace {

constexpr int D_ = 448, NST = 256, F_ = 1792;
constexpr int NRK = 7, NMLP = 112, NCTA = 132;
constexpr int SPIN_MAX = 1 << 20, RETRY_MAX = 512;

struct Scratch {
  unsigned cntA, pad0[31], cntT, pad1[31], epoch, pad2[63];
  uint4 ax[2048];
  uint4 bx[7 * 512];
  uint4 tbl[112 * 329];
  uint4 xnT[224 * 512];
  uint4 s2[16 * 224 * 32];
  uint4 part[16 * 7 * 6 * 1024];
};
__device__ Scratch g_scr;
#define TSTAMP(i)
#define TSINIT()
#define TSDUMP()
extern __shared__ __align__(1024) uint8_t smem_raw[];

constexpr int TBL_SC = 5248, TBL = 5264;
constexpr int TBL_C1 = 2624;
constexpr int SIG = 19584;
constexpr int SIG_U = 0, U_LBO = 656, SIG_V3 = 6272, SIG_V5 = 10368, SIG_V7 = 13440, SIG_V9 = 15488, SIG_V2 = 17536;
constexpr int Y2B = 6528, Y3B = 4352;
constexpr int KREC = 160, KSTG = 32 * KREC;
constexpr int OFF_W = 0, OFF_X = 98304, OFF_A = 147456, OFF_B = OFF_A + 8 * KSTG + 2560, OFF_T = OFF_B + 4 * KSTG;
constexpr int OFF_M = OFF_T + 15872;
constexpr int B_AX = Y2B, B_BX = B_AX + 2048;
constexpr int M_BAR = 0, M_REL = 128, M_EP = 192, M_CSR = 256, M_LT = 1280, M_END = 1536;
constexpr int SMEM_BYTES = OFF_M + M_END + 384;
constexpr int S_WORK = 63232, S_WGB = 2 * SIG + Y2B + Y3B;
static_assert(S_WORK + 3 * S_WGB <= OFF_M && SMEM_BYTES <= 232448, "smem");

struct Params {
  const __nv_bfloat16 *x, *a_re, *a_im, *b_re, *b_im, *c_re, *c_im, *log_dt, *dskip, *w1, *b1, *w2, *b2;
  Scratch* s;
};

__device__ __forceinline__ int opaque(int x) { int v; asm volatile("mov.u32 %0, %1;" : "=r"(v) : "r"(x)); return v; }
__device__ __forceinline__ int rd_bid() { int v; asm volatile("mov.u32 %0, %%ctaid.x;" : "=r"(v)); return v; }
__device__ __forceinline__ uint32_t smem_u32(const void* p) { return (uint32_t)__cvta_generic_to_shared(p); }
__device__ __forceinline__ void mbar_init(uint32_t bar, int cnt) { asm volatile("mbarrier.init.shared::cta.b64 [%0], %1;" ::"r"(bar), "r"(cnt)); }
__device__ __forceinline__ void mbar_expect(uint32_t bar, uint32_t bytes) {
  asm volatile("mbarrier.arrive.expect_tx.shared::cta.b64 _, [%0], %1;" ::"r"(bar), "r"(bytes) : "memory");
}
__device__ __forceinline__ void mbar_wait(uint32_t bar, uint32_t parity) {
  uint32_t done = 0;
#pragma unroll 1
  for (int it = 0; it < SPIN_MAX; it++) {
    asm volatile("{.reg .pred p; mbarrier.try_wait.parity.shared::cta.b64 p, [%1], %2; selp.u32 %0,1,0,p;}"
                 : "=r"(done) : "r"(bar), "r"(parity) : "memory");
    if (done) break;
  }
}
__device__ __forceinline__ void tma_2d(uint32_t dst, const CUtensorMap* m, int c0, int c1, uint32_t bar) {
  asm volatile("cp.async.bulk.tensor.2d.shared::cluster.global.mbarrier::complete_tx::bytes [%0], [%1, {%3, %4}], [%2];"
               ::"r"(dst), "l"(m), "r"(bar), "r"(c0), "r"(c1) : "memory");
}
__device__ __forceinline__ void tma_3d(uint32_t dst, const CUtensorMap* m, int c0, int c1, int c2, uint32_t bar) {
  asm volatile("cp.async.bulk.tensor.3d.shared::cluster.global.mbarrier::complete_tx::bytes [%0], [%1, {%3, %4, %5}], [%2];"
               ::"r"(dst), "l"(m), "r"(bar), "r"(c0), "r"(c1), "r"(c2) : "memory");
}
__device__ __forceinline__ void tma_store_2d(const CUtensorMap* m, uint32_t src, int c0, int c1) {
  asm volatile("cp.async.bulk.tensor.2d.global.shared::cta.bulk_group [%0, {%2, %3}], [%1];"
               ::"l"(m), "r"(src), "r"(c0), "r"(c1) : "memory");
}
__device__ __forceinline__ void bulk_s2g(void* dst, uint32_t src, uint32_t bytes) {
  asm volatile("cp.async.bulk.global.shared::cta.bulk_group [%0], [%1], %2;" ::"l"(dst), "r"(src), "r"(bytes) : "memory");
}
__device__ __forceinline__ void bulk_g2s(uint32_t dst, const void* src, uint32_t bytes, uint32_t bar) {
  asm volatile("cp.async.bulk.shared::cluster.global.mbarrier::complete_tx::bytes [%0], [%1], %2, [%3];"
               ::"r"(dst), "l"(src), "r"(bytes), "r"(bar) : "memory");
}
__device__ __forceinline__ void bulk_commit() { asm volatile("cp.async.bulk.commit_group;" ::: "memory"); }
__device__ __forceinline__ void bulk_wait0() { asm volatile("cp.async.bulk.wait_group 0;" ::: "memory"); }
__device__ __forceinline__ void bulk_wait0_read() { asm volatile("cp.async.bulk.wait_group.read 0;" ::: "memory"); }
__device__ __forceinline__ void fence_async() { asm volatile("fence.proxy.async.shared::cta;" ::: "memory"); }
__device__ __forceinline__ void bar_sync(int id, int n) { asm volatile("bar.sync %0, %1;" ::"r"(id), "r"(n) : "memory"); }
__device__ __forceinline__ void bar_arrive(int id, int n) { asm volatile("bar.arrive %0, %1;" ::"r"(id), "r"(n) : "memory"); }
__device__ __forceinline__ void wg_fence() { asm volatile("wgmma.fence.sync.aligned;" ::: "memory"); }
__device__ __forceinline__ void wg_commit() { asm volatile("wgmma.commit_group.sync.aligned;" ::: "memory"); }
template <int N> __device__ __forceinline__ void wg_wait() { asm volatile("wgmma.wait_group.sync.aligned %0;" ::"n"(N) : "memory"); }
template <int N> __device__ __forceinline__ void fence_regs(float* d) {
#pragma unroll
  for (int i = 0; i < N; i++) asm volatile("" : "+f"(d[i])::"memory");
}
__device__ __forceinline__ uint64_t mkdesc(uint32_t addr, uint32_t lbo, uint32_t sbo, uint32_t sw) {
  return (uint64_t)((addr & 0x3FFFF) >> 4) | ((uint64_t)(lbo >> 4) << 16) | ((uint64_t)(sbo >> 4) << 32) | ((uint64_t)sw << 62);
}
__device__ __forceinline__ uint32_t lds32(uint32_t a) { uint32_t v; asm volatile("ld.shared.b32 %0, [%1];" : "=r"(v) : "r"(a) : "memory"); return v; }
__device__ __forceinline__ float lds32f(uint32_t a) { float v; asm volatile("ld.shared.f32 %0, [%1];" : "=f"(v) : "r"(a) : "memory"); return v; }
__device__ __forceinline__ float2 lds64f(uint32_t a) { float2 v; asm volatile("ld.shared.v2.f32 {%0,%1}, [%2];" : "=f"(v.x), "=f"(v.y) : "r"(a) : "memory"); return v; }
__device__ __forceinline__ uint4 lds128(uint32_t a) {
  uint4 v; asm volatile("ld.shared.v4.b32 {%0,%1,%2,%3}, [%4];" : "=r"(v.x), "=r"(v.y), "=r"(v.z), "=r"(v.w) : "r"(a) : "memory"); return v;
}
__device__ __forceinline__ void sts16(uint32_t a, uint16_t v) { asm volatile("st.shared.b16 [%0], %1;" ::"r"(a), "h"(v) : "memory"); }
__device__ __forceinline__ void sts32f(uint32_t a, float v) { asm volatile("st.shared.f32 [%0], %1;" ::"r"(a), "f"(v) : "memory"); }
__device__ __forceinline__ void sts64f(uint32_t a, float x, float y) { asm volatile("st.shared.v2.f32 [%0], {%1,%2};" ::"r"(a), "f"(x), "f"(y) : "memory"); }
__device__ __forceinline__ void sts128(uint32_t a, uint32_t x, uint32_t y, uint32_t z, uint32_t w) {
  asm volatile("st.shared.v4.b32 [%0], {%1,%2,%3,%4};" ::"r"(a), "r"(x), "r"(y), "r"(z), "r"(w) : "memory");
}
__device__ __forceinline__ void ldsm4(uint32_t a, uint32_t& r0, uint32_t& r1, uint32_t& r2, uint32_t& r3) {
  asm volatile("ldmatrix.sync.aligned.m8n8.x4.shared.b16 {%0,%1,%2,%3}, [%4];" : "=r"(r0), "=r"(r1), "=r"(r2), "=r"(r3) : "r"(a) : "memory");
}
__device__ __forceinline__ void ldsm4t(uint32_t a, uint32_t& r0, uint32_t& r1, uint32_t& r2, uint32_t& r3) {
  asm volatile("ldmatrix.sync.aligned.m8n8.x4.trans.shared.b16 {%0,%1,%2,%3}, [%4];" : "=r"(r0), "=r"(r1), "=r"(r2), "=r"(r3) : "r"(a) : "memory");
}
__device__ __forceinline__ void ldsm2t(uint32_t a, uint32_t& r0, uint32_t& r1) {
  asm volatile("ldmatrix.sync.aligned.m8n8.x2.trans.shared.b16 {%0,%1}, [%2];" : "=r"(r0), "=r"(r1) : "r"(a) : "memory");
}
__device__ __forceinline__ void stsm4(uint32_t a, uint32_t r0, uint32_t r1, uint32_t r2, uint32_t r3) {
  asm volatile("stmatrix.sync.aligned.m8n8.x4.shared.b16 [%0], {%1,%2,%3,%4};" ::"r"(a), "r"(r0), "r"(r1), "r"(r2), "r"(r3) : "memory");
}
__device__ __forceinline__ void mma_f16(float* c, uint32_t a0, uint32_t a1, uint32_t a2, uint32_t a3, uint32_t b0, uint32_t b1) {
  asm("mma.sync.aligned.m16n8k16.row.col.f32.f16.f16.f32 {%0,%1,%2,%3},{%4,%5,%6,%7},{%8,%9},{%0,%1,%2,%3};"
               : "+f"(c[0]), "+f"(c[1]), "+f"(c[2]), "+f"(c[3]) : "r"(a0), "r"(a1), "r"(a2), "r"(a3), "r"(b0), "r"(b1));
}
__device__ __forceinline__ void mma_bf16(float* c, uint32_t a0, uint32_t a1, uint32_t a2, uint32_t a3, uint32_t b0, uint32_t b1) {
  asm("mma.sync.aligned.m16n8k16.row.col.f32.bf16.bf16.f32 {%0,%1,%2,%3},{%4,%5,%6,%7},{%8,%9},{%0,%1,%2,%3};"
      : "+f"(c[0]), "+f"(c[1]), "+f"(c[2]), "+f"(c[3]) : "r"(a0), "r"(a1), "r"(a2), "r"(a3), "r"(b0), "r"(b1));
}
__device__ __forceinline__ uint4 ld_relaxed4(const void* p) {
  uint4 v; asm volatile("ld.relaxed.gpu.global.v4.b32 {%0,%1,%2,%3}, [%4];" : "=r"(v.x), "=r"(v.y), "=r"(v.z), "=r"(v.w) : "l"(p) : "memory"); return v;
}
__device__ __forceinline__ uint4 ld_2x64(const void* p) {
  uint4 v;
  asm volatile("{.reg .b64 a, c; ld.relaxed.gpu.global.v2.b64 {a, c}, [%4]; mov.b64 {%0,%1}, a; mov.b64 {%2,%3}, c;}"
               : "=r"(v.x), "=r"(v.y), "=r"(v.z), "=r"(v.w) : "l"(p) : "memory");
  return v;
}
__device__ __forceinline__ void st_relaxed2(void* p, uint32_t x, uint32_t y) {
  asm volatile("st.relaxed.gpu.global.v2.b32 [%0], {%1,%2};" ::"l"(p), "r"(x), "r"(y) : "memory");
}
__device__ __forceinline__ uint4 ld_b128(const void* p) {
  uint4 v;
  asm volatile("{.reg .b128 t; .reg .b64 a, c; ld.relaxed.gpu.global.b128 t, [%4]; mov.b128 {a, c}, t; mov.b64 {%0,%1}, a; mov.b64 {%2,%3}, c;}"
               : "=r"(v.x), "=r"(v.y), "=r"(v.z), "=r"(v.w) : "l"(p) : "memory");
  return v;
}
__device__ __forceinline__ void st_b128(void* p, uint32_t tag, uint32_t x, uint32_t y, uint32_t z, uint32_t w) {
  asm volatile("{.reg .b128 t; .reg .b64 a, c; mov.b64 a, {%1,%2}; mov.b64 c, {%3,%4}; mov.b128 t, {a, c}; st.relaxed.gpu.global.b128 [%0], t;}"
               ::"l"(p), "r"((x & ~1u) | tag), "r"(y), "r"(z), "r"(w) : "memory");
}
__device__ __forceinline__ unsigned ld_relaxed1(const unsigned* p) {
  unsigned v; asm volatile("ld.relaxed.gpu.global.u32 %0, [%1];" : "=r"(v) : "l"(p) : "memory"); return v;
}
__device__ __forceinline__ void red_relaxed(unsigned* p) {
  asm volatile("red.relaxed.gpu.global.add.u32 [%0], 1;" ::"l"(p) : "memory");
}
__device__ __forceinline__ void red_release(unsigned* p) {
  asm volatile("red.release.gpu.global.add.u32 [%0], 1;" ::"l"(p) : "memory");
}
__device__ __forceinline__ void wait_count(const unsigned* p, unsigned target) {
#pragma unroll 1
  for (int it = 0; it < SPIN_MAX; it++) {
    if ((int)(ld_relaxed1(p) - target) >= 0) break;
    __nanosleep(40);
  }
  asm volatile("fence.acq_rel.gpu;" ::: "memory");
}
__device__ __forceinline__ uint32_t pack_h2(float lo, float hi) { uint32_t r; asm("cvt.rn.f16x2.f32 %0, %1, %2;" : "=r"(r) : "f"(hi), "f"(lo)); return r; }
__device__ __forceinline__ uint32_t pack_bf2(float lo, float hi) { uint32_t r; asm("cvt.rn.bf16x2.f32 %0, %1, %2;" : "=r"(r) : "f"(hi), "f"(lo)); return r; }
__device__ __forceinline__ float bf_lo(uint32_t w) { return __uint_as_float(w << 16); }
__device__ __forceinline__ float bf_hi(uint32_t w) { return __uint_as_float(w & 0xffff0000u); }
__device__ __forceinline__ float rbf(float v) { return __bfloat162float(__float2bfloat16_rn(v)); }
__device__ __forceinline__ float2 h2f(uint32_t w) { return __half22float2(*reinterpret_cast<__half2*>(&w)); }
__device__ __forceinline__ float ex2f(float v) { float r; asm("ex2.approx.ftz.f32 %0, %1;" : "=f"(r) : "f"(v)); return r; }
__device__ __forceinline__ float rcpf_(float v) { float r; asm("rcp.approx.f32 %0, %1;" : "=f"(r) : "f"(v)); return r; }
__device__ __forceinline__ float sqrtf_(float v) { float r; asm("sqrt.approx.f32 %0, %1;" : "=f"(r) : "f"(v)); return r; }
__device__ __forceinline__ float tanhf_(float v) { float r; asm volatile("tanh.approx.f32 %0, %1;" : "=f"(r) : "f"(v)); return r; }

__device__ __forceinline__ void wg_ss_bf16_n256(float* d, uint64_t da, uint64_t db, int sc) {
  asm volatile("{.reg .pred p; setp.ne.b32 p, %130, 0;\n"
    "wgmma.mma_async.sync.aligned.m64n256k16.f32.bf16.bf16 {%0, %1, %2, %3, %4, %5, %6, %7, %8, %9, %10, %11, %12, %13, %14, %15, %16, %17, %18, %19, %20, %21, %22, %23, %24, %25, %26, %27, %28, %29, %30, %31, %32, %33, %34, %35, %36, %37, %38, %39, %40, %41, %42, %43, %44, %45, %46, %47, %48, %49, %50, %51, %52, %53, %54, %55, %56, %57, %58, %59, %60, %61, %62, %63, %64, %65, %66, %67, %68, %69, %70, %71, %72, %73, %74, %75, %76, %77, %78, %79, %80, %81, %82, %83, %84, %85, %86, %87, %88, %89, %90, %91, %92, %93, %94, %95, %96, %97, %98, %99, %100, %101, %102, %103, %104, %105, %106, %107, %108, %109, %110, %111, %112, %113, %114, %115, %116, %117, %118, %119, %120, %121, %122, %123, %124, %125, %126, %127}, %128, %129, p, 1, 1, 0, 1;}\n"
    : "+f"(d[0]), "+f"(d[1]), "+f"(d[2]), "+f"(d[3]), "+f"(d[4]), "+f"(d[5]), "+f"(d[6]), "+f"(d[7]), "+f"(d[8]), "+f"(d[9]), "+f"(d[10]), "+f"(d[11]), "+f"(d[12]), "+f"(d[13]), "+f"(d[14]), "+f"(d[15]), "+f"(d[16]), "+f"(d[17]), "+f"(d[18]), "+f"(d[19]), "+f"(d[20]), "+f"(d[21]), "+f"(d[22]), "+f"(d[23]), "+f"(d[24]), "+f"(d[25]), "+f"(d[26]), "+f"(d[27]), "+f"(d[28]), "+f"(d[29]), "+f"(d[30]), "+f"(d[31]), "+f"(d[32]), "+f"(d[33]), "+f"(d[34]), "+f"(d[35]), "+f"(d[36]), "+f"(d[37]), "+f"(d[38]), "+f"(d[39]), "+f"(d[40]), "+f"(d[41]), "+f"(d[42]), "+f"(d[43]), "+f"(d[44]), "+f"(d[45]), "+f"(d[46]), "+f"(d[47]), "+f"(d[48]), "+f"(d[49]), "+f"(d[50]), "+f"(d[51]), "+f"(d[52]), "+f"(d[53]), "+f"(d[54]), "+f"(d[55]), "+f"(d[56]), "+f"(d[57]), "+f"(d[58]), "+f"(d[59]), "+f"(d[60]), "+f"(d[61]), "+f"(d[62]), "+f"(d[63]), "+f"(d[64]), "+f"(d[65]), "+f"(d[66]), "+f"(d[67]), "+f"(d[68]), "+f"(d[69]), "+f"(d[70]), "+f"(d[71]), "+f"(d[72]), "+f"(d[73]), "+f"(d[74]), "+f"(d[75]), "+f"(d[76]), "+f"(d[77]), "+f"(d[78]), "+f"(d[79]), "+f"(d[80]), "+f"(d[81]), "+f"(d[82]), "+f"(d[83]), "+f"(d[84]), "+f"(d[85]), "+f"(d[86]), "+f"(d[87]), "+f"(d[88]), "+f"(d[89]), "+f"(d[90]), "+f"(d[91]), "+f"(d[92]), "+f"(d[93]), "+f"(d[94]), "+f"(d[95]), "+f"(d[96]), "+f"(d[97]), "+f"(d[98]), "+f"(d[99]), "+f"(d[100]), "+f"(d[101]), "+f"(d[102]), "+f"(d[103]), "+f"(d[104]), "+f"(d[105]), "+f"(d[106]), "+f"(d[107]), "+f"(d[108]), "+f"(d[109]), "+f"(d[110]), "+f"(d[111]), "+f"(d[112]), "+f"(d[113]), "+f"(d[114]), "+f"(d[115]), "+f"(d[116]), "+f"(d[117]), "+f"(d[118]), "+f"(d[119]), "+f"(d[120]), "+f"(d[121]), "+f"(d[122]), "+f"(d[123]), "+f"(d[124]), "+f"(d[125]), "+f"(d[126]), "+f"(d[127])
    : "l"(da), "l"(db), "r"(sc));
}

__device__ __forceinline__ void wg_ss_bf16_n256k(float* d, uint64_t da, uint64_t db, int sc) {
  asm volatile("{.reg .pred p; setp.ne.b32 p, %130, 0;\n"
    "wgmma.mma_async.sync.aligned.m64n256k16.f32.bf16.bf16 {%0, %1, %2, %3, %4, %5, %6, %7, %8, %9, %10, %11, %12, %13, %14, %15, %16, %17, %18, %19, %20, %21, %22, %23, %24, %25, %26, %27, %28, %29, %30, %31, %32, %33, %34, %35, %36, %37, %38, %39, %40, %41, %42, %43, %44, %45, %46, %47, %48, %49, %50, %51, %52, %53, %54, %55, %56, %57, %58, %59, %60, %61, %62, %63, %64, %65, %66, %67, %68, %69, %70, %71, %72, %73, %74, %75, %76, %77, %78, %79, %80, %81, %82, %83, %84, %85, %86, %87, %88, %89, %90, %91, %92, %93, %94, %95, %96, %97, %98, %99, %100, %101, %102, %103, %104, %105, %106, %107, %108, %109, %110, %111, %112, %113, %114, %115, %116, %117, %118, %119, %120, %121, %122, %123, %124, %125, %126, %127}, %128, %129, p, 1, 1, 0, 0;}\n"
    : "+f"(d[0]), "+f"(d[1]), "+f"(d[2]), "+f"(d[3]), "+f"(d[4]), "+f"(d[5]), "+f"(d[6]), "+f"(d[7]), "+f"(d[8]), "+f"(d[9]), "+f"(d[10]), "+f"(d[11]), "+f"(d[12]), "+f"(d[13]), "+f"(d[14]), "+f"(d[15]), "+f"(d[16]), "+f"(d[17]), "+f"(d[18]), "+f"(d[19]), "+f"(d[20]), "+f"(d[21]), "+f"(d[22]), "+f"(d[23]), "+f"(d[24]), "+f"(d[25]), "+f"(d[26]), "+f"(d[27]), "+f"(d[28]), "+f"(d[29]), "+f"(d[30]), "+f"(d[31]), "+f"(d[32]), "+f"(d[33]), "+f"(d[34]), "+f"(d[35]), "+f"(d[36]), "+f"(d[37]), "+f"(d[38]), "+f"(d[39]), "+f"(d[40]), "+f"(d[41]), "+f"(d[42]), "+f"(d[43]), "+f"(d[44]), "+f"(d[45]), "+f"(d[46]), "+f"(d[47]), "+f"(d[48]), "+f"(d[49]), "+f"(d[50]), "+f"(d[51]), "+f"(d[52]), "+f"(d[53]), "+f"(d[54]), "+f"(d[55]), "+f"(d[56]), "+f"(d[57]), "+f"(d[58]), "+f"(d[59]), "+f"(d[60]), "+f"(d[61]), "+f"(d[62]), "+f"(d[63]), "+f"(d[64]), "+f"(d[65]), "+f"(d[66]), "+f"(d[67]), "+f"(d[68]), "+f"(d[69]), "+f"(d[70]), "+f"(d[71]), "+f"(d[72]), "+f"(d[73]), "+f"(d[74]), "+f"(d[75]), "+f"(d[76]), "+f"(d[77]), "+f"(d[78]), "+f"(d[79]), "+f"(d[80]), "+f"(d[81]), "+f"(d[82]), "+f"(d[83]), "+f"(d[84]), "+f"(d[85]), "+f"(d[86]), "+f"(d[87]), "+f"(d[88]), "+f"(d[89]), "+f"(d[90]), "+f"(d[91]), "+f"(d[92]), "+f"(d[93]), "+f"(d[94]), "+f"(d[95]), "+f"(d[96]), "+f"(d[97]), "+f"(d[98]), "+f"(d[99]), "+f"(d[100]), "+f"(d[101]), "+f"(d[102]), "+f"(d[103]), "+f"(d[104]), "+f"(d[105]), "+f"(d[106]), "+f"(d[107]), "+f"(d[108]), "+f"(d[109]), "+f"(d[110]), "+f"(d[111]), "+f"(d[112]), "+f"(d[113]), "+f"(d[114]), "+f"(d[115]), "+f"(d[116]), "+f"(d[117]), "+f"(d[118]), "+f"(d[119]), "+f"(d[120]), "+f"(d[121]), "+f"(d[122]), "+f"(d[123]), "+f"(d[124]), "+f"(d[125]), "+f"(d[126]), "+f"(d[127])
    : "l"(da), "l"(db), "r"(sc));
}

__device__ __forceinline__ void wg_rs_bf16_n64(float* d, uint32_t a0, uint32_t a1, uint32_t a2, uint32_t a3, uint64_t db, int sc) {
  asm volatile("{.reg .pred p; setp.ne.b32 p, %37, 0;\n"
    "wgmma.mma_async.sync.aligned.m64n64k16.f32.bf16.bf16 {%0, %1, %2, %3, %4, %5, %6, %7, %8, %9, %10, %11, %12, %13, %14, %15, %16, %17, %18, %19, %20, %21, %22, %23, %24, %25, %26, %27, %28, %29, %30, %31}, {%32,%33,%34,%35}, %36, p, 1, 1, 1;}\n"
    : "+f"(d[0]), "+f"(d[1]), "+f"(d[2]), "+f"(d[3]), "+f"(d[4]), "+f"(d[5]), "+f"(d[6]), "+f"(d[7]), "+f"(d[8]), "+f"(d[9]), "+f"(d[10]), "+f"(d[11]), "+f"(d[12]), "+f"(d[13]), "+f"(d[14]), "+f"(d[15]), "+f"(d[16]), "+f"(d[17]), "+f"(d[18]), "+f"(d[19]), "+f"(d[20]), "+f"(d[21]), "+f"(d[22]), "+f"(d[23]), "+f"(d[24]), "+f"(d[25]), "+f"(d[26]), "+f"(d[27]), "+f"(d[28]), "+f"(d[29]), "+f"(d[30]), "+f"(d[31])
    : "r"(a0), "r"(a1), "r"(a2), "r"(a3), "l"(db), "r"(sc));
}

__device__ __forceinline__ void wg_rs_f16_n32k(float* d, uint32_t a0, uint32_t a1, uint32_t a2, uint32_t a3, uint64_t db, int sc) {
  asm volatile("{.reg .pred p; setp.ne.b32 p, %21, 0;\n"
    "wgmma.mma_async.sync.aligned.m64n32k16.f32.f16.f16 {%0, %1, %2, %3, %4, %5, %6, %7, %8, %9, %10, %11, %12, %13, %14, %15}, {%16,%17,%18,%19}, %20, p, 1, 1, 0;}\n"
    : "+f"(d[0]), "+f"(d[1]), "+f"(d[2]), "+f"(d[3]), "+f"(d[4]), "+f"(d[5]), "+f"(d[6]), "+f"(d[7]), "+f"(d[8]), "+f"(d[9]), "+f"(d[10]), "+f"(d[11]), "+f"(d[12]), "+f"(d[13]), "+f"(d[14]), "+f"(d[15])
    : "r"(a0), "r"(a1), "r"(a2), "r"(a3), "l"(db), "r"(sc));
}

__device__ __forceinline__ void wg_rs_f16_n24t(float* d, uint32_t a0, uint32_t a1, uint32_t a2, uint32_t a3, uint64_t db, int sc) {
  asm volatile("{.reg .pred p; setp.ne.b32 p, %17, 0;\n"
    "wgmma.mma_async.sync.aligned.m64n24k16.f32.f16.f16 {%0, %1, %2, %3, %4, %5, %6, %7, %8, %9, %10, %11}, {%12,%13,%14,%15}, %16, p, 1, 1, 1;}\n"
    : "+f"(d[0]), "+f"(d[1]), "+f"(d[2]), "+f"(d[3]), "+f"(d[4]), "+f"(d[5]), "+f"(d[6]), "+f"(d[7]), "+f"(d[8]), "+f"(d[9]), "+f"(d[10]), "+f"(d[11])
    : "r"(a0), "r"(a1), "r"(a2), "r"(a3), "l"(db), "r"(sc));
}

__device__ __forceinline__ void wg_rs_f16_n16t(float* d, uint32_t a0, uint32_t a1, uint32_t a2, uint32_t a3, uint64_t db, int sc) {
  asm volatile("{.reg .pred p; setp.ne.b32 p, %13, 0;\n"
    "wgmma.mma_async.sync.aligned.m64n16k16.f32.f16.f16 {%0, %1, %2, %3, %4, %5, %6, %7}, {%8,%9,%10,%11}, %12, p, 1, 1, 1;}\n"
    : "+f"(d[0]), "+f"(d[1]), "+f"(d[2]), "+f"(d[3]), "+f"(d[4]), "+f"(d[5]), "+f"(d[6]), "+f"(d[7])
    : "r"(a0), "r"(a1), "r"(a2), "r"(a3), "l"(db), "r"(sc));
}

struct cf { float x, y; };
__device__ __forceinline__ cf cmul(cf a, cf b) { cf r; r.x = fmaf(a.x, b.x, -a.y * b.y); r.y = fmaf(a.x, b.y, a.y * b.x); return r; }
__device__ __forceinline__ cf zpow(float rho2, float phi, float e) {
  const float m = ex2f(rho2 * e), ang = phi * e;
  cf r; r.x = m * __cosf(ang); r.y = m * __sinf(ang); return r;
}
__device__ __forceinline__ __half2 H2(uint32_t v) { return *reinterpret_cast<__half2*>(&v); }
__device__ __forceinline__ uint32_t U32(__half2 v) { return *reinterpret_cast<uint32_t*>(&v); }
__device__ __forceinline__ uint32_t hprod(uint32_t v, uint32_t r, uint32_t rr) {
  return U32(__hfma2(__high2half2(H2(v)), H2(rr), __hmul2(__low2half2(H2(v)), H2(r))));
}
template <bool CONJ>
__device__ __forceinline__ void hprod2(uint32_t re, uint32_t im, uint32_t r, uint32_t& ore, uint32_t& oim) {
  const __half2 rx = __low2half2(H2(r)), ry = __high2half2(H2(r));
  if (CONJ) {
    ore = U32(__hfma2(H2(re), rx, __hmul2(H2(im), ry)));
    oim = U32(__hfma2(H2(im), rx, __hneg2(__hmul2(H2(re), ry))));
  } else {
    ore = U32(__hfma2(H2(re), rx, __hneg2(__hmul2(H2(im), ry))));
    oim = U32(__hfma2(H2(re), ry, __hmul2(H2(im), rx)));
  }
}
__device__ __forceinline__ cf csq(cf a) { cf r; r.x = fmaf(a.x, a.x, -a.y * a.y); r.y = (a.x + a.x) * a.y; return r; }
__device__ __forceinline__ cf cmulc(cf a, cf b) { cf r; r.x = fmaf(a.x, b.x, a.y * b.y); r.y = fmaf(a.y, b.x, -a.x * b.y); return r; }
__device__ __forceinline__ uint32_t pk(cf a) { return pack_h2(a.x, a.y); }
__device__ __forceinline__ uint32_t ldg32(const void* p, int o) { uint32_t v; asm volatile("ld.global.nc.b32 %0, [%1];" : "=r"(v) : "l"((const char*)p + o)); return v; }
__device__ __forceinline__ uint32_t rot90(uint32_t v) { return __byte_perm(v, 0, 0x1032) ^ 0x00008000u; }
__device__ __forceinline__ uint32_t hadd2u(uint32_t a, uint32_t b) { return U32(__hadd2(H2(a), H2(b))); }

struct KgIn { uint32_t cur[6], nxt[6], ldt, dk; bool odd; };
__device__ __forceinline__ float pow2_floor(float v) { return __uint_as_float(__float_as_uint(fminf(fmaxf(v, 1e-30f), 1e30f)) & 0x7f800000u); }
__device__ __forceinline__ void kgen_mma(float* acc, const uint32_t (*A)[4], const uint32_t (*B)[6], int csrc) {
#pragma unroll
  for (int ks = 0; ks < 4; ks++) {
    const uint32_t rl = __shfl_sync(0xffffffffu, B[ks][4], csrc), rh = __shfl_sync(0xffffffffu, B[ks][5], csrc);
    const uint32_t rlr = rot90(rl), rhr = rot90(rh);
    mma_f16(acc + 0, A[ks][0], A[ks][1], A[ks][2], A[ks][3], B[ks][0], B[ks][1]);
    mma_f16(acc + 4, A[ks][0], A[ks][1], A[ks][2], A[ks][3], B[ks][2], B[ks][3]);
    mma_f16(acc + 8, A[ks][0], A[ks][1], A[ks][2], A[ks][3], B[ks][4], B[ks][5]);
    const uint32_t c0 = hprod(A[ks][0], rl, rlr), c1 = hprod(A[ks][1], rl, rlr);
    const uint32_t c2 = hprod(A[ks][2], rh, rhr), c3 = hprod(A[ks][3], rh, rhr);
    mma_f16(acc + 12, c0, c1, c2, c3, B[ks][0], B[ks][1]);
    mma_f16(acc + 16, c0, c1, c2, c3, B[ks][2], B[ks][3]);
    mma_f16(acc + 20, c0, c1, c2, c3, B[ks][4], B[ks][5]);
  }
}
template <class Mid>
__device__ __forceinline__ void kgen_warp(KgIn& k, int nw, uint32_t stg, uint32_t tbl, int lane, Mid mid) {
  float dl, dt, sc, inv_sc;
  {
    const uint32_t M = 0x7fff7fffu;
    uint32_t mx[2];
#pragma unroll
    for (int i = 0; i < 2; i++) {
      const uint32_t m = __vmaxu2(__vmaxu2(k.cur[2 + 2 * i] & M, k.cur[3 + 2 * i] & M), __vmaxu2(k.nxt[2 + 2 * i] & M, k.nxt[3 + 2 * i] & M));
      mx[i] = __reduce_max_sync(0xffffffffu, max(m << 16, m & 0xffff0000u));
    }
    dt = rbf(ex2f((k.odd ? bf_hi(k.ldt) : bf_lo(k.ldt)) * 1.4426950408889634f));
    sc = pow2_floor(0.125f * __uint_as_float(mx[0]) * __uint_as_float(mx[1]));
    inv_sc = rcpf_(sc);
    if (lane == 0) sts64f(tbl + TBL_SC + 8, dt, (k.odd ? bf_hi(k.dk) : bf_lo(k.dk)) * rcpf_(dt));
    dl = dt * 1.4426950408889634f;
  }
  const uint32_t st0 = stg + lane * KREC + (((lane >> 2) & 1) << 4), st1 = st0 ^ 16;
  const int mat = lane >> 3, rowi = lane & 7;
  const uint32_t ldB = stg + (4 * (mat & 1) + (rowi >> 1)) * KREC + ((((mat >> 1) * 2 + (rowi & 1)) << 4) ^ ((mat & 1) << 4));
  const uint32_t ldA = stg + (4 * (mat >> 1) + (rowi >> 1)) * KREC + ((((mat & 1) * 2 + (rowi & 1)) << 4) ^ ((mat >> 1) << 4)) + 96;
  const int csrc = 20 + (lane & 3);
  float acc[24];
  uint32_t B[4][6], A[4][4];
#pragma unroll
  for (int i = 0; i < 24; i++) { acc[i] = 0.f; B[i / 6][i % 6] = 0u; }
#pragma unroll
  for (int i = 0; i < 16; i++) A[i / 4][i % 4] = 0u;
#pragma unroll 1
  for (int it = 0; it < 2 * nw; it++) {
    if (it == 1) mid();
    const uint32_t sel = (it & 1) ? 0x3244u : 0x1044u;
    float v[6];
#pragma unroll
    for (int i = 0; i < 6; i++) { v[i] = __uint_as_float(__byte_perm(k.cur[i], 0, sel)); if (it == 1) k.cur[i] = k.nxt[i]; }
    const float rho2 = v[0] * dl, phi = v[1] * dt;
    const cf bb = {v[2] * inv_sc, v[3] * -inv_sc}, cc = {v[4], v[5]};
    const cf X0 = cmulc(bb, cc);
    const cf z1 = zpow(rho2, phi, 1.f), z64 = zpow(rho2, phi, 64.f);
    kgen_mma(acc, A, B, csrc);
    const cf z2 = csq(z1), z3 = cmul(z2, z1), z4 = csq(z2), z8 = csq(z4), z16 = csq(z8), z24 = cmul(z16, z8), z32 = csq(z16);
    const cf z128 = csq(z64), y1 = csq(z128), y2 = csq(y1), y3 = cmul(y2, y1), y4 = csq(y2);
    const cf X4 = cmulc(X0, z4), W4 = cmulc(X0, y4), W8 = cmulc(W4, y4);
    uint32_t re[4], im[4], r2[4], i2[4];
    re[0] = pack_h2(X0.x, X4.x); im[0] = pack_h2(X0.y, X4.y);
    hprod2<true>(re[0], im[0], pk(z1), re[1], im[1]);
    hprod2<true>(re[0], im[0], pk(z2), re[2], im[2]);
    hprod2<true>(re[0], im[0], pk(z3), re[3], im[3]);
    sts128(st0, re[0], re[1], re[2], re[3]);
    sts128(st1, im[0], im[1], im[2], im[3]);
    const uint32_t hy1 = pk(y1), hy2 = pk(y2);
    hprod2<true>(re[0], im[0], hy1, r2[0], i2[0]);
    hprod2<true>(re[2], im[2], hy1, r2[1], i2[1]);
    hprod2<true>(re[0], im[0], hy2, r2[2], i2[2]);
    hprod2<true>(re[0], im[0], pk(y3), r2[3], i2[3]);
    sts128(st0 + 32, r2[0], r2[1], r2[2], r2[3]);
    sts128(st1 + 32, i2[0], i2[1], i2[2], i2[3]);
    const cf W5 = cmulc(W4, y1);
    re[0] = pack_h2(W4.x, W5.x); im[0] = pack_h2(W4.y, W5.y);
    hprod2<true>(re[0], im[0], hy2, re[1], im[1]);
    sts128(st0 + 64, re[0], re[1], pack_h2(W8.x, z128.x), hy1);
    sts128(st1 + 64, im[0], im[1], pack_h2(W8.y, z128.y), hy1);
    re[0] = pack_h2(1.f, z32.x); im[0] = pack_h2(0.f, z32.y);
    hprod2<false>(re[0], im[0], pk(z8), re[1], im[1]);
    hprod2<false>(re[0], im[0], pk(z16), re[2], im[2]);
    hprod2<false>(re[0], im[0], pk(z24), re[3], im[3]);
    const uint32_t h64 = pk(z64);
#pragma unroll
    for (int j = 0; j < 4; j++) hprod2<false>(re[j], im[j], h64, r2[j], i2[j]);
    sts128(st0 + 96, re[0], re[1], re[2], re[3]);
    sts128(st1 + 96, im[0], im[1], im[2], im[3]);
    sts128(st0 + 128, r2[0], r2[1], r2[2], r2[3]);
    sts128(st1 + 128, i2[0], i2[1], i2[2], i2[3]);
    __syncwarp();
#pragma unroll
    for (int ks = 0; ks < 4; ks++) {
      ldsm2t(ldB + ks * 8 * KREC + 64, B[ks][4], B[ks][5]);
      ldsm4t(ldA + ks * 8 * KREC, A[ks][0], A[ks][1], A[ks][2], A[ks][3]);
      ldsm4t(ldB + ks * 8 * KREC, B[ks][0], B[ks][1], B[ks][2], B[ks][3]);
    }
  }
  kgen_mma(acc, A, B, csrc);
#pragma unroll
  for (int q = 0; q < 4; q++)
#pragma unroll
    for (int nt = 0; nt < 3; nt++) {
      const float* a = acc + 12 * (q >> 1) + 4 * nt + 2 * (q & 1);
      sts64f(stg + (q * 3 + nt) * 256 + lane * 8, a[0] * sc, a[1] * sc);
    }
  if (lane == 0) sts32f(stg + 3072, sc);
}

__device__ __forceinline__ void tput(uint32_t tbl, int X, uint32_t h) {
  sts16(tbl + 2 * (1296 - X), (uint16_t)h);
  sts16(tbl + TBL_C1 + 2 * (1297 - X), (uint16_t)h);
}
__device__ __forceinline__ void ktab_build(uint32_t src, bool four, int q, uint32_t tbl, int lane) {
  const int tq = lane & 3, r = 8 * q + (lane >> 3) + ((lane >> 2) & 1) * 4;
  float v[6];
  const float2 dd = lds64f(tbl + TBL_SC + 8);
  float sc = fmaxf(fmaxf(lds32f(src + 3072), lds32f(src + 3072 + KSTG)), pow2_floor(fabsf(dd.y) * (1.f / 4096.f)));
  if (four) sc = fmaxf(sc, fmaxf(lds32f(src + 3072 + 2 * KSTG), lds32f(src + 3072 + 3 * KSTG)));
  const float inv = rcpf_(sc);
  src += q * 768 + lane * 8;
#pragma unroll
  for (int nt = 0; nt < 3; nt++) {
    const float2 a = lds64f(src + nt * 256), c = lds64f(src + nt * 256 + KSTG);
    v[2 * nt] = a.x + c.x; v[2 * nt + 1] = a.y + c.y;
  }
  if (four) {
#pragma unroll
    for (int nt = 0; nt < 3; nt++) {
      const float2 a = lds64f(src + nt * 256 + 2 * KSTG), c = lds64f(src + nt * 256 + 3 * KSTG);
      v[2 * nt] += a.x + c.x; v[2 * nt + 1] += a.y + c.y;
    }
  }
  const bool first = (r == 0);
  if (first && tq == 0) { v[0] += dd.y; sts64f(tbl + TBL_SC, v[4] * inv, dd.x * sc); }
  const uint32_t h0 = pack_h2(v[0] * inv, v[1] * inv), h1 = pack_h2(v[2] * inv, v[3] * inv), h2 = pack_h2(v[4] * inv, v[5] * inv);
  tput(tbl, 64 + 8 * r + tq, h0);
  tput(tbl, 68 + 8 * r + tq, h0 >> 16);
  const bool lo = tq < 2;
  const int k2 = 32 * (tq - 2) + r;
  const bool sp = first && tq == 2;
  const int Xa = lo ? 320 + 8 * r + 2 * tq : (sp ? 576 : 911 + k2), Xb = lo ? Xa + 4 : 720 + k2;
  tput(tbl, Xa, h1);
  tput(tbl, Xb, h1 >> 16);
  if (tq == 0 || sp) {
    tput(tbl, Xa + 1, h1);
    if (Xa != 320) tput(tbl, Xa - 1, h1);
    const uint32_t hb = sp ? h1 : h1 >> 16, hc = sp ? h2 : h1 >> 16;
    tput(tbl, sp ? 578 : Xb + 1, hb);
    tput(tbl, sp ? 1295 : Xb - 1, hc);
  }
  if (lo) {
    const int X3 = ((r & 1) ? 1104 : 1231) + 32 * tq + (r >> 1);
    tput(tbl, X3 == 1231 ? 975 : X3, h2);
    tput(tbl, X3 + 16, h2 >> 16);
  }
}

__device__ __forceinline__ void sig_windows(uint32_t sig, int t) {
  uint32_t U[20];
#pragma unroll
  for (int c = 0; c < 5; c++) {
    const int kap = 2 * t - 3 + c + 72;
    const uint4 v = lds128(sig + SIG_U + (kap & 7) * U_LBO + (kap >> 3) * 16);
    U[4 * c] = v.x; U[4 * c + 1] = v.y; U[4 * c + 2] = v.z; U[4 * c + 3] = v.w;
  }
  uint32_t O[19], A2[17], A4[17], V2[8], V5[8];
#pragma unroll
  for (int i = 3; i < 19; i++) O[i] = __byte_perm(U[i - 1], U[i], 0x5432);
#pragma unroll
  for (int i = 3; i < 17; i++) A2[i] = hadd2u(U[i], O[i]);
#pragma unroll
  for (int i = 4; i < 17; i++) A4[i] = hadd2u(A2[i], A2[i - 1]);
#pragma unroll
  for (int k = 0; k < 8; k++) { V2[k] = hadd2u(O[11 + k], U[10 + k]); V5[k] = hadd2u(A4[9 + k], U[7 + k]); }
#pragma unroll
  for (int h = 0; h < 2; h++) {
    sts128(sig + SIG_V3 + t * 32 + h * 16, hadd2u(V2[4 * h], O[10 + 4 * h]), hadd2u(V2[4 * h + 1], O[11 + 4 * h]),
           hadd2u(V2[4 * h + 2], O[12 + 4 * h]), hadd2u(V2[4 * h + 3], O[13 + 4 * h]));
    sts128(sig + SIG_V5 + t * 32 + h * 16, V5[4 * h], V5[4 * h + 1], V5[4 * h + 2], V5[4 * h + 3]);
  }
  if (t < 64) {
    uint32_t V7[8], V9[8];
#pragma unroll
    for (int k = 0; k < 8; k++) {
      V7[k] = hadd2u(V5[k], hadd2u(O[10 + k], O[7 + k]));
      V9[k] = hadd2u(hadd2u(A4[6 + k], A4[4 + k]), U[2 + k]);
    }
#pragma unroll
    for (int h = 0; h < 2; h++) {
      sts128(sig + SIG_V7 + h * 1024 + t * 16, V7[4 * h], V7[4 * h + 1], V7[4 * h + 2], V7[4 * h + 3]);
      sts128(sig + SIG_V9 + h * 1024 + t * 16, V9[4 * h], V9[4 * h + 1], V9[4 * h + 2], V9[4 * h + 3]);
      sts128(sig + SIG_V2 + h * 1024 + t * 16, V2[4 * h], V2[4 * h + 1], V2[4 * h + 2], V2[4 * h + 3]);
    }
  }
}

__device__ __forceinline__ void conv_channel(uint32_t tbl, uint32_t sig, uint32_t y2b, uint32_t y3b, float k1024,
                                             int w, int lane, int barid, float* res) {
  const int g = lane >> 2, tq = lane & 3;
  const uint32_t tb = tbl + ((g & 1) ? TBL_C1 + 2 : 0) + 2 * (1296 - (g - 2 * tq)) - 32 * w + 112;
  float a2[12], a3[8];
#pragma unroll
  for (int i = 0; i < 16; i++) res[i] = 0.f;
#pragma unroll
  for (int i = 0; i < 12; i++) a2[i] = 0.f;
#pragma unroll
  for (int q = 0; q < 4; q++) {
    const float2 f = h2f(lds32(sig + SIG_V2 + (q >> 1) * 1024 + (16 * w + 8 * (q & 1) + g) * 16 + tq * 4));
    a3[2 * q] = k1024 * f.x;
    a3[2 * q + 1] = k1024 * f.y;
  }
  const uint32_t sigu = __shfl_sync(0xffffffffu, opaque(sig), 0);
  const uint64_t dU = mkdesc(sigu + SIG_U, U_LBO, 128, 0);
  const uint64_t dV = mkdesc(sigu, 128, 1024, 0);
  fence_regs<16>(res); fence_regs<12>(a2); fence_regs<8>(a3);
  constexpr int LB = 2 * U_LBO / 16;
  uint32_t Rd[43], R2[22], R3[12];
  uint32_t td = tb - 128, t2 = tb - 1440, t3 = tb - 2208;
  uint64_t dd = dU + 9, d2 = dV + (SIG_V3 + 768) / 16, d3 = dV + (SIG_V7 + 768) / 16;
  auto load_group = [&](int gi) {
#pragma unroll
    for (int i = 1; i < 5; i++) Rd[4 * gi + i] = lds32(td - 16 * (4 * gi + i));
    const int e = gi >> 3;
    if ((gi & 7) == 0) { R2[2 * gi + e] = lds32(t2 - 384 * e); R3[gi + e] = lds32(t3 - 256 * e); }
    R2[2 * gi + e + 1] = lds32(t2 - 384 * e - 16 * (2 * (gi & 7) + 1));
    R2[2 * gi + e + 2] = lds32(t2 - 384 * e - 16 * (2 * (gi & 7) + 2));
    if (!(gi & 1)) {
      R3[gi + e + 1] = lds32(t3 - 256 * e - 16 * ((gi & 7) + 1));
      R3[gi + e + 2] = lds32(t3 - 256 * e - 16 * ((gi & 7) + 2));
    }
  };
  auto dense = [&](int n) {
    wg_rs_f16_n32k(res, Rd[2 * n + 1], Rd[2 * n + 2], Rd[2 * n], Rd[2 * n + 1], dd + ((3 - (n & 3)) * LB + 8 - (n >> 2)) - 8, 1);
  };
  Rd[0] = lds32(td);
  load_group(0);
  load_group(1);
#pragma unroll 1
  for (int sg = 0; sg < 2; sg++) {
#pragma unroll
    for (int gi = 0; gi < 8; gi++) {
      wg_fence();
      dense(2 * gi);
      wg_rs_f16_n24t(a2, R2[2 * gi + 1], R2[2 * gi + 2], R2[2 * gi], R2[2 * gi + 1], d2 - (16 * (gi & 3) + 64 * (gi >> 2)), 1);
      dense(2 * gi + 1);
      if (!(gi & 1)) wg_rs_f16_n16t(a3, R3[gi + 1], R3[gi + 2], R3[gi], R3[gi + 1], d3 - 8 * gi, 1);
      wg_commit();
      wg_wait<1>();
      load_group(gi + 2);
    }
#pragma unroll
    for (int i = 0; i < 9; i++) Rd[i] = Rd[32 + i];
#pragma unroll
    for (int i = 0; i < 5; i++) R2[i] = R2[17 + i];
#pragma unroll
    for (int i = 0; i < 3; i++) R3[i] = R3[9 + i];
    td -= 512; t2 -= 384; t3 -= 256;
    dd -= 4; d2 += 256; d3 += 128;
  }
  Rd[9] = lds32(td - 144); Rd[10] = lds32(td - 160);
  wg_fence();
#pragma unroll
  for (int n = 0; n < 5; n++) dense(n);
  wg_commit();
  wg_wait<1>();
  fence_regs<12>(a2); fence_regs<8>(a3);
  bar_sync(barid, 128);
  {
    const uint32_t o2 = y2b + (136 * w + 8 * g + 2 * tq) * 4, o3 = y3b + (272 * w + 16 * g + 2 * tq) * 4;
#pragma unroll
    for (int q = 0; q < 6; q++) sts64f(o2 + (544 * (q >> 1) + 64 * (q & 1)) * 4, a2[2 * q], a2[2 * q + 1]);
#pragma unroll
    for (int q = 0; q < 4; q++) sts64f(o3 + (8 * (q >> 1) + 136 * (q & 1)) * 4, a3[2 * q], a3[2 * q + 1]);
  }
  bar_sync(barid, 128);
  const uint32_t go = (136 * tq + 16 * w + g) * 4;
  float ex[12];
#pragma unroll
  for (int i = 0; i < 12; i++) {
    const int o = 544 * (i >> 2) + 64 * (i & 1) + 8 * ((i >> 1) & 1);
    ex[i] = lds32f(y2b + go + o * 4);
    if (i >= 4) ex[i] += lds32f(y3b + go + (o - 544) * 4);
  }
  wg_wait<0>();
  fence_regs<16>(res);
#pragma unroll
  for (int i = 0; i < 12; i++) res[4 + i] += ex[i];
}

__device__ __forceinline__ void red16x2(float& a, float& c) {
#pragma unroll
  for (int o = 1; o < 16; o <<= 1) { a += __shfl_xor_sync(0xffffffffu, a, o); c += __shfl_xor_sync(0xffffffffu, c, o); }
}
__device__ __forceinline__ void ln_rows(uint32_t* u, uint32_t term, uint32_t stg_row, int lane) {
  const int j = lane & 15;
  const float piv = __shfl_sync(0xffffffffu, bf_lo(u[0]), lane & 16);
  float s0 = 0.f, s1 = 0.f, q0 = 0.f, q1 = 0.f;
#pragma unroll
  for (int i = 0; i < 14; i++) {
    const float a = bf_lo(u[i]) - piv, c = bf_hi(u[i]) - piv;
    s0 += a; s1 += c; q0 = fmaf(a, a, q0); q1 = fmaf(c, c, q1);
  }
  float s = s0 + s1, q = q0 + q1;
  red16x2(s, q);
  s *= (1.f / D_); q *= (1.f / D_);
  const __nv_bfloat16 m1b = __float2bfloat16_rn(s + piv);
  const __nv_bfloat162 m1v = __halves2bfloat162(m1b, m1b);
  const float den = rbf(sqrtf_(rbf(rbf(fmaxf(fmaf(-s, s, q), 0.f)) + 1e-5f)));
  const float rden = rcpf_(den);
  s0 = s1 = q0 = q1 = 0.f;
#pragma unroll
  for (int i = 0; i < 14; i++) {
    const __nv_bfloat162 cv = __hsub2(*reinterpret_cast<__nv_bfloat162*>(&u[i]), m1v);
    const uint32_t c = *reinterpret_cast<const uint32_t*>(&cv);
    const uint32_t n = pack_bf2(bf_lo(c) * rden, bf_hi(c) * rden);
    const float a = bf_lo(n), e = bf_hi(n);
    s0 += a; s1 += e; q0 = fmaf(a, a, q0); q1 = fmaf(e, e, q1);
    u[i] = pack_h2(a, e);
  }
#pragma unroll
  for (int i = 0; i < 7; i++)
    asm volatile("st.shared.v2.b32 [%0], {%1,%2};" ::"r"(stg_row + (j + 16 * i) * 8), "r"(u[2 * i]), "r"(u[2 * i + 1]) : "memory");
  s = s0 + s1; q = q0 + q1;
  red16x2(s, q);
  s *= (1.f / D_); q *= (1.f / D_);
  const float den2 = rbf(sqrtf_(rbf(rbf(fmaxf(fmaf(-s, s, q), 0.f)) + 1e-5f)));
  if (j == 0) {
    const float ir = den * den2, mu = fmaf(rbf(s), den, __bfloat162float(m1b));
    const float ih = rbf(ir), mh = rbf(mu);
    const uint32_t mm = pack_bf2(mh, mh);
    sts128(term, pack_bf2(mu - mh, ih), mm, pack_bf2(mu - mh, ir - ih), mm);
  }
}

__device__ __forceinline__ void poll_tag(const unsigned* p, uint32_t tag) {
#pragma unroll 1
  for (int it = 0; it < 4096; it++) {
    if (!((ld_relaxed1(p) ^ tag) & 1)) break;
    __nanosleep(32);
  }
}
__device__ __forceinline__ bool last_release(uint32_t cnt) {
  unsigned old;
  asm volatile("atom.relaxed.cta.shared.inc.u32 %0, [%1], 7;" : "=r"(old) : "r"(cnt) : "memory");
  return old == 7;
}
__device__ __forceinline__ int mod7(int v) { return v >= 7 ? v - 7 : v; }

#define IDS const int tid = opaque(tid0), lane = tid & 31, t = tid & 127; (void)lane; (void)t;

__global__ void __launch_bounds__(384, 1)
fused_kernel(const Params p, const __grid_constant__ CUtensorMap tm_x, const __grid_constant__ CUtensorMap tm_w1,
             const __grid_constant__ CUtensorMap tm_w2, const __grid_constant__ CUtensorMap tm_out) {
  const uint32_t sb = smem_u32(smem_raw);
  const uint32_t ms = sb + OFF_M;
  const uint32_t bar0 = ms + M_BAR;
  const int tid0 = threadIdx.x;
  const int wi = __shfl_sync(0xffffffffu, tid0 >> 5, 0), wg = wi >> 2, w = wi & 3;
  const int b = blockIdx.x;
  const bool is_ssm = b >= NMLP;
  const int G = b / NRK, rk = b - G * NRK;
  const int kc0 = (G + rk) % 7;
  TSINIT();
  TSTAMP(0);
  {
    IDS
    TSTAMP(28);
    uint4 ld[7];
    KgIn kin;
    unsigned ep = 0;
    uint32_t b1w;
    const int rl = 2 * wi + (lane >> 4);
    {
      const int d = is_ssm ? 2 * (112 + 3 * (b - NMLP) + wg) + (w >> 1) : (wg < 2 ? 2 * b + wg : 336 + b);
      const int off = d * NST + 64 * (is_ssm ? 2 * (w & 1) : w) + 2 * lane;
      const __nv_bfloat16* P[10] = {p.a_re + off, p.a_im + off, p.b_re + off, p.b_im + off, p.c_re + off, p.c_im + off,
                                    p.log_dt + (d & ~1), p.dskip + (d & ~1), p.b1 + 64 * (is_ssm ? 0 : b >> 2) + (t & 62),
                                    wg < 2 ? p.x + (size_t)(16 * (b & 127) + rl) * D_ + 4 * (lane & 15)
                                           : p.w1 + (size_t)(112 * (b & 3) + 4 * w + (lane & 3)) * F_ + 64 * (is_ssm ? 0 : b >> 2) + 8 * (lane >> 2)};
      const unsigned* pe = &p.s->epoch;
      asm volatile("" : "+l"(P[0]), "+l"(P[1]), "+l"(P[2]), "+l"(P[3]), "+l"(P[4]), "+l"(P[5]), "+l"(P[6]), "+l"(P[7]), "+l"(P[8]), "+l"(P[9]), "+l"(pe));
#pragma unroll
      for (int i = 0; i < 6; i++) kin.cur[i] = ldg32(P[i], 0);
      kin.ldt = ldg32(P[6], 0); kin.dk = ldg32(P[7], 0); b1w = ldg32(P[8], 0);
      if (tid == 256 + 32) ep = ld_relaxed1(pe);
#pragma unroll
      for (int i = 0; i < 6; i++) kin.nxt[i] = 0u;
      if (is_ssm) {
#pragma unroll
        for (int i = 0; i < 6; i++) kin.nxt[i] = ldg32(P[i], 128);
      }
      if (wg < 2) {
#pragma unroll
        for (int i = 0; i < 7; i++) asm volatile("ld.global.nc.v2.b32 {%0,%1}, [%2];" : "=r"(ld[i].x), "=r"(ld[i].y) : "l"(P[9] + 64 * i));
      } else {
#pragma unroll
        for (int i = 0; i < 7; i++)
          asm volatile("ld.global.nc.v4.b32 {%0,%1,%2,%3}, [%4];" : "=r"(ld[i].x), "=r"(ld[i].y), "=r"(ld[i].z), "=r"(ld[i].w) : "l"(P[9] + (size_t)i * 16 * F_));
      }
      asm volatile("" :: "l"(P[0]), "l"(P[1]), "l"(P[2]), "l"(P[3]), "l"(P[4]), "l"(P[5]), "l"(P[6]), "l"(P[7]), "l"(P[8]), "l"(P[9]), "l"(pe));
      kin.odd = d & 1;
    }
    const uint32_t tbl = is_ssm ? sb + (4 * wg + (w >> 1)) * TBL : sb + OFF_T + wg * TBL;
#pragma unroll 1
    for (int i = is_ssm ? t & 63 : t; i < TBL_SC / 16; i += is_ssm ? 64 : 128) sts128(tbl + i * 16, 0u, 0u, 0u, 0u);
    const uint32_t lns = is_ssm ? sb + S_WORK + 2 * S_WGB + 4 * KSTG : sb + OFF_X + 2 * 16384;
    if (wi < 4 && lane == 0) {
      if (wi < 3) mbar_init(bar0 + 8 * wi, 1);
      asm volatile("fence.mbarrier_init.release.cluster;" ::: "memory");
      if (!is_ssm) asm volatile("prefetch.tensormap [%0];" ::"l"(wi == 0 ? &tm_x : wi == 1 ? &tm_w1 : wi == 2 ? &tm_w2 : &tm_out) : "memory");
    }
    __syncwarp();
    if (wi == 4 && lane < 16) asm volatile("st.shared.b32 [%0], 0;" ::"r"(ms + M_REL + 4 * lane) : "memory");
    TSTAMP(31);
    auto mid = [&]() {
    TSTAMP(30);
    if (wg < 2) {
      uint32_t u[14];
#pragma unroll
      for (int i = 0; i < 7; i++) { u[2 * i] = ld[i].x; u[2 * i + 1] = ld[i].y; }
      ln_rows(u, ms + M_LT + rl * 16, lns + ((rl & 1) | ((rl >> 2) << 1) | ((rl & 2) << 2)) * 912, lane);
      bar_arrive(7, 384);
    } else {
      float cs[4] = {0.f, 0.f, 0.f, 0.f};
      const int g = lane >> 2;
      const uint32_t one = (g & 1) ? 0x3f800000u : 0x00003f80u;
      const uint32_t s0 = (g >> 1) == 0 ? one : 0u, s1 = (g >> 1) == 1 ? one : 0u, s2 = (g >> 1) == 2 ? one : 0u, s3 = (g >> 1) == 3 ? one : 0u;
#pragma unroll
      for (int i = 0; i < 7; i++) {
        mma_bf16(cs, s0, 0u, s1, 0u, ld[i].x, ld[i].y);
        mma_bf16(cs, s2, 0u, s3, 0u, ld[i].z, ld[i].w);
      }
      sts32f(ms + M_CSR + (w * 64 + (lane & 3) * 16 + g) * 4, cs[0]);
      sts32f(ms + M_CSR + (w * 64 + (lane & 3) * 16 + g + 8) * 4, cs[1]);
      if (t == 32) { asm volatile("st.shared.b32 [%0], %1;" ::"r"(ms + M_EP), "r"(ep + 1) : "memory"); red_relaxed(&p.s->cntA); }
      bar_sync(7, 384);
      const uint32_t la = lns + (lane & 15) * 912 + (lane >> 4) * 16 + w * 224;
      uint2* dst = (uint2*)(p.s->xnT + (size_t)(56 * w + (lane >> 3)) * 512 + 4 * b) + (lane & 7);
      uint32_t r[28];
#pragma unroll
      for (int k = 0; k < 7; k++) ldsm4t(la + k * 32, r[4 * k], r[4 * k + 1], r[4 * k + 2], r[4 * k + 3]);
      const uint32_t tag = lds32(ms + M_EP) & 1;
      fence_async();
      bar_sync(6, 128);
      if (b < 128) {
#pragma unroll
        for (int k = 0; k < 14; k++) st_relaxed2(dst + k * 4096, (r[2 * k] & ~1u) | tag, (r[2 * k + 1] & ~1u) | tag);
      }
      if (t < 64 && !is_ssm) {
        const uint32_t a = ms + M_CSR + t * 4;
        const float c = -((lds32f(a) + lds32f(a + 256)) + (lds32f(a + 512) + lds32f(a + 768)));
        const float ch = rbf(c);
        uint2* dx = (uint2*)(p.s->bx + (b >> 4) * 512 + ((b >> 1) & 1) * 256 + ((b >> 2) & 3) * 64 + t) + (b & 1);
        const float b1v = (b & 2) ? 0.f : ((t & 1) ? bf_hi(b1w) : bf_lo(b1w));
        asm volatile("{.reg .b64 a; mov.b64 a, {%1,%2}; st.relaxed.gpu.global.b64 [%0], a;}"
                     ::"l"(dx), "r"(pack_bf2(ch, b1v)), "r"((pack_bf2(c - ch, ch) & ~1u) | tag) : "memory");
      }
      if (t >= 64 && t < 80 && b < 128) {
        const uint4 a = lds128(ms + M_LT + (t - 64) * 16);
        st_b128(p.s->ax + 16 * b + t - 64, tag, a.x, a.y, a.z, a.w);
      }
    }
    if ((wi == 0 || wi == 1 || wi == 10) && lane == 0 && !is_ssm) {
      const int i = wi & 3, kc = mod7(kc0 + i);
      mbar_expect(bar0 + 8 * i, 49152);
      tma_2d(sb + OFF_X + i * 16384, &tm_x, 64 * kc, 128 * G, bar0 + 8 * i);
      tma_3d(sb + OFF_W + i * 32768, &tm_w1, 0, 64 * kc, 4 * rk, bar0 + 8 * i);
    }
    __syncwarp();
    TSTAMP(29);
    };
    const uint32_t stg = is_ssm ? sb + S_WORK + wg * S_WGB + w * KSTG : sb + (wg < 2 ? OFF_A + 4 * wg * KSTG : OFF_B) + w * KSTG;
    kgen_warp(kin, is_ssm ? 2 : 1, stg, tbl, lane, mid);
  }
  TSTAMP(1);
  uint4 v[4], tv[5];
  {
    IDS
    bar_sync(4 + wg, 128);
    if (!is_ssm && wg == 2) {
#pragma unroll
      for (int q = 0; q < 4; q++) tv[q] = ld_2x64(p.s->bx + 512 * rk + q * 128 + t);
      tv[4] = ld_b128(p.s->ax + 128 * G + t);
    }
    if (is_ssm || wg == 2) {
      const uint4* src = p.s->xnT + (size_t)(is_ssm ? 112 + 3 * (b - NMLP) + wg : b) * 512 + t;
#pragma unroll
      for (int q = 0; q < 4; q++) v[q] = ld_relaxed4(src + q * 128);
    }
#pragma unroll 1
    for (int c = is_ssm ? 1 : 0; c >= 0; c--) {
      const uint32_t src = is_ssm ? sb + S_WORK + wg * S_WGB + 2 * c * KSTG : sb + (wg < 2 ? OFF_A + 4 * wg * KSTG : OFF_B);
      ktab_build(src, !is_ssm, w, is_ssm ? sb + (4 * wg + c) * TBL : sb + OFF_T + wg * TBL, lane);
    }
    fence_async();
  }
  TSTAMP(2);
  __syncthreads();

  if (is_ssm || wg == 2) {
    asm volatile("setmaxnreg.dec.sync.aligned.u32 136;");
    if (!is_ssm) {
      IDS
      const unsigned ep1 = lds32(ms + M_EP);
#pragma unroll 1
      for (int it = 0; it < 16 * RETRY_MAX; it++) {
        uint32_t bad = tv[4].x ^ ep1;
#pragma unroll
        for (int q = 0; q < 4; q++) bad |= (tv[q].y ^ ep1) | (tv[q].w ^ ep1);
        if (!__any_sync(0xffffffffu, bad & 1)) break;
        __nanosleep(200);
#pragma unroll
        for (int q = 0; q < 4; q++) tv[q] = ld_2x64(p.s->bx + 512 * rk + q * 128 + t);
        tv[4] = ld_b128(p.s->ax + 128 * G + t);
      }
#pragma unroll
      for (int q = 0; q < 5; q++) sts128(sb + OFF_B + (q < 4 ? B_BX + q * 2048 : B_AX) + t * 16, tv[q].x, tv[q].y, tv[q].z, tv[q].w);
      if (t < 64) sts32f(ms + M_CSR + t * 4, 0.5f * __bfloat162float(p.b2[64 * rk + t]));
      fence_async();
      bar_arrive(1, 384);
      if (t == 96) { bulk_s2g(p.s->tbl + b * (TBL / 16), sb + OFF_T + 2 * TBL, TBL); bulk_commit(); }
      if (t == 64)
        asm volatile("cp.async.bulk.prefetch.L2.global [%0], %1;" ::"l"(p.w2 + (size_t)(256 * rk + 16 * G) * D_), "r"(16 * D_ * 2) : "memory");
    }
#pragma unroll 1
    for (int pi = 0; ; pi++) {
      {
        IDS
        const unsigned ep1 = lds32(ms + M_EP);
        const int pair = !is_ssm ? b : (pi == 0 ? 112 + 3 * (b - NMLP) : (b < NMLP + 12 ? 172 + 3 * (b - NMLP) : 184 + 2 * (b - NMLP))) + wg;
        const uint32_t work = is_ssm ? sb + S_WORK + wg * S_WGB : sb + OFF_A;
        const uint32_t z = work + SIG_V3 - 1024 + (t >> 6) * 4096 + (t & 63) * 16;
        sts128(z, 0u, 0u, 0u, 0u); sts128(z + SIG, 0u, 0u, 0u, 0u);
        if (t < 72) {
          const uint32_t zu = work + SIG_U + (t & 7) * U_LBO + (t >> 3) * 16;
          sts128(zu, 0u, 0u, 0u, 0u); sts128(zu + SIG, 0u, 0u, 0u, 0u);
        }
        const uint4* src = p.s->xnT + (size_t)pair * 512 + t;
#pragma unroll 1
        for (int it = 0; it < RETRY_MAX; it++) {
          uint32_t bad = 0;
#pragma unroll
          for (int q = 0; q < 4; q++) bad |= (((v[q].x ^ ep1) | (v[q].y ^ ep1) | (v[q].z ^ ep1) | (v[q].w ^ ep1)) & 1) << q;
          const unsigned m = __ballot_sync(0xffffffffu, bad);
          if (!m) break;
          if (lane == __ffs(m) - 1) poll_tag((const unsigned*)(src + (__ffs(bad) - 1) * 128) + 3, ep1);
          __syncwarp();
#pragma unroll
          for (int q = 0; q < 4; q++) v[q] = ld_relaxed4(src + q * 128);
        }
        TSTAMP(5);
        const uint32_t a = work + ((t >> 1) & 1) * SIG + SIG_U + (2 * ((t >> 2) & 3) + (t & 1)) * U_LBO + ((t >> 4) + 9) * 16;
#pragma unroll
        for (int q = 0; q < 4; q++) sts128(a + q * 128, v[q].x & ~1u, v[q].y & ~1u, v[q].z & ~1u, v[q].w & ~1u);
        bar_sync(4 + wg, 128);
#pragma unroll 1
        for (int k = w; k < 6; k += 4) sig_windows(work + (k & 1) * SIG, (k >> 1) * 32 + lane);
        fence_async();
        if (t == 96 && !is_ssm) { bulk_wait0(); red_release(&p.s->cntT); }
        if (pi == 1) mbar_wait(bar0 + 8 * wg, 0);
        TSTAMP(6);
        bar_sync(is_ssm ? 4 + wg : 3, is_ssm ? 128 : 384);
        TSTAMP(7);
      }
      uint32_t keep[8];
      float res[16];
#pragma unroll 1
      for (int c = 0; c < 2; c++) {
        IDS
        const uint32_t work = is_ssm ? sb + S_WORK + wg * S_WGB : sb + OFF_A;
        const uint32_t tbl = (is_ssm ? sb + (4 * wg + 2 * pi) * TBL : sb + OFF_T) + c * TBL;
        conv_channel(tbl, work + c * SIG, is_ssm ? work + 2 * SIG + Y3B : sb + OFF_B, work + 2 * SIG, lds32f(tbl + TBL_SC), w, lane, 4 + wg, res);
        TSTAMP(16 + 2 * pi + c);
        const float os = lds32f(tbl + TBL_SC + 4);
        if (c == 0) {
#pragma unroll
          for (int i = 0; i < 8; i++) keep[i] = pack_bf2(res[2 * i] * os, res[2 * i + 1] * os);
          if (is_ssm && pi == 0 && t == 96 && (b < NMLP + 12 || wg < 2)) {
            wait_count(&p.s->cntT, lds32(ms + M_EP) * NMLP);
            asm volatile("fence.proxy.async;" ::: "memory");
            mbar_expect(bar0 + 8 * wg, 2 * TBL);
            bulk_g2s(sb + (4 * wg + 2) * TBL, p.s->tbl + (2 * ((b < NMLP + 12 ? 172 + 3 * (b - NMLP) : 184 + 2 * (b - NMLP)) + wg) - 336) * (TBL / 16),
                     2 * TBL, bar0 + 8 * wg);
          }
          __syncwarp();
        } else {
          const int pair = !is_ssm ? b : (pi == 0 ? 112 + 3 * (b - NMLP) : (b < NMLP + 12 ? 172 + 3 * (b - NMLP) : 184 + 2 * (b - NMLP))) + wg;
          uint4* dst = p.s->s2 + ((size_t)(lane & 3) * 224 + pair) * 32 + w * 8 + (lane >> 2);
          const uint32_t tag = (lds32(ms + M_EP) & 1) * 0x10001u;
#pragma unroll
          for (int nt = 0; nt < 4; nt++) {
            const uint32_t n0 = pack_bf2(res[4 * nt] * os, res[4 * nt + 1] * os), n1 = pack_bf2(res[4 * nt + 2] * os, res[4 * nt + 3] * os);
            const uint32_t k0 = (keep[2 * nt] & 0xfffefffeu) | tag;
            asm volatile("{.reg .b64 a, c; mov.b64 a, {%1,%2}; mov.b64 c, {%3,%4}; st.relaxed.gpu.global.v2.b64 [%0], {a, c};}"
                         ::"l"(dst + nt * 4 * 224 * 32), "r"(__byte_perm(k0, n0, 0x5410)), "r"(__byte_perm(keep[2 * nt + 1], n1, 0x5410)),
                         "r"(__byte_perm(k0, n0, 0x7632)), "r"(__byte_perm(keep[2 * nt + 1], n1, 0x7632)) : "memory");
          }
        }
      }
      TSTAMP(8 + pi);
      TSDUMP();
      {
        IDS
        if (pi == 1 || !is_ssm || (b >= NMLP + 12 && wg == 2)) break;
        const uint4* src = p.s->xnT + (size_t)((b < NMLP + 12 ? 172 + 3 * (b - NMLP) : 184 + 2 * (b - NMLP)) + wg) * 512 + t;
#pragma unroll
        for (int q = 0; q < 4; q++) v[q] = ld_relaxed4(src + q * 128);
      }
    }
    if (b == 0 && tid0 == 256) {
      const unsigned ep1 = lds32(ms + M_EP);
      wait_count(&p.s->cntA, ep1 * NCTA);
      *(volatile unsigned*)&p.s->epoch = ep1;
    }
  } else {
    bar_arrive(1, 384);
    asm volatile("setmaxnreg.inc.sync.aligned.u32 192;");
    bar_sync(7, 384);
    uint32_t H[64];
    {
      float acc[128];
      float p0, q0, p1, q1;
      {
        IDS
        int sl = 0;
#pragma unroll 1
        for (int s = 0; s < 7; s++) {
          mbar_wait(bar0 + 8 * sl, (s >= 3 && s < 6));
          TSTAMP(17 + s);
          const uint64_t da = mkdesc(sb + OFF_X + sl * 16384 + wg * 8192, 16, 1024, 1);
          const uint64_t db = mkdesc(sb + OFF_W + sl * 32768, 8192, 1024, 1);
          wg_fence();
#pragma unroll
          for (int k = 0; k < 4; k++) wg_ss_bf16_n256(acc, da + 2 * k, db + 128 * k, (s | k) != 0);
          wg_commit();
          wg_wait<1>();
          const int pl = sl == 0 ? 2 : sl - 1;
          sl = sl == 2 ? 0 : sl + 1;
          if (s > 0 && lane == 0 && last_release(ms + M_REL + 4 * s)) {
            mbar_expect(bar0 + 8 * pl, s == 5 ? 32768 : 49152);
            if (s < 5) tma_3d(sb + OFF_W + pl * 32768, &tm_w1, 0, 64 * mod7(kc0 + s + 2), 4 * rk, bar0 + 8 * pl);
            else tma_2d(sb + OFF_W + pl * 32768, &tm_w2, 64 * mod7(rk + s - 4), 256 * rk, bar0 + 8 * pl);
            if (s != 5) tma_2d(sb + OFF_X + pl * 16384, &tm_x, 64 * (s < 5 ? mod7(kc0 + s + 2) : rk), 128 * G, bar0 + 8 * pl);
          }
        }
        TSTAMP(15);
        bar_sync(1, 384);
        wg_fence();
        wg_ss_bf16_n256k(acc, mkdesc(sb + OFF_B + B_AX + wg * 1024, 0, 128, 0), mkdesc(sb + OFF_B + B_BX, 4096, 128, 0), 1);
        wg_commit();
        wg_wait<1>();
        if (lane == 0 && last_release(ms + M_REL + 4 * 7)) {
          mbar_expect(bar0, 65536);
#pragma unroll 1
          for (int c = 2; c < 4; c++) tma_2d(sb + (c - 2) * OFF_X, &tm_w2, 64 * mod7(rk + 1 + c), 256 * rk, bar0);
        }
        bar_arrive(3, 384);
        const uint32_t ra = sb + OFF_B + B_AX + (16 * wi + (lane >> 2)) * 16;
        const float r0 = rcpf_(bf_hi(lds32(ra)) + bf_hi(lds32(ra + 8))), r1 = rcpf_(bf_hi(lds32(ra + 128)) + bf_hi(lds32(ra + 136)));
        p0 = 0.7978845608028654f * r0; q0 = 0.0356774081363001f * r0 * r0 * r0;
        p1 = 0.7978845608028654f * r1; q1 = 0.0356774081363001f * r1 * r1 * r1;
      }
      wg_wait<0>();
      fence_regs<128>(acc);
      TSTAMP(16);
#pragma unroll 1
      for (int hf = 0; hf < 2; hf++) {
        float th[8];
#pragma unroll
        for (int i = 0; i < 35; i++) {
          if (i < 32) {
            const float pp = (i & 1) ? p1 : p0, qq = (i & 1) ? q1 : q0;
            const float a = acc[2 * i], c = acc[2 * i + 1];
            th[2 * (i & 3)] = tanhf_(a * fmaf(a * a, qq, pp)); th[2 * (i & 3) + 1] = tanhf_(c * fmaf(c * c, qq, pp));
          }
          if (i >= 3) {
            const int j = i - 3;
            asm volatile("{.reg .f32 x, y; fma.rn.f32 x, %0, %5, %0; fma.rn.f32 y, %1, %6, %1; mov.f32 %0, %3; mov.f32 %1, %4;\n"
                         ".reg .b32 h; cvt.rn.bf16x2.f32 h, y, x; mov.b32 %2, h;}"
                         : "+f"(acc[2 * j]), "+f"(acc[2 * j + 1]), "=f"(acc[64 + j])
                         : "f"(acc[64 + 2 * j]), "f"(acc[65 + 2 * j]), "f"(th[2 * (j & 3)]), "f"(th[2 * (j & 3) + 1]));
          }
        }
      }
#pragma unroll
      for (int i = 0; i < 32; i++) { H[i] = __float_as_uint(acc[i]); H[32 + i] = __float_as_uint(acc[64 + i]); }
    }
    TSTAMP(3);
    IDS
    float acc[32], pre[32];
    uint32_t pk[16];
#pragma unroll
    for (int i = 0; i < 32; i++) pre[i] = 0.f;
    const uint32_t tag = lds32(ms + M_EP) & 1;
    const uint4* inbox = p.s->part + (size_t)b * 6 * 1024 + tid;
    auto recv = [&](int slot) {
      const uint4* src = inbox + slot * 1024;
      uint4 v[4];
#pragma unroll 1
      for (int it = 0; it < RETRY_MAX; it++) {
#pragma unroll
        for (int q = 0; q < 4; q++) v[q] = ld_b128(src + q * 256);
        const unsigned m = __ballot_sync(0xffffffffu, ((v[0].x ^ tag) | (v[1].x ^ tag) | (v[2].x ^ tag) | (v[3].x ^ tag)) & 1);
        if (!m) break;
        if (lane == __ffs(m) - 1) poll_tag((const unsigned*)(src + 768), tag);
        __syncwarp();
      }
#pragma unroll
      for (int q = 0; q < 4; q++) {
        const uint32_t u[4] = {v[q].x, v[q].y, v[q].z, v[q].w};
#pragma unroll
        for (int k = 0; k < 4; k++) { pre[8 * q + 2 * k] += bf_lo(u[k]); pre[8 * q + 2 * k + 1] += bf_hi(u[k]); }
      }
    };
#pragma unroll 1
    for (int s = 0; s < 7; s++) {
      if (s != 3) mbar_wait(bar0 + 8 * ((0x0210021u >> (4 * s)) & 3), (0x34 >> s) & 1);
      const uint64_t db = mkdesc(sb + ((0x0213021u >> (4 * s)) & 3) * 32768, 8192, 1024, 1);
      wg_fence();
#pragma unroll
      for (int k = 0; k < 16; k++) wg_rs_bf16_n64(acc, H[4 * k], H[4 * k + 1], H[4 * k + 2], H[4 * k + 3], db + 128 * k, k != 0);
      wg_commit();
      if (s > 0) {
        uint4* dst = p.s->part + ((size_t)(G * 7 + mod7(rk + s)) * 6 + s - 1) * 1024 + tid;
#pragma unroll
        for (int q = 0; q < 4; q++) st_b128(dst + q * 256, tag, pk[4 * q], pk[4 * q + 1], pk[4 * q + 2], pk[4 * q + 3]);
        if (s < 4 && lane == 0 && last_release(ms + M_REL + 4 * (7 + s))) {
          const int sl = (0x0210u >> (4 * s)) & 3;
          mbar_expect(bar0 + 8 * sl, 32768);
          tma_2d(sb + sl * 32768, &tm_w2, 64 * mod7(mod7(rk + 4 + s)), 256 * rk, bar0 + 8 * sl);
        }
        __syncwarp();
      }
      if (s >= 3) recv(s - 3);
      wg_wait<0>();
      fence_regs<32>(acc);
#pragma unroll
      for (int k = 0; k < 16; k++) pk[k] = pack_bf2(acc[2 * k], acc[2 * k + 1]);
      TSTAMP(4 + s);
    }
    {
      const uint2* sp = (const uint2*)(p.s->s2 + ((size_t)G * 224 + 32 * rk + (lane & 3)) * 32 + w * 8 + (lane >> 2)) + wg;
#pragma unroll 1
      for (int it = 0; it < RETRY_MAX; it++) {
#pragma unroll
        for (int i = 0; i < 8; i++)
          asm volatile("{.reg .b64 a; ld.relaxed.gpu.global.b64 a, [%2]; mov.b64 {%0,%1}, a;}"
                       : "=r"(pk[2 * i]), "=r"(pk[2 * i + 1]) : "l"(sp + i * 4 * 64) : "memory");
#pragma unroll 1
        for (int s = it ? 6 : 4; s < 6; s++) recv(s);
        uint32_t bad = 0;
#pragma unroll
        for (int i = 0; i < 8; i++) bad |= ((pk[2 * i] ^ tag) & 1) << i;
        const unsigned m = __ballot_sync(0xffffffffu, bad);
        if (!m) break;
        if (lane == __ffs(m) - 1) poll_tag((const unsigned*)(sp + (__ffs(bad) - 1) * 4 * 64), tag);
        __syncwarp();
      }
    }
    TSTAMP(12);
    const int g = lane >> 2, tq = lane & 3;
    const uint32_t xa = sb + OFF_X + 2 * 16384 + (16 * wi + (lane & 15)) * 128;
    uint32_t xw[16];
#pragma unroll
    for (int q = 0; q < 4; q++) ldsm4(xa + (((2 * q + (lane >> 4)) ^ (lane & 7)) << 4), xw[4 * q], xw[4 * q + 1], xw[4 * q + 2], xw[4 * q + 3]);
    const uint32_t ra = sb + OFF_B + B_AX + (16 * wi + g) * 16;
    const float r0 = 0.25f * rcpf_(bf_hi(lds32(ra)) + bf_hi(lds32(ra + 8))), r1 = 0.25f * rcpf_(bf_hi(lds32(ra + 128)) + bf_hi(lds32(ra + 136)));
#pragma unroll
    for (int i = 0; i < 8; i++) {
      const float2 bb = lds64f(ms + M_CSR + (8 * i + 2 * tq) * 4);
#pragma unroll
      for (int e = 0; e < 2; e++) {
        const int k = 2 * i + e;
        const float h0 = fmaf(acc[2 * k] + pre[2 * k], e ? r1 : r0, bb.x), h1 = fmaf(acc[2 * k + 1] + pre[2 * k + 1], e ? r1 : r0, bb.y);
        const uint32_t gw = pack_bf2(fmaf(h0, tanhf_(h0), h0), fmaf(h1, tanhf_(h1), h1));
        asm("fma.rn.bf16x2 %0, %1, %2, %0;" : "+r"(xw[k]) : "r"(pk[k]), "r"(gw));
      }
    }
#pragma unroll
    for (int q = 0; q < 4; q++) stsm4(xa + (((2 * q + (lane >> 4)) ^ (lane & 7)) << 4), xw[4 * q], xw[4 * q + 1], xw[4 * q + 2], xw[4 * q + 3]);
    fence_async();
    __syncwarp();
    if (lane == 0) {
      tma_store_2d(&tm_out, sb + OFF_X + 2 * 16384 + wi * 2048, 64 * rk, 128 * G + 16 * wi);
      bulk_commit();
      bulk_wait0_read();
    }
    TSTAMP(13);
    TSDUMP();
  }
}

typedef CUresult (*EncodeFn)(CUtensorMap*, CUtensorMapDataType, cuuint32_t, void*, const cuuint64_t*, const cuuint64_t*,
                             const cuuint32_t*, const cuuint32_t*, CUtensorMapInterleave, CUtensorMapSwizzle,
                             CUtensorMapL2promotion, CUtensorMapFloatOOBfill);

void make_map(EncodeFn fn, CUtensorMap* m, const void* ptr, int rank, const cuuint64_t* dims, const cuuint64_t* strides, const cuuint32_t* box) {
  const cuuint32_t es[3] = {1, 1, 1};
  fn(m, CU_TENSOR_MAP_DATA_TYPE_BFLOAT16, rank, const_cast<void*>(ptr), dims, strides, box, es, CU_TENSOR_MAP_INTERLEAVE_NONE,
     CU_TENSOR_MAP_SWIZZLE_128B, CU_TENSOR_MAP_L2_PROMOTION_L2_128B, CU_TENSOR_MAP_FLOAT_OOB_FILL_NONE);
}

}

extern "C" void kernel_launch(void* const* d_in, const int* in_sizes, int n_in, void* d_out, int out_size) {
  (void)in_sizes; (void)n_in; (void)out_size;
  void* fnp = nullptr;
  cudaDriverEntryPointQueryResult qr;
  cudaGetDriverEntryPoint("cuTensorMapEncodeTiled", &fnp, cudaEnableDefault, &qr);
  EncodeFn fn = (EncodeFn)fnp;
  Params p;
  p.x = (const __nv_bfloat16*)d_in[0];
  p.a_re = (const __nv_bfloat16*)d_in[1]; p.a_im = (const __nv_bfloat16*)d_in[2];
  p.b_re = (const __nv_bfloat16*)d_in[3]; p.b_im = (const __nv_bfloat16*)d_in[4];
  p.c_re = (const __nv_bfloat16*)d_in[5]; p.c_im = (const __nv_bfloat16*)d_in[6];
  p.log_dt = (const __nv_bfloat16*)d_in[7]; p.dskip = (const __nv_bfloat16*)d_in[8];
  p.w1 = (const __nv_bfloat16*)d_in[10]; p.b1 = (const __nv_bfloat16*)d_in[11];
  p.w2 = (const __nv_bfloat16*)d_in[12]; p.b2 = (const __nv_bfloat16*)d_in[13];
  void* sp = nullptr;
  cudaGetSymbolAddress(&sp, g_scr);
  p.s = (Scratch*)sp;
  CUtensorMap mx, mw1, mw2, mo;
  {
    const cuuint64_t dims[2] = {448, 2048}, str[1] = {896};
    const cuuint32_t box[2] = {64, 128}, boxo[2] = {64, 16};
    make_map(fn, &mx, p.x, 2, dims, str, box);
    make_map(fn, &mo, d_out, 2, dims, str, boxo);
  }
  {
    const cuuint64_t dims[3] = {64, 448, 28}, str[2] = {3584, 128};
    const cuuint32_t box[3] = {64, 64, 4};
    make_map(fn, &mw1, p.w1, 3, dims, str, box);
  }
  {
    const cuuint64_t dims[2] = {448, 1792}, str[1] = {896};
    const cuuint32_t box[2] = {64, 256};
    make_map(fn, &mw2, p.w2, 2, dims, str, box);
  }
  cudaFuncSetAttribute(fused_kernel, cudaFuncAttributeMaxDynamicSharedMemorySize, SMEM_BYTES);
  fused_kernel<<<NCTA, 384, SMEM_BYTES>>>(p, mx, mw1, mw2, mo);
}
```

```cpp
#include <cuda_runtime.h>
#include <cuda_bf16.h>
#include <cuda_fp16.h>
#include <cuda.h>
#include <stdint.h>

namespace {

constexpr int D_ = 448, NST = 256, F_ = 1792;
constexpr int NRK = 7, NMLP = 112, NCTA = 132;
constexpr int SPIN_MAX = 1 << 20, RETRY_MAX = 512;

struct Scratch {
  unsigned cntA, pad0[31], cntT, pad1[31], epoch, pad2[63];
  uint4 ax[2048];
  uint4 bx[7 * 512];
  uint4 tbl[112 * 329];
  uint4 xnT[224 * 512];
  uint4 s2[16 * 224 * 32];
  uint4 part[16 * 7 * 6 * 1024];
};
__device__ Scratch g_scr;
#define TSTAMP(i)
#define TSINIT()
#define TSDUMP()
extern __shared__ __align__(1024) uint8_t smem_raw[];

constexpr int TBL_SC = 5248, TBL = 5264;
constexpr int TBL_C1 = 2624;
constexpr int SIG = 19584;
constexpr int SIG_U = 0, U_LBO = 656, SIG_V3 = 6272, SIG_V5 = 10368, SIG_V7 = 13440, SIG_V9 = 15488, SIG_V2 = 17536;
constexpr int Y2B = 6528, Y3B = 4352;
constexpr int KSTG = 14 * 2048;
constexpr int OFF_W = 0, OFF_X = 98304, OFF_A = 147456, OFF_B = OFF_A + 2 * SIG + Y3B, OFF_T = OFF_B + 16896;
constexpr int OFF_M = OFF_T + 15872;
constexpr int B_AX = Y2B, B_BX = B_AX + 2048;
constexpr int M_BAR = 0, M_REL = 128, M_EP = 192, M_CSR = 256, M_LT = 1280, M_MX = 1536, M_END = 1664;
constexpr int SMEM_BYTES = OFF_M + M_END + 384;
constexpr int S_WORK = 63232, S_WGB = 2 * SIG + Y2B + Y3B;
static_assert(OFF_A + 2 * KSTG <= OFF_T && S_WORK + 3 * S_WGB <= OFF_M && SMEM_BYTES <= 232448, "smem");

struct Params {
  const __nv_bfloat16 *x, *a_re, *a_im, *b_re, *b_im, *c_re, *c_im, *log_dt, *dskip, *w1, *b1, *w2, *b2;
  Scratch* s;
};

__device__ __forceinline__ int opaque(int x) { int v; asm volatile("mov.u32 %0, %1;" : "=r"(v) : "r"(x)); return v; }
__device__ __forceinline__ int rd_bid() { int v; asm volatile("mov.u32 %0, %%ctaid.x;" : "=r"(v)); return v; }
__device__ __forceinline__ uint32_t smem_u32(const void* p) { return (uint32_t)__cvta_generic_to_shared(p); }
__device__ __forceinline__ void mbar_init(uint32_t bar, int cnt) { asm volatile("mbarrier.init.shared::cta.b64 [%0], %1;" ::"r"(bar), "r"(cnt)); }
__device__ __forceinline__ void mbar_expect(uint32_t bar, uint32_t bytes) {
  asm volatile("mbarrier.arrive.expect_tx.shared::cta.b64 _, [%0], %1;" ::"r"(bar), "r"(bytes) : "memory");
}
__device__ __forceinline__ void mbar_wait(uint32_t bar, uint32_t parity) {
  uint32_t done = 0;
#pragma unroll 1
  for (int it = 0; it < SPIN_MAX; it++) {
    asm volatile("{.reg .pred p; mbarrier.try_wait.parity.shared::cta.b64 p, [%1], %2; selp.u32 %0,1,0,p;}"
                 : "=r"(done) : "r"(bar), "r"(parity) : "memory");
    if (done) break;
  }
}
__device__ __forceinline__ void tma_2d(uint32_t dst, const CUtensorMap* m, int c0, int c1, uint32_t bar) {
  asm volatile("cp.async.bulk.tensor.2d.shared::cluster.global.mbarrier::complete_tx::bytes [%0], [%1, {%3, %4}], [%2];"
               ::"r"(dst), "l"(m), "r"(bar), "r"(c0), "r"(c1) : "memory");
}
__device__ __forceinline__ void tma_3d(uint32_t dst, const CUtensorMap* m, int c0, int c1, int c2, uint32_t bar) {
  asm volatile("cp.async.bulk.tensor.3d.shared::cluster.global.mbarrier::complete_tx::bytes [%0], [%1, {%3, %4, %5}], [%2];"
               ::"r"(dst), "l"(m), "r"(bar), "r"(c0), "r"(c1), "r"(c2) : "memory");
}
__device__ __forceinline__ void tma_store_2d(const CUtensorMap* m, uint32_t src, int c0, int c1) {
  asm volatile("cp.async.bulk.tensor.2d.global.shared::cta.bulk_group [%0, {%2, %3}], [%1];"
               ::"l"(m), "r"(src), "r"(c0), "r"(c1) : "memory");
}
__device__ __forceinline__ void bulk_s2g(void* dst, uint32_t src, uint32_t bytes) {
  asm volatile("cp.async.bulk.global.shared::cta.bulk_group [%0], [%1], %2;" ::"l"(dst), "r"(src), "r"(bytes) : "memory");
}
__device__ __forceinline__ void bulk_g2s(uint32_t dst, const void* src, uint32_t bytes, uint32_t bar) {
  asm volatile("cp.async.bulk.shared::cluster.global.mbarrier::complete_tx::bytes [%0], [%1], %2, [%3];"
               ::"r"(dst), "l"(src), "r"(bytes), "r"(bar) : "memory");
}
__device__ __forceinline__ void bulk_commit() { asm volatile("cp.async.bulk.commit_group;" ::: "memory"); }
__device__ __forceinline__ void bulk_wait0() { asm volatile("cp.async.bulk.wait_group 0;" ::: "memory"); }
__device__ __forceinline__ void bulk_wait0_read() { asm volatile("cp.async.bulk.wait_group.read 0;" ::: "memory"); }
__device__ __forceinline__ void fence_async() { asm volatile("fence.proxy.async.shared::cta;" ::: "memory"); }
__device__ __forceinline__ void bar_sync(int id, int n) { asm volatile("bar.sync %0, %1;" ::"r"(id), "r"(n) : "memory"); }
__device__ __forceinline__ void bar_arrive(int id, int n) { asm volatile("bar.arrive %0, %1;" ::"r"(id), "r"(n) : "memory"); }
__device__ __forceinline__ void wg_fence() { asm volatile("wgmma.fence.sync.aligned;" ::: "memory"); }
__device__ __forceinline__ void wg_commit() { asm volatile("wgmma.commit_group.sync.aligned;" ::: "memory"); }
template <int N> __device__ __forceinline__ void wg_wait() { asm volatile("wgmma.wait_group.sync.aligned %0;" ::"n"(N) : "memory"); }
template <int N> __device__ __forceinline__ void fence_regs(float* d) {
#pragma unroll
  for (int i = 0; i < N; i++) asm volatile("" : "+f"(d[i])::"memory");
}
__device__ __forceinline__ uint64_t mkdesc(uint32_t addr, uint32_t lbo, uint32_t sbo, uint32_t sw) {
  return (uint64_t)((addr & 0x3FFFF) >> 4) | ((uint64_t)(lbo >> 4) << 16) | ((uint64_t)(sbo >> 4) << 32) | ((uint64_t)sw << 62);
}
__device__ __forceinline__ uint32_t lds32(uint32_t a) { uint32_t v; asm volatile("ld.shared.b32 %0, [%1];" : "=r"(v) : "r"(a) : "memory"); return v; }
__device__ __forceinline__ float lds32f(uint32_t a) { float v; asm volatile("ld.shared.f32 %0, [%1];" : "=f"(v) : "r"(a) : "memory"); return v; }
__device__ __forceinline__ float2 lds64f(uint32_t a) { float2 v; asm volatile("ld.shared.v2.f32 {%0,%1}, [%2];" : "=f"(v.x), "=f"(v.y) : "r"(a) : "memory"); return v; }
__device__ __forceinline__ uint4 lds128(uint32_t a) {
  uint4 v; asm volatile("ld.shared.v4.b32 {%0,%1,%2,%3}, [%4];" : "=r"(v.x), "=r"(v.y), "=r"(v.z), "=r"(v.w) : "r"(a) : "memory"); return v;
}
__device__ __forceinline__ void sts16(uint32_t a, uint16_t v) { asm volatile("st.shared.b16 [%0], %1;" ::"r"(a), "h"(v) : "memory"); }
__device__ __forceinline__ void sts32f(uint32_t a, float v) { asm volatile("st.shared.f32 [%0], %1;" ::"r"(a), "f"(v) : "memory"); }
__device__ __forceinline__ void sts64f(uint32_t a, float x, float y) { asm volatile("st.shared.v2.f32 [%0], {%1,%2};" ::"r"(a), "f"(x), "f"(y) : "memory"); }
__device__ __forceinline__ void sts128(uint32_t a, uint32_t x, uint32_t y, uint32_t z, uint32_t w) {
  asm volatile("st.shared.v4.b32 [%0], {%1,%2,%3,%4};" ::"r"(a), "r"(x), "r"(y), "r"(z), "r"(w) : "memory");
}
__device__ __forceinline__ void ldsm4(uint32_t a, uint32_t& r0, uint32_t& r1, uint32_t& r2, uint32_t& r3) {
  asm volatile("ldmatrix.sync.aligned.m8n8.x4.shared.b16 {%0,%1,%2,%3}, [%4];" : "=r"(r0), "=r"(r1), "=r"(r2), "=r"(r3) : "r"(a) : "memory");
}
__device__ __forceinline__ void ldsm4t(uint32_t a, uint32_t& r0, uint32_t& r1, uint32_t& r2, uint32_t& r3) {
  asm volatile("ldmatrix.sync.aligned.m8n8.x4.trans.shared.b16 {%0,%1,%2,%3}, [%4];" : "=r"(r0), "=r"(r1), "=r"(r2), "=r"(r3) : "r"(a) : "memory");
}
__device__ __forceinline__ void ldsm2t(uint32_t a, uint32_t& r0, uint32_t& r1) {
  asm volatile("ldmatrix.sync.aligned.m8n8.x2.trans.shared.b16 {%0,%1}, [%2];" : "=r"(r0), "=r"(r1) : "r"(a) : "memory");
}
__device__ __forceinline__ void stsm4(uint32_t a, uint32_t r0, uint32_t r1, uint32_t r2, uint32_t r3) {
  asm volatile("stmatrix.sync.aligned.m8n8.x4.shared.b16 [%0], {%1,%2,%3,%4};" ::"r"(a), "r"(r0), "r"(r1), "r"(r2), "r"(r3) : "memory");
}
__device__ __forceinline__ void mma_f16(float* c, uint32_t a0, uint32_t a1, uint32_t a2, uint32_t a3, uint32_t b0, uint32_t b1) {
  asm("mma.sync.aligned.m16n8k16.row.col.f32.f16.f16.f32 {%0,%1,%2,%3},{%4,%5,%6,%7},{%8,%9},{%0,%1,%2,%3};"
               : "+f"(c[0]), "+f"(c[1]), "+f"(c[2]), "+f"(c[3]) : "r"(a0), "r"(a1), "r"(a2), "r"(a3), "r"(b0), "r"(b1));
}
__device__ __forceinline__ void mma_bf16(float* c, uint32_t a0, uint32_t a1, uint32_t a2, uint32_t a3, uint32_t b0, uint32_t b1) {
  asm("mma.sync.aligned.m16n8k16.row.col.f32.bf16.bf16.f32 {%0,%1,%2,%3},{%4,%5,%6,%7},{%8,%9},{%0,%1,%2,%3};"
      : "+f"(c[0]), "+f"(c[1]), "+f"(c[2]), "+f"(c[3]) : "r"(a0), "r"(a1), "r"(a2), "r"(a3), "r"(b0), "r"(b1));
}
__device__ __forceinline__ uint4 ld_relaxed4(const void* p) {
  uint4 v; asm volatile("ld.relaxed.gpu.global.v4.b32 {%0,%1,%2,%3}, [%4];" : "=r"(v.x), "=r"(v.y), "=r"(v.z), "=r"(v.w) : "l"(p) : "memory"); return v;
}
__device__ __forceinline__ uint4 ld_2x64(const void* p) {
  uint4 v;
  asm volatile("{.reg .b64 a, c; ld.relaxed.gpu.global.v2.b64 {a, c}, [%4]; mov.b64 {%0,%1}, a; mov.b64 {%2,%3}, c;}"
               : "=r"(v.x), "=r"(v.y), "=r"(v.z), "=r"(v.w) : "l"(p) : "memory");
  return v;
}
__device__ __forceinline__ void st_relaxed2(void* p, uint32_t x, uint32_t y) {
  asm volatile("st.relaxed.gpu.global.v2.b32 [%0], {%1,%2};" ::"l"(p), "r"(x), "r"(y) : "memory");
}
__device__ __forceinline__ uint4 ld_b128(const void* p) {
  uint4 v;
  asm volatile("{.reg .b128 t; .reg .b64 a, c; ld.relaxed.gpu.global.b128 t, [%4]; mov.b128 {a, c}, t; mov.b64 {%0,%1}, a; mov.b64 {%2,%3}, c;}"
               : "=r"(v.x), "=r"(v.y), "=r"(v.z), "=r"(v.w) : "l"(p) : "memory");
  return v;
}
__device__ __forceinline__ void st_b128(void* p, uint32_t tag, uint32_t x, uint32_t y, uint32_t z, uint32_t w) {
  asm volatile("{.reg .b128 t; .reg .b64 a, c; mov.b64 a, {%1,%2}; mov.b64 c, {%3,%4}; mov.b128 t, {a, c}; st.relaxed.gpu.global.b128 [%0], t;}"
               ::"l"(p), "r"((x & ~1u) | tag), "r"(y), "r"(z), "r"(w) : "memory");
}
__device__ __forceinline__ unsigned ld_relaxed1(const unsigned* p) {
  unsigned v; asm volatile("ld.relaxed.gpu.global.u32 %0, [%1];" : "=r"(v) : "l"(p) : "memory"); return v;
}
__device__ __forceinline__ void red_relaxed(unsigned* p) {
  asm volatile("red.relaxed.gpu.global.add.u32 [%0], 1;" ::"l"(p) : "memory");
}
__device__ __forceinline__ void red_release(unsigned* p) {
  asm volatile("red.release.gpu.global.add.u32 [%0], 1;" ::"l"(p) : "memory");
}
__device__ __forceinline__ void wait_count(const unsigned* p, unsigned target) {
#pragma unroll 1
  for (int it = 0; it < SPIN_MAX; it++) {
    if ((int)(ld_relaxed1(p) - target) >= 0) break;
    __nanosleep(40);
  }
  asm volatile("fence.acq_rel.gpu;" ::: "memory");
}
__device__ __forceinline__ uint32_t pack_h2(float lo, float hi) { uint32_t r; asm("cvt.rn.f16x2.f32 %0, %1, %2;" : "=r"(r) : "f"(hi), "f"(lo)); return r; }
__device__ __forceinline__ uint32_t pack_bf2(float lo, float hi) { uint32_t r; asm("cvt.rn.bf16x2.f32 %0, %1, %2;" : "=r"(r) : "f"(hi), "f"(lo)); return r; }
__device__ __forceinline__ float bf_lo(uint32_t w) { return __uint_as_float(w << 16); }
__device__ __forceinline__ float bf_hi(uint32_t w) { return __uint_as_float(w & 0xffff0000u); }
__device__ __forceinline__ float rbf(float v) { return __bfloat162float(__float2bfloat16_rn(v)); }
__device__ __forceinline__ float2 h2f(uint32_t w) { return __half22float2(*reinterpret_cast<__half2*>(&w)); }
__device__ __forceinline__ float ex2f(float v) { float r; asm("ex2.approx.ftz.f32 %0, %1;" : "=f"(r) : "f"(v)); return r; }
__device__ __forceinline__ float rcpf_(float v) { float r; asm("rcp.approx.f32 %0, %1;" : "=f"(r) : "f"(v)); return r; }
__device__ __forceinline__ float sqrtf_(float v) { float r; asm("sqrt.approx.f32 %0, %1;" : "=f"(r) : "f"(v)); return r; }
__device__ __forceinline__ float tanhf_(float v) { float r; asm volatile("tanh.approx.f32 %0, %1;" : "=f"(r) : "f"(v)); return r; }

__device__ __forceinline__ void wg_ss_bf16_n256(float* d, uint64_t da, uint64_t db, int sc) {
  asm volatile("{.reg .pred p; setp.ne.b32 p, %130, 0;\n"
    "wgmma.mma_async.sync.aligned.m64n256k16.f32.bf16.bf16 {%0, %1, %2, %3, %4, %5, %6, %7, %8, %9, %10, %11, %12, %13, %14, %15, %16, %17, %18, %19, %20, %21, %22, %23, %24, %25, %26, %27, %28, %29, %30, %31, %32, %33, %34, %35, %36, %37, %38, %39, %40, %41, %42, %43, %44, %45, %46, %47, %48, %49, %50, %51, %52, %53, %54, %55, %56, %57, %58, %59, %60, %61, %62, %63, %64, %65, %66, %67, %68, %69, %70, %71, %72, %73, %74, %75, %76, %77, %78, %79, %80, %81, %82, %83, %84, %85, %86, %87, %88, %89, %90, %91, %92, %93, %94, %95, %96, %97, %98, %99, %100, %101, %102, %103, %104, %105, %106, %107, %108, %109, %110, %111, %112, %113, %114, %115, %116, %117, %118, %119, %120, %121, %122, %123, %124, %125, %126, %127}, %128, %129, p, 1, 1, 0, 1;}\n"
    : "+f"(d[0]), "+f"(d[1]), "+f"(d[2]), "+f"(d[3]), "+f"(d[4]), "+f"(d[5]), "+f"(d[6]), "+f"(d[7]), "+f"(d[8]), "+f"(d[9]), "+f"(d[10]), "+f"(d[11]), "+f"(d[12]), "+f"(d[13]), "+f"(d[14]), "+f"(d[15]), "+f"(d[16]), "+f"(d[17]), "+f"(d[18]), "+f"(d[19]), "+f"(d[20]), "+f"(d[21]), "+f"(d[22]), "+f"(d[23]), "+f"(d[24]), "+f"(d[25]), "+f"(d[26]), "+f"(d[27]), "+f"(d[28]), "+f"(d[29]), "+f"(d[30]), "+f"(d[31]), "+f"(d[32]), "+f"(d[33]), "+f"(d[34]), "+f"(d[35]), "+f"(d[36]), "+f"(d[37]), "+f"(d[38]), "+f"(d[39]), "+f"(d[40]), "+f"(d[41]), "+f"(d[42]), "+f"(d[43]), "+f"(d[44]), "+f"(d[45]), "+f"(d[46]), "+f"(d[47]), "+f"(d[48]), "+f"(d[49]), "+f"(d[50]), "+f"(d[51]), "+f"(d[52]), "+f"(d[53]), "+f"(d[54]), "+f"(d[55]), "+f"(d[56]), "+f"(d[57]), "+f"(d[58]), "+f"(d[59]), "+f"(d[60]), "+f"(d[61]), "+f"(d[62]), "+f"(d[63]), "+f"(d[64]), "+f"(d[65]), "+f"(d[66]), "+f"(d[67]), "+f"(d[68]), "+f"(d[69]), "+f"(d[70]), "+f"(d[71]), "+f"(d[72]), "+f"(d[73]), "+f"(d[74]), "+f"(d[75]), "+f"(d[76]), "+f"(d[77]), "+f"(d[78]), "+f"(d[79]), "+f"(d[80]), "+f"(d[81]), "+f"(d[82]), "+f"(d[83]), "+f"(d[84]), "+f"(d[85]), "+f"(d[86]), "+f"(d[87]), "+f"(d[88]), "+f"(d[89]), "+f"(d[90]), "+f"(d[91]), "+f"(d[92]), "+f"(d[93]), "+f"(d[94]), "+f"(d[95]), "+f"(d[96]), "+f"(d[97]), "+f"(d[98]), "+f"(d[99]), "+f"(d[100]), "+f"(d[101]), "+f"(d[102]), "+f"(d[103]), "+f"(d[104]), "+f"(d[105]), "+f"(d[106]), "+f"(d[107]), "+f"(d[108]), "+f"(d[109]), "+f"(d[110]), "+f"(d[111]), "+f"(d[112]), "+f"(d[113]), "+f"(d[114]), "+f"(d[115]), "+f"(d[116]), "+f"(d[117]), "+f"(d[118]), "+f"(d[119]), "+f"(d[120]), "+f"(d[121]), "+f"(d[122]), "+f"(d[123]), "+f"(d[124]), "+f"(d[125]), "+f"(d[126]), "+f"(d[127])
    : "l"(da), "l"(db), "r"(sc));
}

__device__ __forceinline__ void wg_ss_bf16_n256k(float* d, uint64_t da, uint64_t db, int sc) {
  asm volatile("{.reg .pred p; setp.ne.b32 p, %130, 0;\n"
    "wgmma.mma_async.sync.aligned.m64n256k16.f32.bf16.bf16 {%0, %1, %2, %3, %4, %5, %6, %7, %8, %9, %10, %11, %12, %13, %14, %15, %16, %17, %18, %19, %20, %21, %22, %23, %24, %25, %26, %27, %28, %29, %30, %31, %32, %33, %34, %35, %36, %37, %38, %39, %40, %41, %42, %43, %44, %45, %46, %47, %48, %49, %50, %51, %52, %53, %54, %55, %56, %57, %58, %59, %60, %61, %62, %63, %64, %65, %66, %67, %68, %69, %70, %71, %72, %73, %74, %75, %76, %77, %78, %79, %80, %81, %82, %83, %84, %85, %86, %87, %88, %89, %90, %91, %92, %93, %94, %95, %96, %97, %98, %99, %100, %101, %102, %103, %104, %105, %106, %107, %108, %109, %110, %111, %112, %113, %114, %115, %116, %117, %118, %119, %120, %121, %122, %123, %124, %125, %126, %127}, %128, %129, p, 1, 1, 0, 0;}\n"
    : "+f"(d[0]), "+f"(d[1]), "+f"(d[2]), "+f"(d[3]), "+f"(d[4]), "+f"(d[5]), "+f"(d[6]), "+f"(d[7]), "+f"(d[8]), "+f"(d[9]), "+f"(d[10]), "+f"(d[11]), "+f"(d[12]), "+f"(d[13]), "+f"(d[14]), "+f"(d[15]), "+f"(d[16]), "+f"(d[17]), "+f"(d[18]), "+f"(d[19]), "+f"(d[20]), "+f"(d[21]), "+f"(d[22]), "+f"(d[23]), "+f"(d[24]), "+f"(d[25]), "+f"(d[26]), "+f"(d[27]), "+f"(d[28]), "+f"(d[29]), "+f"(d[30]), "+f"(d[31]), "+f"(d[32]), "+f"(d[33]), "+f"(d[34]), "+f"(d[35]), "+f"(d[36]), "+f"(d[37]), "+f"(d[38]), "+f"(d[39]), "+f"(d[40]), "+f"(d[41]), "+f"(d[42]), "+f"(d[43]), "+f"(d[44]), "+f"(d[45]), "+f"(d[46]), "+f"(d[47]), "+f"(d[48]), "+f"(d[49]), "+f"(d[50]), "+f"(d[51]), "+f"(d[52]), "+f"(d[53]), "+f"(d[54]), "+f"(d[55]), "+f"(d[56]), "+f"(d[57]), "+f"(d[58]), "+f"(d[59]), "+f"(d[60]), "+f"(d[61]), "+f"(d[62]), "+f"(d[63]), "+f"(d[64]), "+f"(d[65]), "+f"(d[66]), "+f"(d[67]), "+f"(d[68]), "+f"(d[69]), "+f"(d[70]), "+f"(d[71]), "+f"(d[72]), "+f"(d[73]), "+f"(d[74]), "+f"(d[75]), "+f"(d[76]), "+f"(d[77]), "+f"(d[78]), "+f"(d[79]), "+f"(d[80]), "+f"(d[81]), "+f"(d[82]), "+f"(d[83]), "+f"(d[84]), "+f"(d[85]), "+f"(d[86]), "+f"(d[87]), "+f"(d[88]), "+f"(d[89]), "+f"(d[90]), "+f"(d[91]), "+f"(d[92]), "+f"(d[93]), "+f"(d[94]), "+f"(d[95]), "+f"(d[96]), "+f"(d[97]), "+f"(d[98]), "+f"(d[99]), "+f"(d[100]), "+f"(d[101]), "+f"(d[102]), "+f"(d[103]), "+f"(d[104]), "+f"(d[105]), "+f"(d[106]), "+f"(d[107]), "+f"(d[108]), "+f"(d[109]), "+f"(d[110]), "+f"(d[111]), "+f"(d[112]), "+f"(d[113]), "+f"(d[114]), "+f"(d[115]), "+f"(d[116]), "+f"(d[117]), "+f"(d[118]), "+f"(d[119]), "+f"(d[120]), "+f"(d[121]), "+f"(d[122]), "+f"(d[123]), "+f"(d[124]), "+f"(d[125]), "+f"(d[126]), "+f"(d[127])
    : "l"(da), "l"(db), "r"(sc));
}

__device__ __forceinline__ void wg_rs_bf16_n64(float* d, uint32_t a0, uint32_t a1, uint32_t a2, uint32_t a3, uint64_t db, int sc) {
  asm volatile("{.reg .pred p; setp.ne.b32 p, %37, 0;\n"
    "wgmma.mma_async.sync.aligned.m64n64k16.f32.bf16.bf16 {%0, %1, %2, %3, %4, %5, %6, %7, %8, %9, %10, %11, %12, %13, %14, %15, %16, %17, %18, %19, %20, %21, %22, %23, %24, %25, %26, %27, %28, %29, %30, %31}, {%32,%33,%34,%35}, %36, p, 1, 1, 1;}\n"
    : "+f"(d[0]), "+f"(d[1]), "+f"(d[2]), "+f"(d[3]), "+f"(d[4]), "+f"(d[5]), "+f"(d[6]), "+f"(d[7]), "+f"(d[8]), "+f"(d[9]), "+f"(d[10]), "+f"(d[11]), "+f"(d[12]), "+f"(d[13]), "+f"(d[14]), "+f"(d[15]), "+f"(d[16]), "+f"(d[17]), "+f"(d[18]), "+f"(d[19]), "+f"(d[20]), "+f"(d[21]), "+f"(d[22]), "+f"(d[23]), "+f"(d[24]), "+f"(d[25]), "+f"(d[26]), "+f"(d[27]), "+f"(d[28]), "+f"(d[29]), "+f"(d[30]), "+f"(d[31])
    : "r"(a0), "r"(a1), "r"(a2), "r"(a3), "l"(db), "r"(sc));
}

__device__ __forceinline__ void wg_rs_f16_n32k(float* d, uint32_t a0, uint32_t a1, uint32_t a2, uint32_t a3, uint64_t db, int sc) {
  asm volatile("{.reg .pred p; setp.ne.b32 p, %21, 0;\n"
    "wgmma.mma_async.sync.aligned.m64n32k16.f32.f16.f16 {%0, %1, %2, %3, %4, %5, %6, %7, %8, %9, %10, %11, %12, %13, %14, %15}, {%16,%17,%18,%19}, %20, p, 1, 1, 0;}\n"
    : "+f"(d[0]), "+f"(d[1]), "+f"(d[2]), "+f"(d[3]), "+f"(d[4]), "+f"(d[5]), "+f"(d[6]), "+f"(d[7]), "+f"(d[8]), "+f"(d[9]), "+f"(d[10]), "+f"(d[11]), "+f"(d[12]), "+f"(d[13]), "+f"(d[14]), "+f"(d[15])
    : "r"(a0), "r"(a1), "r"(a2), "r"(a3), "l"(db), "r"(sc));
}

__device__ __forceinline__ void wg_rs_f16_n24t(float* d, uint32_t a0, uint32_t a1, uint32_t a2, uint32_t a3, uint64_t db, int sc) {
  asm volatile("{.reg .pred p; setp.ne.b32 p, %17, 0;\n"
    "wgmma.mma_async.sync.aligned.m64n24k16.f32.f16.f16 {%0, %1, %2, %3, %4, %5, %6, %7, %8, %9, %10, %11}, {%12,%13,%14,%15}, %16, p, 1, 1, 1;}\n"
    : "+f"(d[0]), "+f"(d[1]), "+f"(d[2]), "+f"(d[3]), "+f"(d[4]), "+f"(d[5]), "+f"(d[6]), "+f"(d[7]), "+f"(d[8]), "+f"(d[9]), "+f"(d[10]), "+f"(d[11])
    : "r"(a0), "r"(a1), "r"(a2), "r"(a3), "l"(db), "r"(sc));
}

__device__ __forceinline__ void wg_rs_f16_n16t(float* d, uint32_t a0, uint32_t a1, uint32_t a2, uint32_t a3, uint64_t db, int sc) {
  asm volatile("{.reg .pred p; setp.ne.b32 p, %13, 0;\n"
    "wgmma.mma_async.sync.aligned.m64n16k16.f32.f16.f16 {%0, %1, %2, %3, %4, %5, %6, %7}, {%8,%9,%10,%11}, %12, p, 1, 1, 1;}\n"
    : "+f"(d[0]), "+f"(d[1]), "+f"(d[2]), "+f"(d[3]), "+f"(d[4]), "+f"(d[5]), "+f"(d[6]), "+f"(d[7])
    : "r"(a0), "r"(a1), "r"(a2), "r"(a3), "l"(db), "r"(sc));
}

__device__ __forceinline__ void wg_ss_f16_n48t(float* d, uint64_t da, uint64_t db, int sc) {
  asm volatile("{.reg .pred p; setp.ne.b32 p, %26, 0;\n"
    "wgmma.mma_async.sync.aligned.m64n48k16.f32.f16.f16 {%0, %1, %2, %3, %4, %5, %6, %7, %8, %9, %10, %11, %12, %13, %14, %15, %16, %17, %18, %19, %20, %21, %22, %23}, %24, %25, p, 1, 1, 1, 1;}\n"
    : "+f"(d[0]), "+f"(d[1]), "+f"(d[2]), "+f"(d[3]), "+f"(d[4]), "+f"(d[5]), "+f"(d[6]), "+f"(d[7]), "+f"(d[8]), "+f"(d[9]), "+f"(d[10]), "+f"(d[11]), "+f"(d[12]), "+f"(d[13]), "+f"(d[14]), "+f"(d[15]), "+f"(d[16]), "+f"(d[17]), "+f"(d[18]), "+f"(d[19]), "+f"(d[20]), "+f"(d[21]), "+f"(d[22]), "+f"(d[23])
    : "l"(da), "l"(db), "r"(sc));
}

struct cf { float x, y; };
__device__ __forceinline__ cf cmul(cf a, cf b) { cf r; r.x = fmaf(a.x, b.x, -a.y * b.y); r.y = fmaf(a.x, b.y, a.y * b.x); return r; }
__device__ __forceinline__ cf zpow(float rho2, float phi, float e) {
  const float m = ex2f(rho2 * e), ang = phi * e;
  cf r; r.x = m * __cosf(ang); r.y = m * __sinf(ang); return r;
}
__device__ __forceinline__ __half2 H2(uint32_t v) { return *reinterpret_cast<__half2*>(&v); }
__device__ __forceinline__ uint32_t U32(__half2 v) { return *reinterpret_cast<uint32_t*>(&v); }
template <bool CONJ>
__device__ __forceinline__ void hprod2(uint32_t re, uint32_t im, uint32_t r, uint32_t& ore, uint32_t& oim) {
  const __half2 rx = __low2half2(H2(r)), ry = __high2half2(H2(r));
  if (CONJ) {
    ore = U32(__hfma2(H2(re), rx, __hmul2(H2(im), ry)));
    oim = U32(__hfma2(H2(im), rx, __hneg2(__hmul2(H2(re), ry))));
  } else {
    ore = U32(__hfma2(H2(re), rx, __hneg2(__hmul2(H2(im), ry))));
    oim = U32(__hfma2(H2(re), ry, __hmul2(H2(im), rx)));
  }
}
__device__ __forceinline__ cf csq(cf a) { cf r; r.x = fmaf(a.x, a.x, -a.y * a.y); r.y = (a.x + a.x) * a.y; return r; }
__device__ __forceinline__ cf cmulc(cf a, cf b) { cf r; r.x = fmaf(a.x, b.x, a.y * b.y); r.y = fmaf(a.y, b.x, -a.x * b.y); return r; }
__device__ __forceinline__ uint32_t pk(cf a) { return pack_h2(a.x, a.y); }
__device__ __forceinline__ uint32_t ldg32(const void* p, int o) { uint32_t v; asm volatile("ld.global.nc.b32 %0, [%1];" : "=r"(v) : "l"((const char*)p + o)); return v; }
__device__ __forceinline__ uint32_t hadd2u(uint32_t a, uint32_t b) { return U32(__hadd2(H2(a), H2(b))); }

struct KgIn { uint32_t cur[6], nxt[6], ldt, dk; bool odd; };
__device__ __forceinline__ float pow2_floor(float v) { return __uint_as_float(__float_as_uint(fminf(fmaxf(v, 1e-30f), 1e30f)) & 0x7f800000u); }
template <class Mid>
__device__ __forceinline__ void kgen_wg(KgIn& k, int nw, uint32_t stg, uint32_t tbl, uint32_t mxa, int w, int lane, int barid, Mid mid) {
  float dl, dt, inv_sc;
  {
    const uint32_t M = 0x7fff7fffu;
    uint32_t mx[2];
#pragma unroll
    for (int i = 0; i < 2; i++) {
      const uint32_t m = __vmaxu2(__vmaxu2(k.cur[2 + 2 * i] & M, k.cur[3 + 2 * i] & M), __vmaxu2(k.nxt[2 + 2 * i] & M, k.nxt[3 + 2 * i] & M));
      mx[i] = __reduce_max_sync(0xffffffffu, max(m << 16, m & 0xffff0000u));
    }
    if (lane == 0) sts32f(mxa + w * 4, __uint_as_float(mx[0]) * __uint_as_float(mx[1]));
    dt = rbf(ex2f((k.odd ? bf_hi(k.ldt) : bf_lo(k.ldt)) * 1.4426950408889634f));
    const float dsk = (k.odd ? bf_hi(k.dk) : bf_lo(k.dk)) * rcpf_(dt);
    bar_sync(barid, 128);
    const float2 m0 = lds64f(mxa + (w & 2) * 4), m1 = lds64f(mxa + (nw == 1 ? (w & 2) ^ 2 : (w & 2)) * 4);
    const float sc = pow2_floor(fmaxf(0.125f * fmaxf(fmaxf(m0.x, m0.y), fmaxf(m1.x, m1.y)), fabsf(dsk) * (1.f / 4096.f)));
    inv_sc = rcpf_(sc);
    if (lane == 0) sts64f(tbl + TBL_SC + 8, dt * sc, dsk * inv_sc);
    dl = dt * 1.4426950408889634f;
  }
  const uint32_t sa = stg + (w >> 1) * 8192 + (32 * (w & 1) + lane) * 16, sc_ = sa + 16384 - (w >> 1) * 2048;
  const uint64_t dA = mkdesc(stg, 128, 2048, 0), dB = mkdesc(stg + 16384, 128, 2048, 0);
  float acc[24];
#pragma unroll 1
  for (int it = 0; it < 2 * nw; it++) {
    if (it == 1) mid();
    const uint32_t sel = (it & 1) ? 0x3244u : 0x1044u;
    float v[6];
#pragma unroll
    for (int i = 0; i < 6; i++) { v[i] = __uint_as_float(__byte_perm(k.cur[i], 0, sel)); if (it == 1) k.cur[i] = k.nxt[i]; }
    const float rho2 = v[0] * dl, phi = v[1] * dt;
    const cf bb = {v[2] * inv_sc, v[3] * -inv_sc}, cc = {v[4], v[5]};
    const cf X0 = cmulc(bb, cc);
    const cf z1 = zpow(rho2, phi, 1.f), z64 = zpow(rho2, phi, 64.f);
    const cf z2 = csq(z1), z3 = cmul(z2, z1), z4 = csq(z2), z8 = csq(z4), z16 = csq(z8), z24 = cmul(z16, z8), z32 = csq(z16);
    const cf z128 = csq(z64), y1 = csq(z128), y2 = csq(y1), y3 = cmul(y2, y1), y4 = csq(y2);
    const cf X4 = cmulc(X0, z4), W4 = cmulc(X0, y4), W8 = cmulc(W4, y4), W5 = cmulc(W4, y1);
    uint32_t re[4], im[4], r2[4], i2[4];
    re[0] = pack_h2(X0.x, X4.x); im[0] = pack_h2(X0.y, X4.y);
    hprod2<true>(re[0], im[0], pk(z1), re[1], im[1]);
    hprod2<true>(re[0], im[0], pk(z2), re[2], im[2]);
    hprod2<true>(re[0], im[0], pk(z3), re[3], im[3]);
    const uint32_t hy1 = pk(y1), hy2 = pk(y2);
    hprod2<true>(re[0], im[0], hy1, r2[0], i2[0]);
    hprod2<true>(re[2], im[2], hy1, r2[1], i2[1]);
    hprod2<true>(re[0], im[0], hy2, r2[2], i2[2]);
    hprod2<true>(re[0], im[0], pk(y3), r2[3], i2[3]);
    wg_wait<0>();
    bar_sync(barid, 128);
    sts128(sc_, re[0], re[1], re[2], re[3]);
    sts128(sc_ + 1024, im[0], im[1], im[2], im[3]);
    sts128(sc_ + 2048, r2[0], r2[1], r2[2], r2[3]);
    sts128(sc_ + 3072, i2[0], i2[1], i2[2], i2[3]);
    re[0] = pack_h2(W4.x, W5.x); im[0] = pack_h2(W4.y, W5.y);
    hprod2<true>(re[0], im[0], hy2, re[1], im[1]);
    sts128(sc_ + 4096, re[0], re[1], pack_h2(W8.x, 0.f), 0u);
    sts128(sc_ + 5120, im[0], im[1], pack_h2(W8.y, 0.f), 0u);
    re[0] = pack_h2(1.f, z32.x); im[0] = pack_h2(0.f, z32.y);
    hprod2<false>(re[0], im[0], pk(z8), re[1], im[1]);
    hprod2<false>(re[0], im[0], pk(z16), re[2], im[2]);
    hprod2<false>(re[0], im[0], pk(z24), re[3], im[3]);
    const uint32_t h64 = pk(z64), h128 = pk(z128);
#pragma unroll
    for (int j = 0; j < 4; j++) hprod2<false>(re[j], im[j], h64, r2[j], i2[j]);
    sts128(sa, re[0], re[1], re[2], re[3]);
    sts128(sa + 1024, im[0], im[1], im[2], im[3]);
    sts128(sa + 2048, r2[0], r2[1], r2[2], r2[3]);
    sts128(sa + 3072, i2[0], i2[1], i2[2], i2[3]);
    uint32_t r3[4], i3[4], r4[4], i4[4];
#pragma unroll
    for (int j = 0; j < 4; j++) { hprod2<false>(re[j], im[j], h128, r3[j], i3[j]); hprod2<false>(r2[j], i2[j], h128, r4[j], i4[j]); }
    sts128(sa + 4096, r3[0], r3[1], r3[2], r3[3]);
    sts128(sa + 5120, i3[0], i3[1], i3[2], i3[3]);
    sts128(sa + 6144, r4[0], r4[1], r4[2], r4[3]);
    sts128(sa + 7168, i4[0], i4[1], i4[2], i4[3]);
    fence_async();
    bar_sync(barid, 128);
    wg_fence();
#pragma unroll
    for (int ks = 0; ks < 8; ks++) wg_ss_f16_n48t(acc, dA + 16 * ks, dB + 16 * ks, (it | ks) != 0);
    wg_commit();
  }
  wg_wait<0>();
  fence_regs<24>(acc);
  bar_sync(barid, 128);
#pragma unroll
  for (int h = 0; h < 2; h++)
#pragma unroll
    for (int nt = 0; nt < 3; nt++) {
      const int i = 4 * nt + 2 * h;
      sts64f(stg + (w * 2 + h) * 768 + nt * 256 + lane * 8, (w & 2) ? acc[12 + i] : acc[i], (w & 2) ? acc[13 + i] : acc[1 + i]);
    }
}

__device__ __forceinline__ void tput(uint32_t tbl, int X, uint32_t h) {
  sts16(tbl + 2 * (1296 - X), (uint16_t)h);
  sts16(tbl + TBL_C1 + 2 * (1297 - X), (uint16_t)h);
}
__device__ __forceinline__ void ktab_build(uint32_t src, bool two, int q, uint32_t tbl, int lane) {
  const int tq = lane & 3, r = 8 * q + (lane >> 3) + ((lane >> 2) & 1) * 4;
  float v[6];
  src += q * 768 + lane * 8;
#pragma unroll
  for (int nt = 0; nt < 3; nt++) {
    const float2 a = lds64f(src + nt * 256);
    v[2 * nt] = a.x; v[2 * nt + 1] = a.y;
    if (two) { const float2 c = lds64f(src + nt * 256 + 3072); v[2 * nt] += c.x; v[2 * nt + 1] += c.y; }
  }
  const bool first = (r == 0);
  if (first && tq == 0) { v[0] += lds32f(tbl + TBL_SC + 12); sts32f(tbl + TBL_SC, v[4]); }
  const uint32_t h0 = pack_h2(v[0], v[1]), h1 = pack_h2(v[2], v[3]), h2 = pack_h2(v[4], v[5]);
  tput(tbl, 64 + 8 * r + tq, h0);
  tput(tbl, 68 + 8 * r + tq, h0 >> 16);
  const bool lo = tq < 2;
  const int k2 = 32 * (tq - 2) + r;
  const bool sp = first && tq == 2;
  const int Xa = lo ? 320 + 8 * r + 2 * tq : (sp ? 576 : 911 + k2), Xb = lo ? Xa + 4 : 720 + k2;
  tput(tbl, Xa, h1);
  tput(tbl, Xb, h1 >> 16);
  if (tq == 0 || sp) {
    tput(tbl, Xa + 1, h1);
    if (Xa != 320) tput(tbl, Xa - 1, h1);
    const uint32_t hb = sp ? h1 : h1 >> 16, hc = sp ? h2 : h1 >> 16;
    tput(tbl, sp ? 578 : Xb + 1, hb);
    tput(tbl, sp ? 1295 : Xb - 1, hc);
  }
  if (lo) {
    const int X3 = ((r & 1) ? 1104 : 1231) + 32 * tq + (r >> 1);
    tput(tbl, X3 == 1231 ? 975 : X3, h2);
    tput(tbl, X3 + 16, h2 >> 16);
  }
}

__device__ __forceinline__ void sig_windows(uint32_t sig, int t) {
  uint32_t U[20];
#pragma unroll
  for (int c = 0; c < 5; c++) {
    const int kap = 2 * t - 3 + c + 72;
    const uint4 v = lds128(sig + SIG_U + (kap & 7) * U_LBO + (kap >> 3) * 16);
    U[4 * c] = v.x; U[4 * c + 1] = v.y; U[4 * c + 2] = v.z; U[4 * c + 3] = v.w;
  }
  uint32_t O[19], A2[17], A4[17], V2[8], V5[8];
#pragma unroll
  for (int i = 3; i < 19; i++) O[i] = __byte_perm(U[i - 1], U[i], 0x5432);
#pragma unroll
  for (int i = 3; i < 17; i++) A2[i] = hadd2u(U[i], O[i]);
#pragma unroll
  for (int i = 4; i < 17; i++) A4[i] = hadd2u(A2[i], A2[i - 1]);
#pragma unroll
  for (int k = 0; k < 8; k++) { V2[k] = hadd2u(O[11 + k], U[10 + k]); V5[k] = hadd2u(A4[9 + k], U[7 + k]); }
#pragma unroll
  for (int h = 0; h < 2; h++) {
    sts128(sig + SIG_V3 + t * 32 + h * 16, hadd2u(V2[4 * h], O[10 + 4 * h]), hadd2u(V2[4 * h + 1], O[11 + 4 * h]),
           hadd2u(V2[4 * h + 2], O[12 + 4 * h]), hadd2u(V2[4 * h + 3], O[13 + 4 * h]));
    sts128(sig + SIG_V5 + t * 32 + h * 16, V5[4 * h], V5[4 * h + 1], V5[4 * h + 2], V5[4 * h + 3]);
  }
  if (t < 64) {
    uint32_t V7[8], V9[8];
#pragma unroll
    for (int k = 0; k < 8; k++) {
      V7[k] = hadd2u(V5[k], hadd2u(O[10 + k], O[7 + k]));
      V9[k] = hadd2u(hadd2u(A4[6 + k], A4[4 + k]), U[2 + k]);
    }
#pragma unroll
    for (int h = 0; h < 2; h++) {
      sts128(sig + SIG_V7 + h * 1024 + t * 16, V7[4 * h], V7[4 * h + 1], V7[4 * h + 2], V7[4 * h + 3]);
      sts128(sig + SIG_V9 + h * 1024 + t * 16, V9[4 * h], V9[4 * h + 1], V9[4 * h + 2], V9[4 * h + 3]);
      sts128(sig + SIG_V2 + h * 1024 + t * 16, V2[4 * h], V2[4 * h + 1], V2[4 * h + 2], V2[4 * h + 3]);
    }
  }
}

__device__ __forceinline__ void conv_channel(uint32_t tbl, uint32_t sig, uint32_t y2b, uint32_t y3b, float k1024,
                                             int w, int lane, int barid, float* res) {
  const int g = lane >> 2, tq = lane & 3;
  const uint32_t tb = tbl + ((g & 1) ? TBL_C1 + 2 : 0) + 2 * (1296 - (g - 2 * tq)) - 32 * w + 112;
  float a2[12], a3[8];
#pragma unroll
  for (int i = 0; i < 16; i++) res[i] = 0.f;
#pragma unroll
  for (int i = 0; i < 12; i++) a2[i] = 0.f;
#pragma unroll
  for (int q = 0; q < 4; q++) {
    const float2 f = h2f(lds32(sig + SIG_V2 + (q >> 1) * 1024 + (16 * w + 8 * (q & 1) + g) * 16 + tq * 4));
    a3[2 * q] = k1024 * f.x;
    a3[2 * q + 1] = k1024 * f.y;
  }
  const uint32_t sigu = __shfl_sync(0xffffffffu, opaque(sig), 0);
  const uint64_t dU = mkdesc(sigu + SIG_U, U_LBO, 128, 0);
  const uint64_t dV = mkdesc(sigu, 128, 1024, 0);
  fence_regs<16>(res); fence_regs<12>(a2); fence_regs<8>(a3);
  constexpr int LB = 2 * U_LBO / 16;
  uint32_t Rd[43], R2[22], R3[12];
  uint32_t td = tb - 128, t2 = tb - 1440, t3 = tb - 2208;
  uint64_t dd = dU + 9, d2 = dV + (SIG_V3 + 768) / 16, d3 = dV + (SIG_V7 + 768) / 16;
  auto load_group = [&](int gi) {
#pragma unroll
    for (int i = 1; i < 5; i++) Rd[4 * gi + i] = lds32(td - 16 * (4 * gi + i));
    const int e = gi >> 3;
    if ((gi & 7) == 0) { R2[2 * gi + e] = lds32(t2 - 384 * e); R3[gi + e] = lds32(t3 - 256 * e); }
    R2[2 * gi + e + 1] = lds32(t2 - 384 * e - 16 * (2 * (gi & 7) + 1));
    R2[2 * gi + e + 2] = lds32(t2 - 384 * e - 16 * (2 * (gi & 7) + 2));
    if (!(gi & 1)) {
      R3[gi + e + 1] = lds32(t3 - 256 * e - 16 * ((gi & 7) + 1));
      R3[gi + e + 2] = lds32(t3 - 256 * e - 16 * ((gi & 7) + 2));
    }
  };
  auto dense = [&](int n) {
    wg_rs_f16_n32k(res, Rd[2 * n + 1], Rd[2 * n + 2], Rd[2 * n], Rd[2 * n + 1], dd + ((3 - (n & 3)) * LB + 8 - (n >> 2)) - 8, 1);
  };
  Rd[0] = lds32(td);
  load_group(0);
  load_group(1);
#pragma unroll 1
  for (int sg = 0; sg < 2; sg++) {
#pragma unroll
    for (int gi = 0; gi < 8; gi++) {
      wg_fence();
      dense(2 * gi);
      wg_rs_f16_n24t(a2, R2[2 * gi + 1], R2[2 * gi + 2], R2[2 * gi], R2[2 * gi + 1], d2 - (16 * (gi & 3) + 64 * (gi >> 2)), 1);
      dense(2 * gi + 1);
      if (!(gi & 1)) wg_rs_f16_n16t(a3, R3[gi + 1], R3[gi + 2], R3[gi], R3[gi + 1], d3 - 8 * gi, 1);
      wg_commit();
      wg_wait<1>();
      load_group(gi + 2);
    }
#pragma unroll
    for (int i = 0; i < 9; i++) Rd[i] = Rd[32 + i];
#pragma unroll
    for (int i = 0; i < 5; i++) R2[i] = R2[17 + i];
#pragma unroll
    for (int i = 0; i < 3; i++) R3[i] = R3[9 + i];
    td -= 512; t2 -= 384; t3 -= 256;
    dd -= 4; d2 += 256; d3 += 128;
  }
  Rd[9] = lds32(td - 144); Rd[10] = lds32(td - 160);
  wg_fence();
#pragma unroll
  for (int n = 0; n < 5; n++) dense(n);
  wg_commit();
  wg_wait<1>();
  fence_regs<12>(a2); fence_regs<8>(a3);
  bar_sync(barid, 128);
  {
    const uint32_t o2 = y2b + (136 * w + 8 * g + 2 * tq) * 4, o3 = y3b + (272 * w + 16 * g + 2 * tq) * 4;
#pragma unroll
    for (int q = 0; q < 6; q++) sts64f(o2 + (544 * (q >> 1) + 64 * (q & 1)) * 4, a2[2 * q], a2[2 * q + 1]);
#pragma unroll
    for (int q = 0; q < 4; q++) sts64f(o3 + (8 * (q >> 1) + 136 * (q & 1)) * 4, a3[2 * q], a3[2 * q + 1]);
  }
  bar_sync(barid, 128);
  const uint32_t go = (136 * tq + 16 * w + g) * 4;
  float ex[12];
#pragma unroll
  for (int i = 0; i < 12; i++) {
    const int o = 544 * (i >> 2) + 64 * (i & 1) + 8 * ((i >> 1) & 1);
    ex[i] = lds32f(y2b + go + o * 4);
    if (i >= 4) ex[i] += lds32f(y3b + go + (o - 544) * 4);
  }
  wg_wait<0>();
  fence_regs<16>(res);
#pragma unroll
  for (int i = 0; i < 12; i++) res[4 + i] += ex[i];
}

__device__ __forceinline__ void red16x2(float& a, float& c) {
#pragma unroll
  for (int o = 1; o < 16; o <<= 1) { a += __shfl_xor_sync(0xffffffffu, a, o); c += __shfl_xor_sync(0xffffffffu, c, o); }
}
__device__ __forceinline__ void ln_rows(uint32_t* u, uint32_t term, uint32_t stg_row, int lane) {
  const int j = lane & 15;
  const float piv = __shfl_sync(0xffffffffu, bf_lo(u[0]), lane & 16);
  float s0 = 0.f, s1 = 0.f, q0 = 0.f, q1 = 0.f;
#pragma unroll
  for (int i = 0; i < 14; i++) {
    const float a = bf_lo(u[i]) - piv, c = bf_hi(u[i]) - piv;
    s0 += a; s1 += c; q0 = fmaf(a, a, q0); q1 = fmaf(c, c, q1);
  }
  float s = s0 + s1, q = q0 + q1;
  red16x2(s, q);
  s *= (1.f / D_); q *= (1.f / D_);
  const __nv_bfloat16 m1b = __float2bfloat16_rn(s + piv);
  const __nv_bfloat162 m1v = __halves2bfloat162(m1b, m1b);
  const float den = rbf(sqrtf_(rbf(rbf(fmaxf(fmaf(-s, s, q), 0.f)) + 1e-5f)));
  const float rden = rcpf_(den);
  s0 = s1 = q0 = q1 = 0.f;
#pragma unroll
  for (int i = 0; i < 14; i++) {
    const __nv_bfloat162 cv = __hsub2(*reinterpret_cast<__nv_bfloat162*>(&u[i]), m1v);
    const uint32_t c = *reinterpret_cast<const uint32_t*>(&cv);
    const uint32_t n = pack_bf2(bf_lo(c) * rden, bf_hi(c) * rden);
    const float a = bf_lo(n), e = bf_hi(n);
    s0 += a; s1 += e; q0 = fmaf(a, a, q0); q1 = fmaf(e, e, q1);
    u[i] = pack_h2(a, e);
  }
#pragma unroll
  for (int i = 0; i < 7; i++)
    asm volatile("st.shared.v2.b32 [%0], {%1,%2};" ::"r"(stg_row + (j + 16 * i) * 8), "r"(u[2 * i]), "r"(u[2 * i + 1]) : "memory");
  s = s0 + s1; q = q0 + q1;
  red16x2(s, q);
  s *= (1.f / D_); q *= (1.f / D_);
  const float den2 = rbf(sqrtf_(rbf(rbf(fmaxf(fmaf(-s, s, q), 0.f)) + 1e-5f)));
  if (j == 0) {
    const float ir = den * den2, mu = fmaf(rbf(s), den, __bfloat162float(m1b));
    const float ih = rbf(ir), mh = rbf(mu);
    const uint32_t mm = pack_bf2(mh, mh);
    sts128(term, pack_bf2(mu - mh, ih), mm, pack_bf2(mu - mh, ir - ih), mm);
  }
}

__device__ __forceinline__ void poll_tag(const unsigned* p, uint32_t tag) {
#pragma unroll 1
  for (int it = 0; it < 4096; it++) {
    if (!((ld_relaxed1(p) ^ tag) & 1)) break;
    __nanosleep(32);
  }
}
__device__ __forceinline__ bool last_release(uint32_t cnt) {
  unsigned old;
  asm volatile("atom.relaxed.cta.shared.inc.u32 %0, [%1], 7;" : "=r"(old) : "r"(cnt) : "memory");
  return old == 7;
}
__device__ __forceinline__ int mod7(int v) { return v >= 7 ? v - 7 : v; }

#define IDS const int tid = opaque(tid0), lane = tid & 31, t = tid & 127; (void)lane; (void)t;

__global__ void __launch_bounds__(384, 1)
fused_kernel(const Params p, const __grid_constant__ CUtensorMap tm_x, const __grid_constant__ CUtensorMap tm_w1,
             const __grid_constant__ CUtensorMap tm_w2, const __grid_constant__ CUtensorMap tm_out) {
  const uint32_t sb = smem_u32(smem_raw);
  const uint32_t ms = sb + OFF_M;
  const uint32_t bar0 = ms + M_BAR;
  const int tid0 = threadIdx.x;
  const int wi = __shfl_sync(0xffffffffu, tid0 >> 5, 0), wg = wi >> 2, w = wi & 3;
  const int b = blockIdx.x;
  const bool is_ssm = b >= NMLP;
  const int G = b / NRK, rk = b - G * NRK;
  const int kc0 = (G + rk) % 7;
  TSINIT();
  TSTAMP(0);
  {
    IDS
    TSTAMP(28);
    uint4 ld[7];
    KgIn kin;
    unsigned ep = 0;
    uint32_t b1w;
    const int rl = 2 * wi + (lane >> 4);
    {
      const int d = is_ssm ? 2 * (112 + 3 * (b - NMLP) + wg) + (w >> 1) : (wg < 2 ? 2 * b + wg : 336 + b);
      const int off = d * NST + 64 * (is_ssm ? 2 * (w & 1) : w) + 2 * lane;
      const __nv_bfloat16* P[10] = {p.a_re + off, p.a_im + off, p.b_re + off, p.b_im + off, p.c_re + off, p.c_im + off,
                                    p.log_dt + (d & ~1), p.dskip + (d & ~1), p.b1 + 64 * (is_ssm ? 0 : b >> 2) + (t & 62),
                                    wg < 2 ? p.x + (size_t)(16 * (b & 127) + rl) * D_ + 4 * (lane & 15)
                                           : p.w1 + (size_t)(112 * (b & 3) + 4 * w + (lane & 3)) * F_ + 64 * (is_ssm ? 0 : b >> 2) + 8 * (lane >> 2)};
      const unsigned* pe = &p.s->epoch;
      asm volatile("" : "+l"(P[0]), "+l"(P[1]), "+l"(P[2]), "+l"(P[3]), "+l"(P[4]), "+l"(P[5]), "+l"(P[6]), "+l"(P[7]), "+l"(P[8]), "+l"(P[9]), "+l"(pe));
#pragma unroll
      for (int i = 0; i < 6; i++) kin.cur[i] = ldg32(P[i], 0);
      kin.ldt = ldg32(P[6], 0); kin.dk = ldg32(P[7], 0); b1w = ldg32(P[8], 0);
      if (tid == 256 + 32) ep = ld_relaxed1(pe);
#pragma unroll
      for (int i = 0; i < 6; i++) kin.nxt[i] = 0u;
      if (is_ssm) {
#pragma unroll
        for (int i = 0; i < 6; i++) kin.nxt[i] = ldg32(P[i], 128);
      }
      if (wg < 2) {
#pragma unroll
        for (int i = 0; i < 7; i++) asm volatile("ld.global.nc.v2.b32 {%0,%1}, [%2];" : "=r"(ld[i].x), "=r"(ld[i].y) : "l"(P[9] + 64 * i));
      } else {
#pragma unroll
        for (int i = 0; i < 7; i++)
          asm volatile("ld.global.nc.v4.b32 {%0,%1,%2,%3}, [%4];" : "=r"(ld[i].x), "=r"(ld[i].y), "=r"(ld[i].z), "=r"(ld[i].w) : "l"(P[9] + (size_t)i * 16 * F_));
      }
      asm volatile("" :: "l"(P[0]), "l"(P[1]), "l"(P[2]), "l"(P[3]), "l"(P[4]), "l"(P[5]), "l"(P[6]), "l"(P[7]), "l"(P[8]), "l"(P[9]), "l"(pe));
      kin.odd = d & 1;
    }
    const uint32_t tbl = is_ssm ? sb + (4 * wg + (w >> 1)) * TBL : sb + OFF_T + wg * TBL;
#pragma unroll 1
    for (int i = is_ssm ? t & 63 : t; i < TBL_SC / 16; i += is_ssm ? 64 : 128) sts128(tbl + i * 16, 0u, 0u, 0u, 0u);
    const uint32_t lns = is_ssm ? sb + S_WORK + 2 * S_WGB + KSTG : sb + OFF_X + 2 * 16384;
    if (wi < 4 && lane == 0) {
      if (wi < 3) mbar_init(bar0 + 8 * wi, 1);
      asm volatile("fence.mbarrier_init.release.cluster;" ::: "memory");
      if (!is_ssm) asm volatile("prefetch.tensormap [%0];" ::"l"(wi == 0 ? &tm_x : wi == 1 ? &tm_w1 : wi == 2 ? &tm_w2 : &tm_out) : "memory");
    }
    __syncwarp();
    if (wi == 4 && lane < 16) asm volatile("st.shared.b32 [%0], 0;" ::"r"(ms + M_REL + 4 * lane) : "memory");
    TSTAMP(31);
    auto mid = [&]() {
    TSTAMP(30);
    if (wg < 2) {
      uint32_t u[14];
#pragma unroll
      for (int i = 0; i < 7; i++) { u[2 * i] = ld[i].x; u[2 * i + 1] = ld[i].y; }
      ln_rows(u, ms + M_LT + rl * 16, lns + ((rl & 1) | ((rl >> 2) << 1) | ((rl & 2) << 2)) * 912, lane);
      bar_arrive(7, 384);
    } else {
      float cs[4] = {0.f, 0.f, 0.f, 0.f};
      const int g = lane >> 2;
      const uint32_t one = (g & 1) ? 0x3f800000u : 0x00003f80u;
      const uint32_t s0 = (g >> 1) == 0 ? one : 0u, s1 = (g >> 1) == 1 ? one : 0u, s2 = (g >> 1) == 2 ? one : 0u, s3 = (g >> 1) == 3 ? one : 0u;
#pragma unroll
      for (int i = 0; i < 7; i++) {
        mma_bf16(cs, s0, 0u, s1, 0u, ld[i].x, ld[i].y);
        mma_bf16(cs, s2, 0u, s3, 0u, ld[i].z, ld[i].w);
      }
      sts32f(ms + M_CSR + (w * 64 + (lane & 3) * 16 + g) * 4, cs[0]);
      sts32f(ms + M_CSR + (w * 64 + (lane & 3) * 16 + g + 8) * 4, cs[1]);
      if (t == 32) { asm volatile("st.shared.b32 [%0], %1;" ::"r"(ms + M_EP), "r"(ep + 1) : "memory"); red_relaxed(&p.s->cntA); }
      bar_sync(7, 384);
      const uint32_t la = lns + (lane & 15) * 912 + (lane >> 4) * 16 + w * 224;
      uint2* dst = (uint2*)(p.s->xnT + (size_t)(56 * w + (lane >> 3)) * 512 + 4 * b) + (lane & 7);
      uint32_t r[28];
#pragma unroll
      for (int k = 0; k < 7; k++) ldsm4t(la + k * 32, r[4 * k], r[4 * k + 1], r[4 * k + 2], r[4 * k + 3]);
      const uint32_t tag = lds32(ms + M_EP) & 1;
      if (b < 128) {
#pragma unroll
        for (int k = 0; k < 14; k++) st_relaxed2(dst + k * 4096, (r[2 * k] & ~1u) | tag, (r[2 * k + 1] & ~1u) | tag);
      }
      if (t < 64 && !is_ssm) {
        const uint32_t a = ms + M_CSR + t * 4;
        const float c = -((lds32f(a) + lds32f(a + 256)) + (lds32f(a + 512) + lds32f(a + 768)));
        const float ch = rbf(c);
        uint2* dx = (uint2*)(p.s->bx + (b >> 4) * 512 + ((b >> 1) & 1) * 256 + ((b >> 2) & 3) * 64 + t) + (b & 1);
        const float b1v = (b & 2) ? 0.f : ((t & 1) ? bf_hi(b1w) : bf_lo(b1w));
        asm volatile("{.reg .b64 a; mov.b64 a, {%1,%2}; st.relaxed.gpu.global.b64 [%0], a;}"
                     ::"l"(dx), "r"(pack_bf2(ch, b1v)), "r"((pack_bf2(c - ch, ch) & ~1u) | tag) : "memory");
      }
      if (t >= 64 && t < 80 && b < 128) {
        const uint4 a = lds128(ms + M_LT + (t - 64) * 16);
        st_b128(p.s->ax + 16 * b + t - 64, tag, a.x, a.y, a.z, a.w);
      }
    }
    if (wi < 2 && lane == 0 && !is_ssm) {
      const int i = wi, kc = i;
      mbar_expect(bar0 + 8 * i, 49152);
      tma_2d(sb + OFF_X + i * 16384, &tm_x, 64 * kc, 128 * G, bar0 + 8 * i);
      tma_3d(sb + OFF_W + i * 32768, &tm_w1, 0, 64 * kc, 4 * rk, bar0 + 8 * i);
    }
    __syncwarp();
    TSTAMP(29);
    };
    kgen_wg(kin, is_ssm ? 2 : 1, stg, tbl, ms + M_MX + wg * 16, w, lane, 4 + wg, mid);
  }
  TSTAMP(1);
  uint4 v[4], tv[5];
  {
    IDS
    bar_sync(4 + wg, 128);
    if (!is_ssm && wg == 2) {
#pragma unroll
      for (int q = 0; q < 4; q++) tv[q] = ld_2x64(p.s->bx + 512 * rk + q * 128 + t);
      tv[4] = ld_b128(p.s->ax + 128 * G + t);
    }
    if (is_ssm || wg == 2) {
      const uint4* src = p.s->xnT + (size_t)(is_ssm ? 112 + 3 * (b - NMLP) + wg : b) * 512 + t;
#pragma unroll
      for (int q = 0; q < 4; q++) v[q] = ld_relaxed4(src + q * 128);
    }
#pragma unroll 1
    for (int c = is_ssm ? 1 : 0; c >= 0; c--) {
      ktab_build(stg + c * 3072, !is_ssm, w, is_ssm ? sb + (4 * wg + c) * TBL : sb + OFF_T + wg * TBL, lane);
    }
    fence_async();
  }
  TSTAMP(2);
  __syncthreads();

  if (is_ssm || wg == 2) {
    asm volatile("setmaxnreg.dec.sync.aligned.u32 136;");
    if (!is_ssm) {
      IDS
      if (t == 0) {
        mbar_expect(bar0 + 16, 49152);
        tma_2d(sb + OFF_X + 2 * 16384, &tm_x, 128, 128 * G, bar0 + 16);
        tma_3d(sb + OFF_W + 2 * 32768, &tm_w1, 0, 128, 4 * rk, bar0 + 16);
      }
      __syncwarp();
      const unsigned ep1 = lds32(ms + M_EP);
#pragma unroll 1
      for (int it = 0; it < 16 * RETRY_MAX; it++) {
        uint32_t bad = tv[4].x ^ ep1;
#pragma unroll
        for (int q = 0; q < 4; q++) bad |= (tv[q].y ^ ep1) | (tv[q].w ^ ep1);
        if (!__any_sync(0xffffffffu, bad & 1)) break;
        __nanosleep(200);
#pragma unroll
        for (int q = 0; q < 4; q++) tv[q] = ld_2x64(p.s->bx + 512 * rk + q * 128 + t);
        tv[4] = ld_b128(p.s->ax + 128 * G + t);
      }
#pragma unroll
      for (int q = 0; q < 5; q++) sts128(sb + OFF_B + (q < 4 ? B_BX + q * 2048 : B_AX) + t * 16, tv[q].x, tv[q].y, tv[q].z, tv[q].w);
      if (t < 64) sts32f(ms + M_CSR + t * 4, 0.5f * __bfloat162float(p.b2[64 * rk + t]));
      fence_async();
      bar_arrive(1, 384);
      if (t == 96) { bulk_s2g(p.s->tbl + b * (TBL / 16), sb + OFF_T + 2 * TBL, TBL); bulk_commit(); }
      if (t == 64)
        asm volatile("cp.async.bulk.prefetch.L2.global [%0], %1;" ::"l"(p.w2 + (size_t)(256 * rk + 16 * G) * D_), "r"(16 * D_ * 2) : "memory");
    }
#pragma unroll 1
    for (int pi = 0; ; pi++) {
      {
        IDS
        const unsigned ep1 = lds32(ms + M_EP);
        const int pair = !is_ssm ? b : (pi == 0 ? 112 + 3 * (b - NMLP) : (b < NMLP + 12 ? 172 + 3 * (b - NMLP) : 184 + 2 * (b - NMLP))) + wg;
        const uint32_t work = is_ssm ? sb + S_WORK + wg * S_WGB : sb + OFF_A;
        const uint32_t z = work + SIG_V3 - 1024 + (t >> 6) * 4096 + (t & 63) * 16;
        sts128(z, 0u, 0u, 0u, 0u); sts128(z + SIG, 0u, 0u, 0u, 0u);
        if (t < 72) {
          const uint32_t zu = work + SIG_U + (t & 7) * U_LBO + (t >> 3) * 16;
          sts128(zu, 0u, 0u, 0u, 0u); sts128(zu + SIG, 0u, 0u, 0u, 0u);
        }
        const uint4* src = p.s->xnT + (size_t)pair * 512 + t;
#pragma unroll 1
        for (int it = 0; it < RETRY_MAX; it++) {
          uint32_t bad = 0;
#pragma unroll
          for (int q = 0; q < 4; q++) bad |= (((v[q].x ^ ep1) | (v[q].y ^ ep1) | (v[q].z ^ ep1) | (v[q].w ^ ep1)) & 1) << q;
          const unsigned m = __ballot_sync(0xffffffffu, bad);
          if (!m) break;
          if (lane == __ffs(m) - 1) poll_tag((const unsigned*)(src + (__ffs(bad) - 1) * 128) + 3, ep1);
          __syncwarp();
#pragma unroll
          for (int q = 0; q < 4; q++) v[q] = ld_relaxed4(src + q * 128);
        }
        TSTAMP(5);
        const uint32_t a = work + ((t >> 1) & 1) * SIG + SIG_U + (2 * ((t >> 2) & 3) + (t & 1)) * U_LBO + ((t >> 4) + 9) * 16;
#pragma unroll
        for (int q = 0; q < 4; q++) sts128(a + q * 128, v[q].x & ~1u, v[q].y & ~1u, v[q].z & ~1u, v[q].w & ~1u);
        bar_sync(4 + wg, 128);
#pragma unroll 1
        for (int k = w; k < 6; k += 4) sig_windows(work + (k & 1) * SIG, (k >> 1) * 32 + lane);
        fence_async();
        if (t == 96 && !is_ssm) { bulk_wait0(); red_release(&p.s->cntT); }
        if (pi == 1) mbar_wait(bar0 + 8 * wg, 0);
        TSTAMP(6);
        bar_sync(is_ssm ? 4 + wg : 3, is_ssm ? 128 : 384);
        TSTAMP(7);
      }
      uint32_t keep[8];
      float res[16];
#pragma unroll 1
      for (int c = 0; c < 2; c++) {
        IDS
        const uint32_t work = is_ssm ? sb + S_WORK + wg * S_WGB : sb + OFF_A;
        const uint32_t tbl = (is_ssm ? sb + (4 * wg + 2 * pi) * TBL : sb + OFF_T) + c * TBL;
        conv_channel(tbl, work + c * SIG, is_ssm ? work + 2 * SIG + Y3B : sb + OFF_B, work + 2 * SIG, lds32f(tbl + TBL_SC), w, lane, 4 + wg, res);
        TSTAMP(16 + 2 * pi + c);
        const float os = lds32f(tbl + TBL_SC + 8);
        if (c == 0) {
#pragma unroll
          for (int i = 0; i < 8; i++) keep[i] = pack_bf2(res[2 * i] * os, res[2 * i + 1] * os);
          if (is_ssm && pi == 0 && t == 96 && (b < NMLP + 12 || wg < 2)) {
            wait_count(&p.s->cntT, lds32(ms + M_EP) * NMLP);
            asm volatile("fence.proxy.async;" ::: "memory");
            mbar_expect(bar0 + 8 * wg, 2 * TBL);
            bulk_g2s(sb + (4 * wg + 2) * TBL, p.s->tbl + (2 * ((b < NMLP + 12 ? 172 + 3 * (b - NMLP) : 184 + 2 * (b - NMLP)) + wg) - 336) * (TBL / 16),
                     2 * TBL, bar0 + 8 * wg);
          }
          __syncwarp();
        } else {
          const int pair = !is_ssm ? b : (pi == 0 ? 112 + 3 * (b - NMLP) : (b < NMLP + 12 ? 172 + 3 * (b - NMLP) : 184 + 2 * (b - NMLP))) + wg;
          uint4* dst = p.s->s2 + ((size_t)(lane & 3) * 224 + pair) * 32 + w * 8 + (lane >> 2);
          const uint32_t tag = (lds32(ms + M_EP) & 1) * 0x10001u;
#pragma unroll
          for (int nt = 0; nt < 4; nt++) {
            const uint32_t n0 = pack_bf2(res[4 * nt] * os, res[4 * nt + 1] * os), n1 = pack_bf2(res[4 * nt + 2] * os, res[4 * nt + 3] * os);
            const uint32_t k0 = (keep[2 * nt] & 0xfffefffeu) | tag;
            asm volatile("{.reg .b64 a, c; mov.b64 a, {%1,%2}; mov.b64 c, {%3,%4}; st.relaxed.gpu.global.v2.b64 [%0], {a, c};}"
                         ::"l"(dst + nt * 4 * 224 * 32), "r"(__byte_perm(k0, n0, 0x5410)), "r"(__byte_perm(keep[2 * nt + 1], n1, 0x5410)),
                         "r"(__byte_perm(k0, n0, 0x7632)), "r"(__byte_perm(keep[2 * nt + 1], n1, 0x7632)) : "memory");
          }
        }
      }
      TSTAMP(8 + pi);
      TSDUMP();
      {
        IDS
        if (pi == 1 || !is_ssm || (b >= NMLP + 12 && wg == 2)) break;
        const uint4* src = p.s->xnT + (size_t)((b < NMLP + 12 ? 172 + 3 * (b - NMLP) : 184 + 2 * (b - NMLP)) + wg) * 512 + t;
#pragma unroll
        for (int q = 0; q < 4; q++) v[q] = ld_relaxed4(src + q * 128);
      }
    }
    if (b == 0 && tid0 == 256) {
      const unsigned ep1 = lds32(ms + M_EP);
      wait_count(&p.s->cntA, ep1 * NCTA);
      *(volatile unsigned*)&p.s->epoch = ep1;
    }
  } else {
    bar_arrive(1, 384);
    asm volatile("setmaxnreg.inc.sync.aligned.u32 192;");
    bar_sync(7, 384);
    uint32_t H[64];
    {
      float acc[128];
      float p0, q0, p1, q1;
      {
        IDS
        int sl = 0;
#pragma unroll 1
        for (int s = 0; s < 7; s++) {
          mbar_wait(bar0 + 8 * sl, (s >= 3 && s < 6));
          TSTAMP(17 + s);
          const uint64_t da = mkdesc(sb + OFF_X + sl * 16384 + wg * 8192, 16, 1024, 1);
          const uint64_t db = mkdesc(sb + OFF_W + sl * 32768, 8192, 1024, 1);
          wg_fence();
#pragma unroll
          for (int k = 0; k < 4; k++) wg_ss_bf16_n256(acc, da + 2 * k, db + 128 * k, (s | k) != 0);
          wg_commit();
          wg_wait<1>();
          const int pl = sl == 0 ? 2 : sl - 1;
          sl = sl == 2 ? 0 : sl + 1;
          if (s > 0 && lane == 0 && last_release(ms + M_REL + 4 * s)) {
            mbar_expect(bar0 + 8 * pl, s == 5 ? 32768 : 49152);
            if (s < 5) tma_3d(sb + OFF_W + pl * 32768, &tm_w1, 0, 64 * (s + 2), 4 * rk, bar0 + 8 * pl);
            else tma_2d(sb + OFF_W + pl * 32768, &tm_w2, 64 * mod7(rk + s - 4), 256 * rk, bar0 + 8 * pl);
            if (s != 5) tma_2d(sb + OFF_X + pl * 16384, &tm_x, 64 * (s < 5 ? (s + 2) : rk), 128 * G, bar0 + 8 * pl);
          }
        }
        TSTAMP(15);
        bar_sync(1, 384);
        wg_fence();
        wg_ss_bf16_n256k(acc, mkdesc(sb + OFF_B + B_AX + wg * 1024, 0, 128, 0), mkdesc(sb + OFF_B + B_BX, 4096, 128, 0), 1);
        wg_commit();
        wg_wait<1>();
        if (lane == 0 && last_release(ms + M_REL + 4 * 7)) {
          mbar_expect(bar0, 65536);
#pragma unroll 1
          for (int c = 2; c < 4; c++) tma_2d(sb + (c - 2) * OFF_X, &tm_w2, 64 * mod7(rk + 1 + c), 256 * rk, bar0);
        }
        bar_arrive(3, 384);
        const uint32_t ra = sb + OFF_B + B_AX + (16 * wi + (lane >> 2)) * 16;
        const float r0 = rcpf_(bf_hi(lds32(ra)) + bf_hi(lds32(ra + 8))), r1 = rcpf_(bf_hi(lds32(ra + 128)) + bf_hi(lds32(ra + 136)));
        p0 = 0.7978845608028654f * r0; q0 = 0.0356774081363001f * r0 * r0 * r0;
        p1 = 0.7978845608028654f * r1; q1 = 0.0356774081363001f * r1 * r1 * r1;
      }
      wg_wait<0>();
      fence_regs<128>(acc);
      TSTAMP(16);
#pragma unroll 1
      for (int hf = 0; hf < 2; hf++) {
        float th[8];
#pragma unroll
        for (int i = 0; i < 35; i++) {
          if (i < 32) {
            const float pp = (i & 1) ? p1 : p0, qq = (i & 1) ? q1 : q0;
            const float a = acc[2 * i], c = acc[2 * i + 1];
            th[2 * (i & 3)] = tanhf_(a * fmaf(a * a, qq, pp)); th[2 * (i & 3) + 1] = tanhf_(c * fmaf(c * c, qq, pp));
          }
          if (i >= 3) {
            const int j = i - 3;
            asm volatile("{.reg .f32 x, y; fma.rn.f32 x, %0, %5, %0; fma.rn.f32 y, %1, %6, %1; mov.f32 %0, %3; mov.f32 %1, %4;\n"
                         ".reg .b32 h; cvt.rn.bf16x2.f32 h, y, x; mov.b32 %2, h;}"
                         : "+f"(acc[2 * j]), "+f"(acc[2 * j + 1]), "=f"(acc[64 + j])
                         : "f"(acc[64 + 2 * j]), "f"(acc[65 + 2 * j]), "f"(th[2 * (j & 3)]), "f"(th[2 * (j & 3) + 1]));
          }
        }
      }
#pragma unroll
      for (int i = 0; i < 32; i++) { H[i] = __float_as_uint(acc[i]); H[32 + i] = __float_as_uint(acc[64 + i]); }
    }
    TSTAMP(3);
    IDS
    float acc[32], pre[32];
    uint32_t pk[16];
#pragma unroll
    for (int i = 0; i < 32; i++) pre[i] = 0.f;
    const uint32_t tag = lds32(ms + M_EP) & 1;
    const uint4* inbox = p.s->part + (size_t)b * 6 * 1024 + tid;
    uint4 rv[4];
    auto fetch = [&](int slot) {
#pragma unroll
      for (int q = 0; q < 4; q++) rv[q] = ld_b128(inbox + slot * 1024 + q * 256);
    };
    auto recv = [&](int slot) {
#pragma unroll 1
      for (int it = 0; it < RETRY_MAX; it++) {
        const unsigned m = __ballot_sync(0xffffffffu, ((rv[0].x ^ tag) | (rv[1].x ^ tag) | (rv[2].x ^ tag) | (rv[3].x ^ tag)) & 1);
        if (!m) break;
        if (lane == __ffs(m) - 1) poll_tag((const unsigned*)(inbox + slot * 1024 + 768), tag);
        __syncwarp();
        fetch(slot);
      }
#pragma unroll
      for (int q = 0; q < 4; q++) {
        const uint32_t u[4] = {rv[q].x, rv[q].y, rv[q].z, rv[q].w};
#pragma unroll
        for (int k = 0; k < 4; k++) { pre[8 * q + 2 * k] += bf_lo(u[k]); pre[8 * q + 2 * k + 1] += bf_hi(u[k]); }
      }
    };
#pragma unroll 1
    for (int s = 0; s < 7; s++) {
      if (s != 3) mbar_wait(bar0 + 8 * ((0x0210021u >> (4 * s)) & 3), (0x34 >> s) & 1);
      const uint64_t db = mkdesc(sb + ((0x0213021u >> (4 * s)) & 3) * 32768, 8192, 1024, 1);
      wg_fence();
#pragma unroll
      for (int k = 0; k < 16; k++) wg_rs_bf16_n64(acc, H[4 * k], H[4 * k + 1], H[4 * k + 2], H[4 * k + 3], db + 128 * k, k != 0);
      wg_commit();
      if (s > 0) {
        uint4* dst = p.s->part + ((size_t)(G * 7 + mod7(rk + s)) * 6 + s - 1) * 1024 + tid;
#pragma unroll
        for (int q = 0; q < 4; q++) st_b128(dst + q * 256, tag, pk[4 * q], pk[4 * q + 1], pk[4 * q + 2], pk[4 * q + 3]);
        if (s < 4 && lane == 0 && last_release(ms + M_REL + 4 * (7 + s))) {
          const int sl = (0x0210u >> (4 * s)) & 3;
          mbar_expect(bar0 + 8 * sl, 32768);
          tma_2d(sb + sl * 32768, &tm_w2, 64 * mod7(mod7(rk + 4 + s)), 256 * rk, bar0 + 8 * sl);
        }
        __syncwarp();
      }
      if (s >= 4) recv(s - 4);
      if (s >= 3) fetch(s - 3);
      wg_wait<0>();
      fence_regs<32>(acc);
#pragma unroll
      for (int k = 0; k < 16; k++) pk[k] = pack_bf2(acc[2 * k], acc[2 * k + 1]);
      TSTAMP(4 + s);
    }
    {
      const uint2* sp = (const uint2*)(p.s->s2 + ((size_t)G * 224 + 32 * rk + (lane & 3)) * 32 + w * 8 + (lane >> 2)) + wg;
#pragma unroll 1
      for (int it = 0; it < RETRY_MAX; it++) {
#pragma unroll
        for (int i = 0; i < 8; i++)
          asm volatile("{.reg .b64 a; ld.relaxed.gpu.global.b64 a, [%2]; mov.b64 {%0,%1}, a;}"
                       : "=r"(pk[2 * i]), "=r"(pk[2 * i + 1]) : "l"(sp + i * 4 * 64) : "memory");
#pragma unroll 1
        for (int s = it ? 6 : 3; s < 6; s++) { recv(s); if (s < 5) fetch(s + 1); }
        uint32_t bad = 0;
#pragma unroll
        for (int i = 0; i < 8; i++) bad |= ((pk[2 * i] ^ tag) & 1) << i;
        const unsigned m = __ballot_sync(0xffffffffu, bad);
        if (!m) break;
        if (lane == __ffs(m) - 1) poll_tag((const unsigned*)(sp + (__ffs(bad) - 1) * 4 * 64), tag);
        __syncwarp();
      }
    }
    TSTAMP(12);
    const int g = lane >> 2, tq = lane & 3;
    const uint32_t xa = sb + OFF_X + 2 * 16384 + (16 * wi + (lane & 15)) * 128;
    uint32_t xw[16];
#pragma unroll
    for (int q = 0; q < 4; q++) ldsm4(xa + (((2 * q + (lane >> 4)) ^ (lane & 7)) << 4), xw[4 * q], xw[4 * q + 1], xw[4 * q + 2], xw[4 * q + 3]);
    const uint32_t ra = sb + OFF_B + B_AX + (16 * wi + g) * 16;
    const float r0 = 0.25f * rcpf_(bf_hi(lds32(ra)) + bf_hi(lds32(ra + 8))), r1 = 0.25f * rcpf_(bf_hi(lds32(ra + 128)) + bf_hi(lds32(ra + 136)));
#pragma unroll
    for (int i = 0; i < 8; i++) {
      const float2 bb = lds64f(ms + M_CSR + (8 * i + 2 * tq) * 4);
#pragma unroll
      for (int e = 0; e < 2; e++) {
        const int k = 2 * i + e;
        const float h0 = fmaf(acc[2 * k] + pre[2 * k], e ? r1 : r0, bb.x), h1 = fmaf(acc[2 * k + 1] + pre[2 * k + 1], e ? r1 : r0, bb.y);
        const uint32_t gw = pack_bf2(fmaf(h0, tanhf_(h0), h0), fmaf(h1, tanhf_(h1), h1));
        asm("fma.rn.bf16x2 %0, %1, %2, %0;" : "+r"(xw[k]) : "r"(pk[k]), "r"(gw));
      }
    }
#pragma unroll
    for (int q = 0; q < 4; q++) stsm4(xa + (((2 * q + (lane >> 4)) ^ (lane & 7)) << 4), xw[4 * q], xw[4 * q + 1], xw[4 * q + 2], xw[4 * q + 3]);
    fence_async();
    __syncwarp();
    if (lane == 0) {
      tma_store_2d(&tm_out, sb + OFF_X + 2 * 16384 + wi * 2048, 64 * rk, 128 * G + 16 * wi);
      bulk_commit();
      bulk_wait0_read();
    }
    TSTAMP(13);
    TSDUMP();
  }
}

typedef CUresult (*EncodeFn)(CUtensorMap*, CUtensorMapDataType, cuuint32_t, void*, const cuuint64_t*, const cuuint64_t*,
                             const cuuint32_t*, const cuuint32_t*, CUtensorMapInterleave, CUtensorMapSwizzle,
                             CUtensorMapL2promotion, CUtensorMapFloatOOBfill);

void make_map(EncodeFn fn, CUtensorMap* m, const void* ptr, int rank, const cuuint64_t* dims, const cuuint64_t* strides, const cuuint32_t* box) {
  const cuuint32_t es[3] = {1, 1, 1};
  fn(m, CU_TENSOR_MAP_DATA_TYPE_BFLOAT16, rank, const_cast<void*>(ptr), dims, strides, box, es, CU_TENSOR_MAP_INTERLEAVE_NONE,
     CU_TENSOR_MAP_SWIZZLE_128B, CU_TENSOR_MAP_L2_PROMOTION_L2_128B, CU_TENSOR_MAP_FLOAT_OOB_FILL_NONE);
}

}

extern "C" void kernel_launch(void* const* d_in, const int* in_sizes, int n_in, void* d_out, int out_size) {
  (void)in_sizes; (void)n_in; (void)out_size;
  void* fnp = nullptr;
  cudaDriverEntryPointQueryResult qr;
  cudaGetDriverEntryPoint("cuTensorMapEncodeTiled", &fnp, cudaEnableDefault, &qr);
  EncodeFn fn = (EncodeFn)fnp;
  Params p;
  p.x = (const __nv_bfloat16*)d_in[0];
  p.a_re = (const __nv_bfloat16*)d_in[1]; p.a_im = (const __nv_bfloat16*)d_in[2];
  p.b_re = (const __nv_bfloat16*)d_in[3]; p.b_im = (const __nv_bfloat16*)d_in[4];
  p.c_re = (const __nv_bfloat16*)d_in[5]; p.c_im = (const __nv_bfloat16*)d_in[6];
  p.log_dt = (const __nv_bfloat16*)d_in[7]; p.dskip = (const __nv_bfloat16*)d_in[8];
  p.w1 = (const __nv_bfloat16*)d_in[10]; p.b1 = (const __nv_bfloat16*)d_in[11];
  p.w2 = (const __nv_bfloat16*)d_in[12]; p.b2 = (const __nv_bfloat16*)d_in[13];
  void* sp = nullptr;
  cudaGetSymbolAddress(&sp, g_scr);
  p.s = (Scratch*)sp;
  CUtensorMap mx, mw1, mw2, mo;
  {
    const cuuint64_t dims[2] = {448, 2048}, str[1] = {896};
    const cuuint32_t box[2] = {64, 128}, boxo[2] = {64, 16};
    make_map(fn, &mx, p.x, 2, dims, str, box);
    make_map(fn, &mo, d_out, 2, dims, str, boxo);
  }
  {
    const cuuint64_t dims[3] = {64, 448, 28}, str[2] = {3584, 128};
    const cuuint32_t box[3] = {64, 64, 4};
    make_map(fn, &mw1, p.w1, 3, dims, str, box);
  }
  {
    const cuuint64_t dims[2] = {448, 1792}, str[1] = {896};
    const cuuint32_t box[2] = {64, 256};
    make_map(fn, &mw2, p.w2, 2, dims, str, box);
  }
  cudaFuncSetAttribute(fused_kernel, cudaFuncAttributeMaxDynamicSharedMemorySize, SMEM_BYTES);
  fused_kernel<<<NCTA, 384, SMEM_BYTES>>>(p, mx, mw1, mw2, mo);
}
```

```cpp
#include <cuda_runtime.h>
#include <cuda_bf16.h>
#include <cuda_fp16.h>
#include <cuda.h>
#include <stdint.h>

namespace {

constexpr int D_ = 448, NST = 256, F_ = 1792;
constexpr int NRK = 7, NMLP = 112, NCTA = 132;
constexpr int SPIN_MAX = 1 << 20, RETRY_MAX = 512;

struct Scratch {
  unsigned cntA, pad0[31], cntT, pad1[31], epoch, pad2[63];
  uint4 ax[2048];
  uint4 bx[7 * 512];
  uint4 tbl[112 * 329];
  uint4 xnT[224 * 512];
  uint4 s2[16 * 224 * 32];
  uint4 part[16 * 7 * 6 * 1024];
};
__device__ Scratch g_scr;
#define TSTAMP(i)
#define TSINIT()
#define TSDUMP()
extern __shared__ __align__(1024) uint8_t smem_raw[];

constexpr int TBL_SC = 5248, TBL = 5264;
constexpr int TBL_C1 = 2624;
constexpr int SIG = 19584;
constexpr int SIG_U = 0, U_LBO = 656, SIG_V3 = 6272, SIG_V5 = 10368, SIG_V7 = 13440, SIG_V9 = 15488, SIG_V2 = 17536;
constexpr int Y2B = 6528, Y3B = 4352;
constexpr int KSTG = 14 * 2048;
constexpr int OFF_W = 0, OFF_X = 98304, OFF_A = 147456, OFF_B = OFF_A + 2 * SIG + Y3B, OFF_T = OFF_B + 16896;
constexpr int OFF_M = OFF_T + 15872;
constexpr int B_AX = Y2B, B_BX = B_AX + 2048;
constexpr int M_BAR = 0, M_REL = 128, M_EP = 192, M_CSR = 256, M_LT = 1280, M_MX = 1536, M_END = 1664;
constexpr int SMEM_BYTES = OFF_M + M_END + 384;
constexpr int S_WORK = 63232, S_WGB = 2 * SIG + Y2B + Y3B;
static_assert(OFF_A + 2 * KSTG <= OFF_T && S_WORK + 3 * S_WGB <= OFF_M && SMEM_BYTES <= 232448, "smem");

struct Params {
  const __nv_bfloat16 *x, *a_re, *a_im, *b_re, *b_im, *c_re, *c_im, *log_dt, *dskip, *w1, *b1, *w2, *b2;
  Scratch* s;
};

__device__ __forceinline__ int opaque(int x) { int v; asm volatile("mov.u32 %0, %1;" : "=r"(v) : "r"(x)); return v; }
__device__ __forceinline__ int rd_bid() { int v; asm volatile("mov.u32 %0, %%ctaid.x;" : "=r"(v)); return v; }
__device__ __forceinline__ uint32_t smem_u32(const void* p) { return (uint32_t)__cvta_generic_to_shared(p); }
__device__ __forceinline__ void mbar_init(uint32_t bar, int cnt) { asm volatile("mbarrier.init.shared::cta.b64 [%0], %1;" ::"r"(bar), "r"(cnt)); }
__device__ __forceinline__ void mbar_expect(uint32_t bar, uint32_t bytes) {
  asm volatile("mbarrier.arrive.expect_tx.shared::cta.b64 _, [%0], %1;" ::"r"(bar), "r"(bytes) : "memory");
}
__device__ __forceinline__ void mbar_wait(uint32_t bar, uint32_t parity) {
  uint32_t done = 0;
#pragma unroll 1
  for (int it = 0; it < SPIN_MAX; it++) {
    asm volatile("{.reg .pred p; mbarrier.try_wait.parity.shared::cta.b64 p, [%1], %2; selp.u32 %0,1,0,p;}"
                 : "=r"(done) : "r"(bar), "r"(parity) : "memory");
    if (done) break;
  }
}
__device__ __forceinline__ void tma_2d(uint32_t dst, const CUtensorMap* m, int c0, int c1, uint32_t bar) {
  asm volatile("cp.async.bulk.tensor.2d.shared::cluster.global.mbarrier::complete_tx::bytes [%0], [%1, {%3, %4}], [%2];"
               ::"r"(dst), "l"(m), "r"(bar), "r"(c0), "r"(c1) : "memory");
}
__device__ __forceinline__ void tma_3d(uint32_t dst, const CUtensorMap* m, int c0, int c1, int c2, uint32_t bar) {
  asm volatile("cp.async.bulk.tensor.3d.shared::cluster.global.mbarrier::complete_tx::bytes [%0], [%1, {%3, %4, %5}], [%2];"
               ::"r"(dst), "l"(m), "r"(bar), "r"(c0), "r"(c1), "r"(c2) : "memory");
}
__device__ __forceinline__ void tma_store_2d(const CUtensorMap* m, uint32_t src, int c0, int c1) {
  asm volatile("cp.async.bulk.tensor.2d.global.shared::cta.bulk_group [%0, {%2, %3}], [%1];"
               ::"l"(m), "r"(src), "r"(c0), "r"(c1) : "memory");
}
__device__ __forceinline__ void bulk_s2g(void* dst, uint32_t src, uint32_t bytes) {
  asm volatile("cp.async.bulk.global.shared::cta.bulk_group [%0], [%1], %2;" ::"l"(dst), "r"(src), "r"(bytes) : "memory");
}
__device__ __forceinline__ void bulk_g2s(uint32_t dst, const void* src, uint32_t bytes, uint32_t bar) {
  asm volatile("cp.async.bulk.shared::cluster.global.mbarrier::complete_tx::bytes [%0], [%1], %2, [%3];"
               ::"r"(dst), "l"(src), "r"(bytes), "r"(bar) : "memory");
}
__device__ __forceinline__ void bulk_commit() { asm volatile("cp.async.bulk.commit_group;" ::: "memory"); }
__device__ __forceinline__ void bulk_wait0() { asm volatile("cp.async.bulk.wait_group 0;" ::: "memory"); }
__device__ __forceinline__ void bulk_wait0_read() { asm volatile("cp.async.bulk.wait_group.read 0;" ::: "memory"); }
__device__ __forceinline__ void fence_async() { asm volatile("fence.proxy.async.shared::cta;" ::: "memory"); }
__device__ __forceinline__ void bar_sync(int id, int n) { asm volatile("bar.sync %0, %1;" ::"r"(id), "r"(n) : "memory"); }
__device__ __forceinline__ void bar_arrive(int id, int n) { asm volatile("bar.arrive %0, %1;" ::"r"(id), "r"(n) : "memory"); }
__device__ __forceinline__ void wg_fence() { asm volatile("wgmma.fence.sync.aligned;" ::: "memory"); }
__device__ __forceinline__ void wg_commit() { asm volatile("wgmma.commit_group.sync.aligned;" ::: "memory"); }
template <int N> __device__ __forceinline__ void wg_wait() { asm volatile("wgmma.wait_group.sync.aligned %0;" ::"n"(N) : "memory"); }
template <int N> __device__ __forceinline__ void fence_regs(float* d) {
#pragma unroll
  for (int i = 0; i < N; i++) asm volatile("" : "+f"(d[i])::"memory");
}
__device__ __forceinline__ uint64_t mkdesc(uint32_t addr, uint32_t lbo, uint32_t sbo, uint32_t sw) {
  return (uint64_t)((addr & 0x3FFFF) >> 4) | ((uint64_t)(lbo >> 4) << 16) | ((uint64_t)(sbo >> 4) << 32) | ((uint64_t)sw << 62);
}
__device__ __forceinline__ uint32_t lds32(uint32_t a) { uint32_t v; asm volatile("ld.shared.b32 %0, [%1];" : "=r"(v) : "r"(a) : "memory"); return v; }
__device__ __forceinline__ float lds32f(uint32_t a) { float v; asm volatile("ld.shared.f32 %0, [%1];" : "=f"(v) : "r"(a) : "memory"); return v; }
__device__ __forceinline__ float2 lds64f(uint32_t a) { float2 v; asm volatile("ld.shared.v2.f32 {%0,%1}, [%2];" : "=f"(v.x), "=f"(v.y) : "r"(a) : "memory"); return v; }
__device__ __forceinline__ uint4 lds128(uint32_t a) {
  uint4 v; asm volatile("ld.shared.v4.b32 {%0,%1,%2,%3}, [%4];" : "=r"(v.x), "=r"(v.y), "=r"(v.z), "=r"(v.w) : "r"(a) : "memory"); return v;
}
__device__ __forceinline__ void sts16(uint32_t a, uint16_t v) { asm volatile("st.shared.b16 [%0], %1;" ::"r"(a), "h"(v) : "memory"); }
__device__ __forceinline__ void sts32f(uint32_t a, float v) { asm volatile("st.shared.f32 [%0], %1;" ::"r"(a), "f"(v) : "memory"); }
__device__ __forceinline__ void sts64f(uint32_t a, float x, float y) { asm volatile("st.shared.v2.f32 [%0], {%1,%2};" ::"r"(a), "f"(x), "f"(y) : "memory"); }
__device__ __forceinline__ void sts128(uint32_t a, uint32_t x, uint32_t y, uint32_t z, uint32_t w) {
  asm volatile("st.shared.v4.b32 [%0], {%1,%2,%3,%4};" ::"r"(a), "r"(x), "r"(y), "r"(z), "r"(w) : "memory");
}
__device__ __forceinline__ void ldsm4(uint32_t a, uint32_t& r0, uint32_t& r1, uint32_t& r2, uint32_t& r3) {
  asm volatile("ldmatrix.sync.aligned.m8n8.x4.shared.b16 {%0,%1,%2,%3}, [%4];" : "=r"(r0), "=r"(r1), "=r"(r2), "=r"(r3) : "r"(a) : "memory");
}
__device__ __forceinline__ void ldsm4t(uint32_t a, uint32_t& r0, uint32_t& r1, uint32_t& r2, uint32_t& r3) {
  asm volatile("ldmatrix.sync.aligned.m8n8.x4.trans.shared.b16 {%0,%1,%2,%3}, [%4];" : "=r"(r0), "=r"(r1), "=r"(r2), "=r"(r3) : "r"(a) : "memory");
}
__device__ __forceinline__ void stsm4(uint32_t a, uint32_t r0, uint32_t r1, uint32_t r2, uint32_t r3) {
  asm volatile("stmatrix.sync.aligned.m8n8.x4.shared.b16 [%0], {%1,%2,%3,%4};" ::"r"(a), "r"(r0), "r"(r1), "r"(r2), "r"(r3) : "memory");
}
__device__ __forceinline__ void mma_bf16(float* c, uint32_t a0, uint32_t a1, uint32_t a2, uint32_t a3, uint32_t b0, uint32_t b1) {
  asm("mma.sync.aligned.m16n8k16.row.col.f32.bf16.bf16.f32 {%0,%1,%2,%3},{%4,%5,%6,%7},{%8,%9},{%0,%1,%2,%3};"
      : "+f"(c[0]), "+f"(c[1]), "+f"(c[2]), "+f"(c[3]) : "r"(a0), "r"(a1), "r"(a2), "r"(a3), "r"(b0), "r"(b1));
}
__device__ __forceinline__ uint4 ld_relaxed4(const void* p) {
  uint4 v; asm volatile("ld.relaxed.gpu.global.v4.b32 {%0,%1,%2,%3}, [%4];" : "=r"(v.x), "=r"(v.y), "=r"(v.z), "=r"(v.w) : "l"(p) : "memory"); return v;
}
__device__ __forceinline__ uint4 ld_2x64(const void* p) {
  uint4 v;
  asm volatile("{.reg .b64 a, c; ld.relaxed.gpu.global.v2.b64 {a, c}, [%4]; mov.b64 {%0,%1}, a; mov.b64 {%2,%3}, c;}"
               : "=r"(v.x), "=r"(v.y), "=r"(v.z), "=r"(v.w) : "l"(p) : "memory");
  return v;
}
__device__ __forceinline__ void st_relaxed2(void* p, uint32_t x, uint32_t y) {
  asm volatile("st.relaxed.gpu.global.v2.b32 [%0], {%1,%2};" ::"l"(p), "r"(x), "r"(y) : "memory");
}
__device__ __forceinline__ uint4 ld_b128(const void* p) {
  uint4 v;
  asm volatile("{.reg .b128 t; .reg .b64 a, c; ld.relaxed.gpu.global.b128 t, [%4]; mov.b128 {a, c}, t; mov.b64 {%0,%1}, a; mov.b64 {%2,%3}, c;}"
               : "=r"(v.x), "=r"(v.y), "=r"(v.z), "=r"(v.w) : "l"(p) : "memory");
  return v;
}
__device__ __forceinline__ void st_b128(void* p, uint32_t tag, uint32_t x, uint32_t y, uint32_t z, uint32_t w) {
  asm volatile("{.reg .b128 t; .reg .b64 a, c; mov.b64 a, {%1,%2}; mov.b64 c, {%3,%4}; mov.b128 t, {a, c}; st.relaxed.gpu.global.b128 [%0], t;}"
               ::"l"(p), "r"((x & ~1u) | tag), "r"(y), "r"(z), "r"(w) : "memory");
}
__device__ __forceinline__ unsigned ld_relaxed1(const unsigned* p) {
  unsigned v; asm volatile("ld.relaxed.gpu.global.u32 %0, [%1];" : "=r"(v) : "l"(p) : "memory"); return v;
}
__device__ __forceinline__ void red_relaxed(unsigned* p) {
  asm volatile("red.relaxed.gpu.global.add.u32 [%0], 1;" ::"l"(p) : "memory");
}
__device__ __forceinline__ void red_release(unsigned* p) {
  asm volatile("red.release.gpu.global.add.u32 [%0], 1;" ::"l"(p) : "memory");
}
__device__ __forceinline__ void wait_count(const unsigned* p, unsigned target) {
#pragma unroll 1
  for (int it = 0; it < SPIN_MAX; it++) {
    if ((int)(ld_relaxed1(p) - target) >= 0) break;
    __nanosleep(40);
  }
  asm volatile("fence.acq_rel.gpu;" ::: "memory");
}
__device__ __forceinline__ uint32_t pack_h2(float lo, float hi) { uint32_t r; asm("cvt.rn.f16x2.f32 %0, %1, %2;" : "=r"(r) : "f"(hi), "f"(lo)); return r; }
__device__ __forceinline__ uint32_t pack_bf2(float lo, float hi) { uint32_t r; asm("cvt.rn.bf16x2.f32 %0, %1, %2;" : "=r"(r) : "f"(hi), "f"(lo)); return r; }
__device__ __forceinline__ float bf_lo(uint32_t w) { return __uint_as_float(w << 16); }
__device__ __forceinline__ float bf_hi(uint32_t w) { return __uint_as_float(w & 0xffff0000u); }
__device__ __forceinline__ float rbf(float v) { return __bfloat162float(__float2bfloat16_rn(v)); }
__device__ __forceinline__ float2 h2f(uint32_t w) { return __half22float2(*reinterpret_cast<__half2*>(&w)); }
__device__ __forceinline__ float ex2f(float v) { float r; asm("ex2.approx.ftz.f32 %0, %1;" : "=f"(r) : "f"(v)); return r; }
__device__ __forceinline__ float rcpf_(float v) { float r; asm("rcp.approx.f32 %0, %1;" : "=f"(r) : "f"(v)); return r; }
__device__ __forceinline__ float sqrtf_(float v) { float r; asm("sqrt.approx.f32 %0, %1;" : "=f"(r) : "f"(v)); return r; }
__device__ __forceinline__ float tanhf_(float v) { float r; asm volatile("tanh.approx.f32 %0, %1;" : "=f"(r) : "f"(v)); return r; }

__device__ __forceinline__ void wg_ss_bf16_n256(float* d, uint64_t da, uint64_t db, int sc) {
  asm volatile("{.reg .pred p; setp.ne.b32 p, %130, 0;\n"
    "wgmma.mma_async.sync.aligned.m64n256k16.f32.bf16.bf16 {%0, %1, %2, %3, %4, %5, %6, %7, %8, %9, %10, %11, %12, %13, %14, %15, %16, %17, %18, %19, %20, %21, %22, %23, %24, %25, %26, %27, %28, %29, %30, %31, %32, %33, %34, %35, %36, %37, %38, %39, %40, %41, %42, %43, %44, %45, %46, %47, %48, %49, %50, %51, %52, %53, %54, %55, %56, %57, %58, %59, %60, %61, %62, %63, %64, %65, %66, %67, %68, %69, %70, %71, %72, %73, %74, %75, %76, %77, %78, %79, %80, %81, %82, %83, %84, %85, %86, %87, %88, %89, %90, %91, %92, %93, %94, %95, %96, %97, %98, %99, %100, %101, %102, %103, %104, %105, %106, %107, %108, %109, %110, %111, %112, %113, %114, %115, %116, %117, %118, %119, %120, %121, %122, %123, %124, %125, %126, %127}, %128, %129, p, 1, 1, 0, 1;}\n"
    : "+f"(d[0]), "+f"(d[1]), "+f"(d[2]), "+f"(d[3]), "+f"(d[4]), "+f"(d[5]), "+f"(d[6]), "+f"(d[7]), "+f"(d[8]), "+f"(d[9]), "+f"(d[10]), "+f"(d[11]), "+f"(d[12]), "+f"(d[13]), "+f"(d[14]), "+f"(d[15]), "+f"(d[16]), "+f"(d[17]), "+f"(d[18]), "+f"(d[19]), "+f"(d[20]), "+f"(d[21]), "+f"(d[22]), "+f"(d[23]), "+f"(d[24]), "+f"(d[25]), "+f"(d[26]), "+f"(d[27]), "+f"(d[28]), "+f"(d[29]), "+f"(d[30]), "+f"(d[31]), "+f"(d[32]), "+f"(d[33]), "+f"(d[34]), "+f"(d[35]), "+f"(d[36]), "+f"(d[37]), "+f"(d[38]), "+f"(d[39]), "+f"(d[40]), "+f"(d[41]), "+f"(d[42]), "+f"(d[43]), "+f"(d[44]), "+f"(d[45]), "+f"(d[46]), "+f"(d[47]), "+f"(d[48]), "+f"(d[49]), "+f"(d[50]), "+f"(d[51]), "+f"(d[52]), "+f"(d[53]), "+f"(d[54]), "+f"(d[55]), "+f"(d[56]), "+f"(d[57]), "+f"(d[58]), "+f"(d[59]), "+f"(d[60]), "+f"(d[61]), "+f"(d[62]), "+f"(d[63]), "+f"(d[64]), "+f"(d[65]), "+f"(d[66]), "+f"(d[67]), "+f"(d[68]), "+f"(d[69]), "+f"(d[70]), "+f"(d[71]), "+f"(d[72]), "+f"(d[73]), "+f"(d[74]), "+f"(d[75]), "+f"(d[76]), "+f"(d[77]), "+f"(d[78]), "+f"(d[79]), "+f"(d[80]), "+f"(d[81]), "+f"(d[82]), "+f"(d[83]), "+f"(d[84]), "+f"(d[85]), "+f"(d[86]), "+f"(d[87]), "+f"(d[88]), "+f"(d[89]), "+f"(d[90]), "+f"(d[91]), "+f"(d[92]), "+f"(d[93]), "+f"(d[94]), "+f"(d[95]), "+f"(d[96]), "+f"(d[97]), "+f"(d[98]), "+f"(d[99]), "+f"(d[100]), "+f"(d[101]), "+f"(d[102]), "+f"(d[103]), "+f"(d[104]), "+f"(d[105]), "+f"(d[106]), "+f"(d[107]), "+f"(d[108]), "+f"(d[109]), "+f"(d[110]), "+f"(d[111]), "+f"(d[112]), "+f"(d[113]), "+f"(d[114]), "+f"(d[115]), "+f"(d[116]), "+f"(d[117]), "+f"(d[118]), "+f"(d[119]), "+f"(d[120]), "+f"(d[121]), "+f"(d[122]), "+f"(d[123]), "+f"(d[124]), "+f"(d[125]), "+f"(d[126]), "+f"(d[127])
    : "l"(da), "l"(db), "r"(sc));
}

__device__ __forceinline__ void wg_ss_bf16_n256k(float* d, uint64_t da, uint64_t db, int sc) {
  asm volatile("{.reg .pred p; setp.ne.b32 p, %130, 0;\n"
    "wgmma.mma_async.sync.aligned.m64n256k16.f32.bf16.bf16 {%0, %1, %2, %3, %4, %5, %6, %7, %8, %9, %10, %11, %12, %13, %14, %15, %16, %17, %18, %19, %20, %21, %22, %23, %24, %25, %26, %27, %28, %29, %30, %31, %32, %33, %34, %35, %36, %37, %38, %39, %40, %41, %42, %43, %44, %45, %46, %47, %48, %49, %50, %51, %52, %53, %54, %55, %56, %57, %58, %59, %60, %61, %62, %63, %64, %65, %66, %67, %68, %69, %70, %71, %72, %73, %74, %75, %76, %77, %78, %79, %80, %81, %82, %83, %84, %85, %86, %87, %88, %89, %90, %91, %92, %93, %94, %95, %96, %97, %98, %99, %100, %101, %102, %103, %104, %105, %106, %107, %108, %109, %110, %111, %112, %113, %114, %115, %116, %117, %118, %119, %120, %121, %122, %123, %124, %125, %126, %127}, %128, %129, p, 1, 1, 0, 0;}\n"
    : "+f"(d[0]), "+f"(d[1]), "+f"(d[2]), "+f"(d[3]), "+f"(d[4]), "+f"(d[5]), "+f"(d[6]), "+f"(d[7]), "+f"(d[8]), "+f"(d[9]), "+f"(d[10]), "+f"(d[11]), "+f"(d[12]), "+f"(d[13]), "+f"(d[14]), "+f"(d[15]), "+f"(d[16]), "+f"(d[17]), "+f"(d[18]), "+f"(d[19]), "+f"(d[20]), "+f"(d[21]), "+f"(d[22]), "+f"(d[23]), "+f"(d[24]), "+f"(d[25]), "+f"(d[26]), "+f"(d[27]), "+f"(d[28]), "+f"(d[29]), "+f"(d[30]), "+f"(d[31]), "+f"(d[32]), "+f"(d[33]), "+f"(d[34]), "+f"(d[35]), "+f"(d[36]), "+f"(d[37]), "+f"(d[38]), "+f"(d[39]), "+f"(d[40]), "+f"(d[41]), "+f"(d[42]), "+f"(d[43]), "+f"(d[44]), "+f"(d[45]), "+f"(d[46]), "+f"(d[47]), "+f"(d[48]), "+f"(d[49]), "+f"(d[50]), "+f"(d[51]), "+f"(d[52]), "+f"(d[53]), "+f"(d[54]), "+f"(d[55]), "+f"(d[56]), "+f"(d[57]), "+f"(d[58]), "+f"(d[59]), "+f"(d[60]), "+f"(d[61]), "+f"(d[62]), "+f"(d[63]), "+f"(d[64]), "+f"(d[65]), "+f"(d[66]), "+f"(d[67]), "+f"(d[68]), "+f"(d[69]), "+f"(d[70]), "+f"(d[71]), "+f"(d[72]), "+f"(d[73]), "+f"(d[74]), "+f"(d[75]), "+f"(d[76]), "+f"(d[77]), "+f"(d[78]), "+f"(d[79]), "+f"(d[80]), "+f"(d[81]), "+f"(d[82]), "+f"(d[83]), "+f"(d[84]), "+f"(d[85]), "+f"(d[86]), "+f"(d[87]), "+f"(d[88]), "+f"(d[89]), "+f"(d[90]), "+f"(d[91]), "+f"(d[92]), "+f"(d[93]), "+f"(d[94]), "+f"(d[95]), "+f"(d[96]), "+f"(d[97]), "+f"(d[98]), "+f"(d[99]), "+f"(d[100]), "+f"(d[101]), "+f"(d[102]), "+f"(d[103]), "+f"(d[104]), "+f"(d[105]), "+f"(d[106]), "+f"(d[107]), "+f"(d[108]), "+f"(d[109]), "+f"(d[110]), "+f"(d[111]), "+f"(d[112]), "+f"(d[113]), "+f"(d[114]), "+f"(d[115]), "+f"(d[116]), "+f"(d[117]), "+f"(d[118]), "+f"(d[119]), "+f"(d[120]), "+f"(d[121]), "+f"(d[122]), "+f"(d[123]), "+f"(d[124]), "+f"(d[125]), "+f"(d[126]), "+f"(d[127])
    : "l"(da), "l"(db), "r"(sc));
}

__device__ __forceinline__ void wg_rs_bf16_n64(float* d, uint32_t a0, uint32_t a1, uint32_t a2, uint32_t a3, uint64_t db, int sc) {
  asm volatile("{.reg .pred p; setp.ne.b32 p, %37, 0;\n"
    "wgmma.mma_async.sync.aligned.m64n64k16.f32.bf16.bf16 {%0, %1, %2, %3, %4, %5, %6, %7, %8, %9, %10, %11, %12, %13, %14, %15, %16, %17, %18, %19, %20, %21, %22, %23, %24, %25, %26, %27, %28, %29, %30, %31}, {%32,%33,%34,%35}, %36, p, 1, 1, 1;}\n"
    : "+f"(d[0]), "+f"(d[1]), "+f"(d[2]), "+f"(d[3]), "+f"(d[4]), "+f"(d[5]), "+f"(d[6]), "+f"(d[7]), "+f"(d[8]), "+f"(d[9]), "+f"(d[10]), "+f"(d[11]), "+f"(d[12]), "+f"(d[13]), "+f"(d[14]), "+f"(d[15]), "+f"(d[16]), "+f"(d[17]), "+f"(d[18]), "+f"(d[19]), "+f"(d[20]), "+f"(d[21]), "+f"(d[22]), "+f"(d[23]), "+f"(d[24]), "+f"(d[25]), "+f"(d[26]), "+f"(d[27]), "+f"(d[28]), "+f"(d[29]), "+f"(d[30]), "+f"(d[31])
    : "r"(a0), "r"(a1), "r"(a2), "r"(a3), "l"(db), "r"(sc));
}

__device__ __forceinline__ void wg_rs_f16_n32k(float* d, uint32_t a0, uint32_t a1, uint32_t a2, uint32_t a3, uint64_t db, int sc) {
  asm volatile("{.reg .pred p; setp.ne.b32 p, %21, 0;\n"
    "wgmma.mma_async.sync.aligned.m64n32k16.f32.f16.f16 {%0, %1, %2, %3, %4, %5, %6, %7, %8, %9, %10, %11, %12, %13, %14, %15}, {%16,%17,%18,%19}, %20, p, 1, 1, 0;}\n"
    : "+f"(d[0]), "+f"(d[1]), "+f"(d[2]), "+f"(d[3]), "+f"(d[4]), "+f"(d[5]), "+f"(d[6]), "+f"(d[7]), "+f"(d[8]), "+f"(d[9]), "+f"(d[10]), "+f"(d[11]), "+f"(d[12]), "+f"(d[13]), "+f"(d[14]), "+f"(d[15])
    : "r"(a0), "r"(a1), "r"(a2), "r"(a3), "l"(db), "r"(sc));
}

__device__ __forceinline__ void wg_rs_f16_n24t(float* d, uint32_t a0, uint32_t a1, uint32_t a2, uint32_t a3, uint64_t db, int sc) {
  asm volatile("{.reg .pred p; setp.ne.b32 p, %17, 0;\n"
    "wgmma.mma_async.sync.aligned.m64n24k16.f32.f16.f16 {%0, %1, %2, %3, %4, %5, %6, %7, %8, %9, %10, %11}, {%12,%13,%14,%15}, %16, p, 1, 1, 1;}\n"
    : "+f"(d[0]), "+f"(d[1]), "+f"(d[2]), "+f"(d[3]), "+f"(d[4]), "+f"(d[5]), "+f"(d[6]), "+f"(d[7]), "+f"(d[8]), "+f"(d[9]), "+f"(d[10]), "+f"(d[11])
    : "r"(a0), "r"(a1), "r"(a2), "r"(a3), "l"(db), "r"(sc));
}

__device__ __forceinline__ void wg_rs_f16_n16t(float* d, uint32_t a0, uint32_t a1, uint32_t a2, uint32_t a3, uint64_t db, int sc) {
  asm volatile("{.reg .pred p; setp.ne.b32 p, %13, 0;\n"
    "wgmma.mma_async.sync.aligned.m64n16k16.f32.f16.f16 {%0, %1, %2, %3, %4, %5, %6, %7}, {%8,%9,%10,%11}, %12, p, 1, 1, 1;}\n"
    : "+f"(d[0]), "+f"(d[1]), "+f"(d[2]), "+f"(d[3]), "+f"(d[4]), "+f"(d[5]), "+f"(d[6]), "+f"(d[7])
    : "r"(a0), "r"(a1), "r"(a2), "r"(a3), "l"(db), "r"(sc));
}

__device__ __forceinline__ void wg_ss_f16_n48t(float* d, uint64_t da, uint64_t db, int sc) {
  asm volatile("{.reg .pred p; setp.ne.b32 p, %26, 0;\n"
    "wgmma.mma_async.sync.aligned.m64n48k16.f32.f16.f16 {%0, %1, %2, %3, %4, %5, %6, %7, %8, %9, %10, %11, %12, %13, %14, %15, %16, %17, %18, %19, %20, %21, %22, %23}, %24, %25, p, 1, 1, 1, 1;}\n"
    : "+f"(d[0]), "+f"(d[1]), "+f"(d[2]), "+f"(d[3]), "+f"(d[4]), "+f"(d[5]), "+f"(d[6]), "+f"(d[7]), "+f"(d[8]), "+f"(d[9]), "+f"(d[10]), "+f"(d[11]), "+f"(d[12]), "+f"(d[13]), "+f"(d[14]), "+f"(d[15]), "+f"(d[16]), "+f"(d[17]), "+f"(d[18]), "+f"(d[19]), "+f"(d[20]), "+f"(d[21]), "+f"(d[22]), "+f"(d[23])
    : "l"(da), "l"(db), "r"(sc));
}

struct cf { float x, y; };
__device__ __forceinline__ cf cmul(cf a, cf b) { cf r; r.x = fmaf(a.x, b.x, -a.y * b.y); r.y = fmaf(a.x, b.y, a.y * b.x); return r; }
__device__ __forceinline__ cf zpow(float rho2, float phi, float e) {
  const float m = ex2f(rho2 * e), ang = phi * e;
  cf r; r.x = m * __cosf(ang); r.y = m * __sinf(ang); return r;
}
__device__ __forceinline__ __half2 H2(uint32_t v) { return *reinterpret_cast<__half2*>(&v); }
__device__ __forceinline__ uint32_t U32(__half2 v) { return *reinterpret_cast<uint32_t*>(&v); }
struct h2c { __half2 x, y; };
template <bool CONJ>
__device__ __forceinline__ void hprod2(uint32_t re, uint32_t im, h2c r, uint32_t& ore, uint32_t& oim) {
  if (CONJ) {
    ore = U32(__hfma2(H2(re), r.x, __hmul2(H2(im), r.y)));
    oim = U32(__hfma2(H2(im), r.x, __hneg2(__hmul2(H2(re), r.y))));
  } else {
    ore = U32(__hfma2(H2(re), r.x, __hneg2(__hmul2(H2(im), r.y))));
    oim = U32(__hfma2(H2(re), r.y, __hmul2(H2(im), r.x)));
  }
}
__device__ __forceinline__ cf csq(cf a) { cf r; r.x = fmaf(a.x, a.x, -a.y * a.y); r.y = (a.x + a.x) * a.y; return r; }
__device__ __forceinline__ cf cmulc(cf a, cf b) { cf r; r.x = fmaf(a.x, b.x, a.y * b.y); r.y = fmaf(a.y, b.x, -a.x * b.y); return r; }
__device__ __forceinline__ h2c pk(cf a) { h2c r; r.x = H2(pack_h2(a.x, a.x)); r.y = H2(pack_h2(a.y, a.y)); return r; }
__device__ __forceinline__ uint32_t ldg32(const void* p, int o) { uint32_t v; asm volatile("ld.global.nc.b32 %0, [%1];" : "=r"(v) : "l"((const char*)p + o)); return v; }
__device__ __forceinline__ uint32_t hadd2u(uint32_t a, uint32_t b) { return U32(__hadd2(H2(a), H2(b))); }

struct KgIn { uint32_t cur[6], nxt[6], ldt, dk; bool odd; };
__device__ __forceinline__ float pow2_floor(float v) { return __uint_as_float(__float_as_uint(fminf(fmaxf(v, 1e-30f), 1e30f)) & 0x7f800000u); }
template <class Mid0, class Mid1>
__device__ __forceinline__ void kgen_wg(KgIn& k, int nw, uint32_t stg, uint32_t tbl, uint32_t mxa, int w, int lane, int barid, Mid0 mid0, Mid1 mid1) {
  float dl, dt, inv_sc;
  {
    const uint32_t M = 0x7fff7fffu;
    uint32_t mx[2];
#pragma unroll
    for (int i = 0; i < 2; i++) {
      const uint32_t m = __vmaxu2(__vmaxu2(k.cur[2 + 2 * i] & M, k.cur[3 + 2 * i] & M), __vmaxu2(k.nxt[2 + 2 * i] & M, k.nxt[3 + 2 * i] & M));
      mx[i] = __reduce_max_sync(0xffffffffu, max(m << 16, m & 0xffff0000u));
    }
    if (lane == 0) sts32f(mxa + w * 4, __uint_as_float(mx[0]) * __uint_as_float(mx[1]));
    dt = rbf(ex2f((k.odd ? bf_hi(k.ldt) : bf_lo(k.ldt)) * 1.4426950408889634f));
    const float dsk = (k.odd ? bf_hi(k.dk) : bf_lo(k.dk)) * rcpf_(dt);
    bar_sync(barid, 128);
    const float2 m0 = lds64f(mxa + (w & 2) * 4), m1 = lds64f(mxa + (nw == 1 ? (w & 2) ^ 2 : (w & 2)) * 4);
    const float sc = pow2_floor(fmaxf(0.125f * fmaxf(fmaxf(m0.x, m0.y), fmaxf(m1.x, m1.y)), fabsf(dsk) * (1.f / 4096.f)));
    inv_sc = rcpf_(sc);
    if (lane == 0) sts64f(tbl + TBL_SC + 8, dt * sc, dsk * inv_sc);
    dl = dt * 1.4426950408889634f;
  }
  const uint32_t sa = stg + (w >> 1) * 8192 + (32 * (w & 1) + lane) * 16, sc_ = sa + 16384 - (w >> 1) * 2048;
  const uint64_t dA = mkdesc(stg, 128, 2048, 0), dB = mkdesc(stg + 16384, 128, 2048, 0);
  float acc[24];
#pragma unroll 1
  for (int it = 0; it < 2 * nw; it++) {
    const uint32_t sel = (it & 1) ? 0x3244u : 0x1044u;
    float v[6];
#pragma unroll
    for (int i = 0; i < 6; i++) { v[i] = __uint_as_float(__byte_perm(k.cur[i], 0, sel)); if (it == 1) k.cur[i] = k.nxt[i]; }
    const float rho2 = v[0] * dl, phi = v[1] * dt;
    const cf bb = {v[2] * inv_sc, v[3] * -inv_sc}, cc = {v[4], v[5]};
    const cf X0 = cmulc(bb, cc);
    const cf z1 = zpow(rho2, phi, 1.f), z64 = zpow(rho2, phi, 64.f);
    const cf z2 = csq(z1), z3 = cmul(z2, z1), z4 = csq(z2), z8 = csq(z4), z16 = csq(z8), z24 = cmul(z16, z8), z32 = csq(z16);
    const cf z128 = csq(z64), y1 = csq(z128), y2 = csq(y1), y3 = cmul(y2, y1), y4 = csq(y2);
    const cf X4 = cmulc(X0, z4), W4 = cmulc(X0, y4), W8 = cmulc(W4, y4), W5 = cmulc(W4, y1);
    uint32_t re[4], im[4], r2[4], i2[4];
    re[0] = pack_h2(X0.x, X4.x); im[0] = pack_h2(X0.y, X4.y);
    hprod2<true>(re[0], im[0], pk(z1), re[1], im[1]);
    hprod2<true>(re[0], im[0], pk(z2), re[2], im[2]);
    hprod2<true>(re[0], im[0], pk(z3), re[3], im[3]);
    const h2c hy1 = pk(y1), hy2 = pk(y2);
    hprod2<true>(re[0], im[0], hy1, r2[0], i2[0]);
    hprod2<true>(re[2], im[2], hy1, r2[1], i2[1]);
    hprod2<true>(re[0], im[0], hy2, r2[2], i2[2]);
    hprod2<true>(re[0], im[0], pk(y3), r2[3], i2[3]);
    wg_wait<0>();
    bar_sync(barid, 128);
    sts128(sc_, re[0], re[1], re[2], re[3]);
    sts128(sc_ + 1024, im[0], im[1], im[2], im[3]);
    sts128(sc_ + 2048, r2[0], r2[1], r2[2], r2[3]);
    sts128(sc_ + 3072, i2[0], i2[1], i2[2], i2[3]);
    re[0] = pack_h2(W4.x, W5.x); im[0] = pack_h2(W4.y, W5.y);
    hprod2<true>(re[0], im[0], hy2, re[1], im[1]);
    sts128(sc_ + 4096, re[0], re[1], pack_h2(W8.x, 0.f), 0u);
    sts128(sc_ + 5120, im[0], im[1], pack_h2(W8.y, 0.f), 0u);
    re[0] = pack_h2(1.f, z32.x); im[0] = pack_h2(0.f, z32.y);
    hprod2<false>(re[0], im[0], pk(z8), re[1], im[1]);
    hprod2<false>(re[0], im[0], pk(z16), re[2], im[2]);
    hprod2<false>(re[0], im[0], pk(z24), re[3], im[3]);
    const h2c h64 = pk(z64), h128 = pk(z128);
#pragma unroll
    for (int j = 0; j < 4; j++) hprod2<false>(re[j], im[j], h64, r2[j], i2[j]);
    sts128(sa, re[0], re[1], re[2], re[3]);
    sts128(sa + 1024, im[0], im[1], im[2], im[3]);
    sts128(sa + 2048, r2[0], r2[1], r2[2], r2[3]);
    sts128(sa + 3072, i2[0], i2[1], i2[2], i2[3]);
    uint32_t r3[4], i3[4], r4[4], i4[4];
#pragma unroll
    for (int j = 0; j < 4; j++) { hprod2<false>(re[j], im[j], h128, r3[j], i3[j]); hprod2<false>(r2[j], i2[j], h128, r4[j], i4[j]); }
    sts128(sa + 4096, r3[0], r3[1], r3[2], r3[3]);
    sts128(sa + 5120, i3[0], i3[1], i3[2], i3[3]);
    sts128(sa + 6144, r4[0], r4[1], r4[2], r4[3]);
    sts128(sa + 7168, i4[0], i4[1], i4[2], i4[3]);
    fence_async();
    bar_sync(barid, 128);
    wg_fence();
#pragma unroll
    for (int ks = 0; ks < 8; ks++) wg_ss_f16_n48t(acc, dA + 16 * ks, dB + 16 * ks, (it | ks) != 0);
    wg_commit();
    if (it == 0) mid0();
    if (it == 1) mid1();
  }
  wg_wait<0>();
  fence_regs<24>(acc);
  bar_sync(barid, 128);
#pragma unroll
  for (int h = 0; h < 2; h++)
#pragma unroll
    for (int nt = 0; nt < 3; nt++) {
      const int i = 4 * nt + 2 * h;
      sts64f(stg + (w * 2 + h) * 768 + nt * 256 + lane * 8, (w & 2) ? acc[12 + i] : acc[i], (w & 2) ? acc[13 + i] : acc[1 + i]);
    }
}

__device__ __forceinline__ void tput(uint32_t tbl, int X, uint32_t h) {
  sts16(tbl + 2 * (1296 - X), (uint16_t)h);
  sts16(tbl + TBL_C1 + 2 * (1297 - X), (uint16_t)h);
}
__device__ __forceinline__ void ktab_build(uint32_t src, bool two, int q, uint32_t tbl, int lane) {
  const int tq = lane & 3, r = 8 * q + (lane >> 3) + ((lane >> 2) & 1) * 4;
  float v[6];
  src += q * 768 + lane * 8;
#pragma unroll
  for (int nt = 0; nt < 3; nt++) {
    const float2 a = lds64f(src + nt * 256);
    v[2 * nt] = a.x; v[2 * nt + 1] = a.y;
    if (two) { const float2 c = lds64f(src + nt * 256 + 3072); v[2 * nt] += c.x; v[2 * nt + 1] += c.y; }
  }
  const bool first = (r == 0);
  if (first && tq == 0) { v[0] += lds32f(tbl + TBL_SC + 12); sts32f(tbl + TBL_SC, v[4]); }
  const uint32_t h0 = pack_h2(v[0], v[1]), h1 = pack_h2(v[2], v[3]), h2 = pack_h2(v[4], v[5]);
  tput(tbl, 64 + 8 * r + tq, h0);
  tput(tbl, 68 + 8 * r + tq, h0 >> 16);
  const bool lo = tq < 2;
  const int k2 = 32 * (tq - 2) + r;
  const bool sp = first && tq == 2;
  const int Xa = lo ? 320 + 8 * r + 2 * tq : (sp ? 576 : 911 + k2), Xb = lo ? Xa + 4 : 720 + k2;
  tput(tbl, Xa, h1);
  tput(tbl, Xb, h1 >> 16);
  if (tq == 0 || sp) {
    tput(tbl, Xa + 1, h1);
    if (Xa != 320) tput(tbl, Xa - 1, h1);
    const uint32_t hb = sp ? h1 : h1 >> 16, hc = sp ? h2 : h1 >> 16;
    tput(tbl, sp ? 578 : Xb + 1, hb);
    tput(tbl, sp ? 1295 : Xb - 1, hc);
  }
  if (lo) {
    const int X3 = ((r & 1) ? 1104 : 1231) + 32 * tq + (r >> 1);
    tput(tbl, X3 == 1231 ? 975 : X3, h2);
    tput(tbl, X3 + 16, h2 >> 16);
  }
}

__device__ __forceinline__ void sig_windows(uint32_t sig, int t) {
  uint32_t U[20];
#pragma unroll
  for (int c = 0; c < 5; c++) {
    const int kap = 2 * t - 3 + c + 72;
    const uint4 v = lds128(sig + SIG_U + (kap & 7) * U_LBO + (kap >> 3) * 16);
    U[4 * c] = v.x; U[4 * c + 1] = v.y; U[4 * c + 2] = v.z; U[4 * c + 3] = v.w;
  }
  uint32_t O[19], A2[17], A4[17], V2[8], V5[8];
#pragma unroll
  for (int i = 3; i < 19; i++) O[i] = __byte_perm(U[i - 1], U[i], 0x5432);
#pragma unroll
  for (int i = 3; i < 17; i++) A2[i] = hadd2u(U[i], O[i]);
#pragma unroll
  for (int i = 4; i < 17; i++) A4[i] = hadd2u(A2[i], A2[i - 1]);
#pragma unroll
  for (int k = 0; k < 8; k++) { V2[k] = hadd2u(O[11 + k], U[10 + k]); V5[k] = hadd2u(A4[9 + k], U[7 + k]); }
#pragma unroll
  for (int h = 0; h < 2; h++) {
    sts128(sig + SIG_V3 + t * 32 + h * 16, hadd2u(V2[4 * h], O[10 + 4 * h]), hadd2u(V2[4 * h + 1], O[11 + 4 * h]),
           hadd2u(V2[4 * h + 2], O[12 + 4 * h]), hadd2u(V2[4 * h + 3], O[13 + 4 * h]));
    sts128(sig + SIG_V5 + t * 32 + h * 16, V5[4 * h], V5[4 * h + 1], V5[4 * h + 2], V5[4 * h + 3]);
  }
  if (t < 64) {
    uint32_t V7[8], V9[8];
#pragma unroll
    for (int k = 0; k < 8; k++) {
      V7[k] = hadd2u(V5[k], hadd2u(O[10 + k], O[7 + k]));
      V9[k] = hadd2u(hadd2u(A4[6 + k], A4[4 + k]), U[2 + k]);
    }
#pragma unroll
    for (int h = 0; h < 2; h++) {
      sts128(sig + SIG_V7 + h * 1024 + t * 16, V7[4 * h], V7[4 * h + 1], V7[4 * h + 2], V7[4 * h + 3]);
      sts128(sig + SIG_V9 + h * 1024 + t * 16, V9[4 * h], V9[4 * h + 1], V9[4 * h + 2], V9[4 * h + 3]);
      sts128(sig + SIG_V2 + h * 1024 + t * 16, V2[4 * h], V2[4 * h + 1], V2[4 * h + 2], V2[4 * h + 3]);
    }
  }
}

__device__ __forceinline__ void conv_channel(uint32_t tbl, uint32_t sig, uint32_t y2b, uint32_t y3b, float k1024,
                                             int w, int lane, int barid, float* res) {
  const int g = lane >> 2, tq = lane & 3;
  const uint32_t tb = tbl + ((g & 1) ? TBL_C1 + 2 : 0) + 2 * (1296 - (g - 2 * tq)) - 32 * w + 112;
  float a2[12], a3[8];
#pragma unroll
  for (int i = 0; i < 16; i++) res[i] = 0.f;
#pragma unroll
  for (int i = 0; i < 12; i++) a2[i] = 0.f;
#pragma unroll
  for (int q = 0; q < 4; q++) {
    const float2 f = h2f(lds32(sig + SIG_V2 + (q >> 1) * 1024 + (16 * w + 8 * (q & 1) + g) * 16 + tq * 4));
    a3[2 * q] = k1024 * f.x;
    a3[2 * q + 1] = k1024 * f.y;
  }
  const uint32_t sigu = __shfl_sync(0xffffffffu, opaque(sig), 0);
  const uint64_t dU = mkdesc(sigu + SIG_U, U_LBO, 128, 0);
  const uint64_t dV = mkdesc(sigu, 128, 1024, 0);
  fence_regs<16>(res); fence_regs<12>(a2); fence_regs<8>(a3);
  constexpr int LB = 2 * U_LBO / 16;
  uint32_t Rd[43], R2[22], R3[12];
  uint32_t td = tb - 128, t2 = tb - 1440, t3 = tb - 2208;
  uint64_t dd = dU + 9, d2 = dV + (SIG_V3 + 768) / 16, d3 = dV + (SIG_V7 + 768) / 16;
  auto load_group = [&](int gi) {
#pragma unroll
    for (int i = 1; i < 5; i++) Rd[4 * gi + i] = lds32(td - 16 * (4 * gi + i));
    const int e = gi >> 3;
    if ((gi & 7) == 0) { R2[2 * gi + e] = lds32(t2 - 384 * e); R3[gi + e] = lds32(t3 - 256 * e); }
    R2[2 * gi + e + 1] = lds32(t2 - 384 * e - 16 * (2 * (gi & 7) + 1));
    R2[2 * gi + e + 2] = lds32(t2 - 384 * e - 16 * (2 * (gi & 7) + 2));
    if (!(gi & 1)) {
      R3[gi + e + 1] = lds32(t3 - 256 * e - 16 * ((gi & 7) + 1));
      R3[gi + e + 2] = lds32(t3 - 256 * e - 16 * ((gi & 7) + 2));
    }
  };
  auto dense = [&](int n) {
    wg_rs_f16_n32k(res, Rd[2 * n + 1], Rd[2 * n + 2], Rd[2 * n], Rd[2 * n + 1], dd + ((3 - (n & 3)) * LB + 8 - (n >> 2)) - 8, 1);
  };
  Rd[0] = lds32(td);
  load_group(0);
  load_group(1);
#pragma unroll 1
  for (int sg = 0; sg < 2; sg++) {
#pragma unroll
    for (int gi = 0; gi < 8; gi++) {
      wg_fence();
      dense(2 * gi);
      wg_rs_f16_n24t(a2, R2[2 * gi + 1], R2[2 * gi + 2], R2[2 * gi], R2[2 * gi + 1], d2 - (16 * (gi & 3) + 64 * (gi >> 2)), 1);
      dense(2 * gi + 1);
      if (!(gi & 1)) wg_rs_f16_n16t(a3, R3[gi + 1], R3[gi + 2], R3[gi], R3[gi + 1], d3 - 8 * gi, 1);
      wg_commit();
      wg_wait<1>();
      load_group(gi + 2);
    }
#pragma unroll
    for (int i = 0; i < 9; i++) Rd[i] = Rd[32 + i];
#pragma unroll
    for (int i = 0; i < 5; i++) R2[i] = R2[17 + i];
#pragma unroll
    for (int i = 0; i < 3; i++) R3[i] = R3[9 + i];
    td -= 512; t2 -= 384; t3 -= 256;
    dd -= 4; d2 += 256; d3 += 128;
  }
  Rd[9] = lds32(td - 144); Rd[10] = lds32(td - 160);
  wg_fence();
#pragma unroll
  for (int n = 0; n < 5; n++) dense(n);
  wg_commit();
  wg_wait<1>();
  fence_regs<12>(a2); fence_regs<8>(a3);
  bar_sync(barid, 128);
  {
    const uint32_t o2 = y2b + (136 * w + 8 * g + 2 * tq) * 4, o3 = y3b + (272 * w + 16 * g + 2 * tq) * 4;
#pragma unroll
    for (int q = 0; q < 6; q++) sts64f(o2 + (544 * (q >> 1) + 64 * (q & 1)) * 4, a2[2 * q], a2[2 * q + 1]);
#pragma unroll
    for (int q = 0; q < 4; q++) sts64f(o3 + (8 * (q >> 1) + 136 * (q & 1)) * 4, a3[2 * q], a3[2 * q + 1]);
  }
  bar_sync(barid, 128);
  const uint32_t go = (136 * tq + 16 * w + g) * 4;
  float ex[12];
#pragma unroll
  for (int i = 0; i < 12; i++) {
    const int o = 544 * (i >> 2) + 64 * (i & 1) + 8 * ((i >> 1) & 1);
    ex[i] = lds32f(y2b + go + o * 4);
    if (i >= 4) ex[i] += lds32f(y3b + go + (o - 544) * 4);
  }
  wg_wait<0>();
  fence_regs<16>(res);
#pragma unroll
  for (int i = 0; i < 12; i++) res[4 + i] += ex[i];
}

__device__ __forceinline__ void red16x2(float& a, float& c) {
#pragma unroll
  for (int o = 1; o < 16; o <<= 1) { a += __shfl_xor_sync(0xffffffffu, a, o); c += __shfl_xor_sync(0xffffffffu, c, o); }
}
__device__ __forceinline__ void ln_rows(uint32_t* u, uint32_t term, uint32_t stg_row, int lane) {
  const int j = lane & 15;
  const float piv = __shfl_sync(0xffffffffu, bf_lo(u[0]), lane & 16);
  float s0 = 0.f, s1 = 0.f, q0 = 0.f, q1 = 0.f;
#pragma unroll
  for (int i = 0; i < 14; i++) {
    const float a = bf_lo(u[i]) - piv, c = bf_hi(u[i]) - piv;
    s0 += a; s1 += c; q0 = fmaf(a, a, q0); q1 = fmaf(c, c, q1);
  }
  float s = s0 + s1, q = q0 + q1;
  red16x2(s, q);
  s *= (1.f / D_); q *= (1.f / D_);
  const __nv_bfloat16 m1b = __float2bfloat16_rn(s + piv);
  const __nv_bfloat162 m1v = __halves2bfloat162(m1b, m1b);
  const float den = rbf(sqrtf_(rbf(rbf(fmaxf(fmaf(-s, s, q), 0.f)) + 1e-5f)));
  const float rden = rcpf_(den);
  s0 = s1 = q0 = q1 = 0.f;
#pragma unroll
  for (int i = 0; i < 14; i++) {
    const __nv_bfloat162 cv = __hsub2(*reinterpret_cast<__nv_bfloat162*>(&u[i]), m1v);
    const uint32_t c = *reinterpret_cast<const uint32_t*>(&cv);
    const uint32_t n = pack_bf2(bf_lo(c) * rden, bf_hi(c) * rden);
    const float a = bf_lo(n), e = bf_hi(n);
    s0 += a; s1 += e; q0 = fmaf(a, a, q0); q1 = fmaf(e, e, q1);
    u[i] = pack_h2(a, e);
  }
#pragma unroll
  for (int i = 0; i < 7; i++)
    asm volatile("st.shared.v2.b32 [%0], {%1,%2};" ::"r"(stg_row + (j + 16 * i) * 8), "r"(u[2 * i]), "r"(u[2 * i + 1]) : "memory");
  s = s0 + s1; q = q0 + q1;
  red16x2(s, q);
  s *= (1.f / D_); q *= (1.f / D_);
  const float den2 = rbf(sqrtf_(rbf(rbf(fmaxf(fmaf(-s, s, q), 0.f)) + 1e-5f)));
  if (j == 0) {
    const float ir = den * den2, mu = fmaf(rbf(s), den, __bfloat162float(m1b));
    const float ih = rbf(ir), mh = rbf(mu);
    const uint32_t mm = pack_bf2(mh, mh);
    sts128(term, pack_bf2(mu - mh, ih), mm, pack_bf2(mu - mh, ir - ih), mm);
  }
}

__device__ __forceinline__ void poll_tag(const unsigned* p, uint32_t tag) {
#pragma unroll 1
  for (int it = 0; it < 4096; it++) {
    if (!((ld_relaxed1(p) ^ tag) & 1)) break;
    __nanosleep(32);
  }
}
__device__ __forceinline__ bool last_release(uint32_t cnt) {
  unsigned old;
  asm volatile("atom.relaxed.cta.shared.inc.u32 %0, [%1], 7;" : "=r"(old) : "r"(cnt) : "memory");
  return old == 7;
}
__device__ __forceinline__ int mod7(int v) { return v >= 7 ? v - 7 : v; }

#define IDS const int tid = opaque(tid0), lane = tid & 31, t = tid & 127; (void)lane; (void)t;

__global__ void __launch_bounds__(384, 1)
fused_kernel(const Params p, const __grid_constant__ CUtensorMap tm_x, const __grid_constant__ CUtensorMap tm_w1,
             const __grid_constant__ CUtensorMap tm_w2, const __grid_constant__ CUtensorMap tm_out) {
  const uint32_t sb = smem_u32(smem_raw);
  const uint32_t ms = sb + OFF_M;
  const uint32_t bar0 = ms + M_BAR;
  const int tid0 = threadIdx.x;
  const int wi = __shfl_sync(0xffffffffu, tid0 >> 5, 0), wg = wi >> 2, w = wi & 3;
  const int b = blockIdx.x;
  const bool is_ssm = b >= NMLP;
  const int G = b / NRK, rk = b - G * NRK;
  const int kc0 = (G + rk) % 7;
  TSINIT();
  TSTAMP(0);
  {
    IDS
    TSTAMP(28);
    uint4 ld[7];
    KgIn kin;
    unsigned ep = 0;
    uint32_t b1w;
    const int rl = 2 * wi + (lane >> 4);
    {
      const int d = is_ssm ? 2 * (112 + 3 * (b - NMLP) + wg) + (w >> 1) : (wg < 2 ? 2 * b + wg : 336 + b);
      const int off = d * NST + 64 * (is_ssm ? 2 * (w & 1) : w) + 2 * lane;
      const __nv_bfloat16* P[8] = {p.a_re + off, p.a_im + off, p.b_re + off, p.b_im + off, p.c_re + off, p.c_im + off,
                                   p.log_dt + (d & ~1), p.dskip + (d & ~1)};
      asm volatile("" : "+l"(P[0]), "+l"(P[1]), "+l"(P[2]), "+l"(P[3]), "+l"(P[4]), "+l"(P[5]), "+l"(P[6]), "+l"(P[7]));
#pragma unroll
      for (int i = 0; i < 6; i++) kin.cur[i] = ldg32(P[i], 0);
      kin.ldt = ldg32(P[6], 0); kin.dk = ldg32(P[7], 0);
#pragma unroll
      for (int i = 0; i < 6; i++) kin.nxt[i] = 0u;
      if (is_ssm) {
#pragma unroll
        for (int i = 0; i < 6; i++) kin.nxt[i] = ldg32(P[i], 128);
      }
      asm volatile("" :: "l"(P[0]), "l"(P[1]), "l"(P[2]), "l"(P[3]), "l"(P[4]), "l"(P[5]), "l"(P[6]), "l"(P[7]));
      kin.odd = d & 1;
    }
    const uint32_t tbl = is_ssm ? sb + (4 * wg + (w >> 1)) * TBL : sb + OFF_T + wg * TBL;
#pragma unroll 1
    for (int i = is_ssm ? t & 63 : t; i < TBL_SC / 16; i += is_ssm ? 64 : 128) sts128(tbl + i * 16, 0u, 0u, 0u, 0u);
    const uint32_t lns = is_ssm ? sb + S_WORK + 2 * S_WGB + KSTG : sb + OFF_X + 2 * 16384;
    if (wi < 4 && lane == 0) {
      if (wi < 3) mbar_init(bar0 + 8 * wi, 1);
      asm volatile("fence.mbarrier_init.release.cluster;" ::: "memory");
      if (!is_ssm) asm volatile("prefetch.tensormap [%0];" ::"l"(wi == 0 ? &tm_x : wi == 1 ? &tm_w1 : wi == 2 ? &tm_w2 : &tm_out) : "memory");
    }
    if ((wi == 5 || (wi == 6 && !is_ssm)) && lane == 0)
      asm volatile("cp.async.bulk.prefetch.L2.global [%0], %1;" ::"l"(wi == 5 ? p.x + (size_t)(b & 127) * 16 * D_ : p.w1 + (size_t)b * 4 * F_), "r"(14336) : "memory");
    __syncwarp();
    if (wi == 4 && lane < 16) asm volatile("st.shared.b32 [%0], 0;" ::"r"(ms + M_REL + 4 * lane) : "memory");
    TSTAMP(31);
    auto mid0 = [&]() {
      TSTAMP(27);
      if (wg < 2) {
        const __nv_bfloat16* xr = p.x + (size_t)(16 * (b & 127) + rl) * D_ + 4 * (lane & 15);
#pragma unroll
        for (int i = 0; i < 7; i++) asm volatile("ld.global.nc.v2.b32 {%0,%1}, [%2];" : "=r"(ld[i].x), "=r"(ld[i].y) : "l"(xr + 64 * i));
      } else {
        const __nv_bfloat16* wr = p.w1 + (size_t)(112 * (b & 3) + 4 * w + (lane & 3)) * F_ + 64 * (is_ssm ? 0 : b >> 2) + 8 * (lane >> 2);
#pragma unroll
        for (int i = 0; i < 7; i++)
          asm volatile("ld.global.nc.v4.b32 {%0,%1,%2,%3}, [%4];" : "=r"(ld[i].x), "=r"(ld[i].y), "=r"(ld[i].z), "=r"(ld[i].w) : "l"(wr + (size_t)i * 16 * F_));
        b1w = ldg32(p.b1 + 64 * (is_ssm ? 0 : b >> 2) + (t & 62), 0);
        if (t == 32) ep = ld_relaxed1(&p.s->epoch);
      }
    };
    auto mid = [&]() {
    TSTAMP(30);
    if (wi < 2 && lane == 0 && !is_ssm) {
      mbar_expect(bar0 + 8 * wi, 49152);
      tma_2d(sb + OFF_X + wi * 16384, &tm_x, 64 * wi, 128 * G, bar0 + 8 * wi);
      tma_3d(sb + OFF_W + wi * 32768, &tm_w1, 0, 64 * wi, 4 * rk, bar0 + 8 * wi);
    }
    __syncwarp();
    if (wg < 2) {
      uint32_t u[14];
#pragma unroll
      for (int i = 0; i < 7; i++) { u[2 * i] = ld[i].x; u[2 * i + 1] = ld[i].y; }
      ln_rows(u, ms + M_LT + rl * 16, lns + ((rl & 1) | ((rl >> 2) << 1) | ((rl & 2) << 2)) * 912, lane);
      bar_arrive(7, 384);
    } else {
      float cs[4] = {0.f, 0.f, 0.f, 0.f};
      const int g = lane >> 2;
      const uint32_t one = (g & 1) ? 0x3f800000u : 0x00003f80u;
      const uint32_t s0 = (g >> 1) == 0 ? one : 0u, s1 = (g >> 1) == 1 ? one : 0u, s2 = (g >> 1) == 2 ? one : 0u, s3 = (g >> 1) == 3 ? one : 0u;
#pragma unroll
      for (int i = 0; i < 7; i++) {
        mma_bf16(cs, s0, 0u, s1, 0u, ld[i].x, ld[i].y);
        mma_bf16(cs, s2, 0u, s3, 0u, ld[i].z, ld[i].w);
      }
      sts32f(ms + M_CSR + (w * 64 + (lane & 3) * 16 + g) * 4, cs[0]);
      sts32f(ms + M_CSR + (w * 64 + (lane & 3) * 16 + g + 8) * 4, cs[1]);
      if (t == 32) { asm volatile("st.shared.b32 [%0], %1;" ::"r"(ms + M_EP), "r"(ep + 1) : "memory"); red_relaxed(&p.s->cntA); }
      bar_sync(7, 384);
      const uint32_t la = lns + (lane & 15) * 912 + (lane >> 4) * 16 + w * 224;
      uint2* dst = (uint2*)(p.s->xnT + (size_t)(56 * w + (lane >> 3)) * 512 + 4 * b) + (lane & 7);
      uint32_t r[28];
#pragma unroll
      for (int k = 0; k < 7; k++) ldsm4t(la + k * 32, r[4 * k], r[4 * k + 1], r[4 * k + 2], r[4 * k + 3]);
      const uint32_t tag = lds32(ms + M_EP) & 1;
      if (b < 128) {
#pragma unroll
        for (int k = 0; k < 14; k++) st_relaxed2(dst + k * 4096, (r[2 * k] & ~1u) | tag, (r[2 * k + 1] & ~1u) | tag);
      }
      if (t < 64 && !is_ssm) {
        const uint32_t a = ms + M_CSR + t * 4;
        const float c = -((lds32f(a) + lds32f(a + 256)) + (lds32f(a + 512) + lds32f(a + 768)));
        const float ch = rbf(c);
        uint2* dx = (uint2*)(p.s->bx + (b >> 4) * 512 + ((b >> 1) & 1) * 256 + ((b >> 2) & 3) * 64 + t) + (b & 1);
        const float b1v = (b & 2) ? 0.f : ((t & 1) ? bf_hi(b1w) : bf_lo(b1w));
        asm volatile("{.reg .b64 a; mov.b64 a, {%1,%2}; st.relaxed.gpu.global.b64 [%0], a;}"
                     ::"l"(dx), "r"(pack_bf2(ch, b1v)), "r"((pack_bf2(c - ch, ch) & ~1u) | tag) : "memory");
      }
      if (t >= 64 && t < 80 && b < 128) {
        const uint4 a = lds128(ms + M_LT + (t - 64) * 16);
        st_b128(p.s->ax + 16 * b + t - 64, tag, a.x, a.y, a.z, a.w);
      }
    }
    TSTAMP(29);
    };
    kgen_wg(kin, is_ssm ? 2 : 1, stg, tbl, ms + M_MX + wg * 16, w, lane, 4 + wg, mid0, mid);
  }
  TSTAMP(1);

  if (is_ssm || wg == 2) {
    asm volatile("setmaxnreg.dec.sync.aligned.u32 136;");
    uint4 v[4], tv[5];
    {
      IDS
      bar_sync(2, 384);
#pragma unroll 1
      for (int c = is_ssm ? 1 : 2; c >= 0; c--) {
        ktab_build(is_ssm ? stg + c * 3072 : (c < 2 ? sb + OFF_A + c * KSTG : stg), !is_ssm, w, (is_ssm ? sb + S_TBL + 4 * wg * TBL : sb + OFF_T) + c * TBL, lane);
        if (c == 2) {
          fence_async();
          bar_sync(6, 128);
          if (t == 0) {
            mbar_expect(bar0 + 16, 49152);
            tma_2d(sb + OFF_X + 2 * 16384, &tm_x, 128, 128 * G, bar0 + 16);
            tma_3d(sb + OFF_W + 2 * 32768, &tm_w1, 0, 128, 4 * rk, bar0 + 16);
          }
          if (t == 96) { bulk_s2g(p.s->tbl + b * (TBL / 16), sb + OFF_T + 2 * TBL, TBL); bulk_commit(); }
          __syncwarp();
        }
      }
      if (!is_ssm) {
#pragma unroll
        for (int q = 0; q < 4; q++) tv[q] = ld_2x64(p.s->bx + 512 * rk + q * 128 + t);
        tv[4] = ld_b128(p.s->ax + 128 * G + t);
      }
      const uint4* src = p.s->xnT + (size_t)(is_ssm ? 112 + 3 * (b - NMLP) + wg : b) * 512 + t;
#pragma unroll
      for (int q = 0; q < 4; q++) v[q] = ld_relaxed4(src + q * 128);
      bar_sync(4 + wg, 128);
    }
    TSTAMP(2);
    if (!is_ssm) {
      IDS
      const unsigned ep1 = lds32(ms + M_EP);
#pragma unroll 1
      for (int it = 0; it < 16 * RETRY_MAX; it++) {
        uint32_t bad = tv[4].x ^ ep1;
#pragma unroll
        for (int q = 0; q < 4; q++) bad |= (tv[q].y ^ ep1) | (tv[q].w ^ ep1);
        if (!__any_sync(0xffffffffu, bad & 1)) break;
        __nanosleep(200);
#pragma unroll
        for (int q = 0; q < 4; q++) tv[q] = ld_2x64(p.s->bx + 512 * rk + q * 128 + t);
        tv[4] = ld_b128(p.s->ax + 128 * G + t);
      }
#pragma unroll
      for (int q = 0; q < 5; q++) sts128(sb + OFF_B + (q < 4 ? B_BX + q * 2048 : B_AX) + t * 16, tv[q].x, tv[q].y, tv[q].z, tv[q].w);
      if (t < 64) sts32f(ms + M_CSR + t * 4, 0.5f * __bfloat162float(p.b2[64 * rk + t]));
      fence_async();
      bar_arrive(1, 384);
      if (t == 64)
        asm volatile("cp.async.bulk.prefetch.L2.global [%0], %1;" ::"l"(p.w2 + (size_t)(256 * rk + 16 * G) * D_), "r"(16 * D_ * 2) : "memory");
    }
#pragma unroll 1
    for (int pi = 0; ; pi++) {
      {
        IDS
        const unsigned ep1 = lds32(ms + M_EP);
        const int pair = !is_ssm ? b : (pi == 0 ? 112 + 3 * (b - NMLP) : (b < NMLP + 12 ? 172 + 3 * (b - NMLP) : 184 + 2 * (b - NMLP))) + wg;
        const uint32_t work = is_ssm ? sb + S_WORK + wg * S_WGB : sb + OFF_A;
        const uint32_t z = work + SIG_V3 - 1024 + (t >> 6) * 4096 + (t & 63) * 16;
        sts128(z, 0u, 0u, 0u, 0u); sts128(z + SIG, 0u, 0u, 0u, 0u);
        if (t < 72) {
          const uint32_t zu = work + SIG_U + (t & 7) * U_LBO + (t >> 3) * 16;
          sts128(zu, 0u, 0u, 0u, 0u); sts128(zu + SIG, 0u, 0u, 0u, 0u);
        }
        const uint4* src = p.s->xnT + (size_t)pair * 512 + t;
#pragma unroll 1
        for (int it = 0; it < RETRY_MAX; it++) {
          uint32_t bad = 0;
#pragma unroll
          for (int q = 0; q < 4; q++) bad |= (((v[q].x ^ ep1) | (v[q].y ^ ep1) | (v[q].z ^ ep1) | (v[q].w ^ ep1)) & 1) << q;
          const unsigned m = __ballot_sync(0xffffffffu, bad);
          if (!m) break;
          if (lane == __ffs(m) - 1) poll_tag((const unsigned*)(src + (__ffs(bad) - 1) * 128) + 3, ep1);
          __syncwarp();
#pragma unroll
          for (int q = 0; q < 4; q++) v[q] = ld_relaxed4(src + q * 128);
        }
        TSTAMP(5);
        const uint32_t a = work + ((t >> 1) & 1) * SIG + SIG_U + (2 * ((t >> 2) & 3) + (t & 1)) * U_LBO + ((t >> 4) + 9) * 16;
#pragma unroll
        for (int q = 0; q < 4; q++) sts128(a + q * 128, v[q].x & ~1u, v[q].y & ~1u, v[q].z & ~1u, v[q].w & ~1u);
        bar_sync(4 + wg, 128);
#pragma unroll 1
        for (int k = w; k < 6; k += 4) sig_windows(work + (k & 1) * SIG, (k >> 1) * 32 + lane);
        fence_async();
        if (t == 96 && !is_ssm) { bulk_wait0(); red_release(&p.s->cntT); }
        if (pi == 1) mbar_wait(bar0 + 8 * wg, 0);
        TSTAMP(6);
        bar_sync(is_ssm ? 4 + wg : 3, is_ssm ? 128 : 384);
        TSTAMP(7);
      }
      uint32_t keep[8];
      float res[16];
#pragma unroll 1
      for (int c = 0; c < 2; c++) {
        IDS
        const uint32_t work = is_ssm ? sb + S_WORK + wg * S_WGB : sb + OFF_A;
        const uint32_t tbl = (is_ssm ? sb + (4 * wg + 2 * pi) * TBL : sb + OFF_T) + c * TBL;
        conv_channel(tbl, work + c * SIG, is_ssm ? work + 2 * SIG + Y3B : sb + OFF_B, work + 2 * SIG, lds32f(tbl + TBL_SC), w, lane, 4 + wg, res);
        TSTAMP(16 + 2 * pi + c);
        const float os = lds32f(tbl + TBL_SC + 8);
        if (c == 0) {
#pragma unroll
          for (int i = 0; i < 8; i++) keep[i] = pack_bf2(res[2 * i] * os, res[2 * i + 1] * os);
          if (is_ssm && pi == 0 && t == 96 && (b < NMLP + 12 || wg < 2)) {
            wait_count(&p.s->cntT, lds32(ms + M_EP) * NMLP);
            asm volatile("fence.proxy.async;" ::: "memory");
            mbar_expect(bar0 + 8 * wg, 2 * TBL);
            bulk_g2s(sb + (4 * wg + 2) * TBL, p.s->tbl + (2 * ((b < NMLP + 12 ? 172 + 3 * (b - NMLP) : 184 + 2 * (b - NMLP)) + wg) - 336) * (TBL / 16),
                     2 * TBL, bar0 + 8 * wg);
          }
          __syncwarp();
        } else {
          const int pair = !is_ssm ? b : (pi == 0 ? 112 + 3 * (b - NMLP) : (b < NMLP + 12 ? 172 + 3 * (b - NMLP) : 184 + 2 * (b - NMLP))) + wg;
          uint4* dst = p.s->s2 + ((size_t)(lane & 3) * 224 + pair) * 32 + w * 8 + (lane >> 2);
          const uint32_t tag = (lds32(ms + M_EP) & 1) * 0x10001u;
#pragma unroll
          for (int nt = 0; nt < 4; nt++) {
            const uint32_t n0 = pack_bf2(res[4 * nt] * os, res[4 * nt + 1] * os), n1 = pack_bf2(res[4 * nt + 2] * os, res[4 * nt + 3] * os);
            const uint32_t k0 = (keep[2 * nt] & 0xfffefffeu) | tag;
            asm volatile("{.reg .b64 a, c; mov.b64 a, {%1,%2}; mov.b64 c, {%3,%4}; st.relaxed.gpu.global.v2.b64 [%0], {a, c};}"
                         ::"l"(dst + nt * 4 * 224 * 32), "r"(__byte_perm(k0, n0, 0x5410)), "r"(__byte_perm(keep[2 * nt + 1], n1, 0x5410)),
                         "r"(__byte_perm(k0, n0, 0x7632)), "r"(__byte_perm(keep[2 * nt + 1], n1, 0x7632)) : "memory");
          }
        }
      }
      TSTAMP(8 + pi);
      TSDUMP();
      {
        IDS
        if (pi == 1 || !is_ssm || (b >= NMLP + 12 && wg == 2)) break;
        const uint4* src = p.s->xnT + (size_t)((b < NMLP + 12 ? 172 + 3 * (b - NMLP) : 184 + 2 * (b - NMLP)) + wg) * 512 + t;
#pragma unroll
        for (int q = 0; q < 4; q++) v[q] = ld_relaxed4(src + q * 128);
      }
    }
    if (b == 0 && tid0 == 256) {
      const unsigned ep1 = lds32(ms + M_EP);
      wait_count(&p.s->cntA, ep1 * NCTA);
      *(volatile unsigned*)&p.s->epoch = ep1;
    }
  } else {
    bar_arrive(1, 384);
    asm volatile("setmaxnreg.inc.sync.aligned.u32 192;");
    bar_sync(7, 384);
    uint32_t H[64];
    {
      float acc[128];
      float p0, q0, p1, q1;
      {
        IDS
        int sl = 0;
#pragma unroll 1
        for (int s = 0; s < 7; s++) {
          mbar_wait(bar0 + 8 * sl, (s >= 3 && s < 6));
          TSTAMP(17 + s);
          const uint64_t da = mkdesc(sb + OFF_X + sl * 16384 + wg * 8192, 16, 1024, 1);
          const uint64_t db = mkdesc(sb + OFF_W + sl * 32768, 8192, 1024, 1);
          wg_fence();
#pragma unroll
          for (int k = 0; k < 4; k++) wg_ss_bf16_n256(acc, da + 2 * k, db + 128 * k, (s | k) != 0);
          wg_commit();
          wg_wait<1>();
          const int pl = sl == 0 ? 2 : sl - 1;
          sl = sl == 2 ? 0 : sl + 1;
          if (s > 0 && lane == 0 && last_release(ms + M_REL + 4 * s)) {
            mbar_expect(bar0 + 8 * pl, s == 5 ? 32768 : 49152);
            if (s < 5) tma_3d(sb + OFF_W + pl * 32768, &tm_w1, 0, 64 * (s + 2), 4 * rk, bar0 + 8 * pl);
            else tma_2d(sb + OFF_W + pl * 32768, &tm_w2, 64 * mod7(rk + s - 4), 256 * rk, bar0 + 8 * pl);
            if (s != 5) tma_2d(sb + OFF_X + pl * 16384, &tm_x, 64 * (s < 5 ? (s + 2) : rk), 128 * G, bar0 + 8 * pl);
          }
        }
        TSTAMP(15);
        asm volatile("setmaxnreg.inc.sync.aligned.u32 184;");
        bar_sync(1, 384);
        wg_fence();
        wg_ss_bf16_n256k(acc, mkdesc(sb + OFF_B + B_AX + wg * 1024, 0, 128, 0), mkdesc(sb + OFF_B + B_BX, 4096, 128, 0), 1);
        wg_commit();
        wg_wait<1>();
        if (lane == 0 && last_release(ms + M_REL + 4 * 7)) {
          mbar_expect(bar0, 65536);
#pragma unroll 1
          for (int c = 2; c < 4; c++) tma_2d(sb + (c - 2) * OFF_X, &tm_w2, 64 * mod7(rk + 1 + c), 256 * rk, bar0);
        }
        bar_arrive(3, 384);
        const uint32_t ra = sb + OFF_B + B_AX + (16 * wi + (lane >> 2)) * 16;
        const float r0 = rcpf_(bf_hi(lds32(ra)) + bf_hi(lds32(ra + 8))), r1 = rcpf_(bf_hi(lds32(ra + 128)) + bf_hi(lds32(ra + 136)));
        p0 = 0.7978845608028654f * r0; q0 = 0.0356774081363001f * r0 * r0 * r0;
        p1 = 0.7978845608028654f * r1; q1 = 0.0356774081363001f * r1 * r1 * r1;
      }
      wg_wait<0>();
      fence_regs<128>(acc);
      TSTAMP(16);
#pragma unroll 1
      for (int hf = 0; hf < 2; hf++) {
        float th[8];
#pragma unroll
        for (int i = 0; i < 35; i++) {
          if (i < 32) {
            const float pp = (i & 1) ? p1 : p0, qq = (i & 1) ? q1 : q0;
            const float a = acc[2 * i], c = acc[2 * i + 1];
            th[2 * (i & 3)] = tanhf_(a * fmaf(a * a, qq, pp)); th[2 * (i & 3) + 1] = tanhf_(c * fmaf(c * c, qq, pp));
          }
          if (i >= 3) {
            const int j = i - 3;
            asm volatile("{.reg .f32 x, y; fma.rn.f32 x, %0, %5, %0; fma.rn.f32 y, %1, %6, %1; mov.f32 %0, %3; mov.f32 %1, %4;\n"
                         ".reg .b32 h; cvt.rn.bf16x2.f32 h, y, x; mov.b32 %2, h;}"
                         : "+f"(acc[2 * j]), "+f"(acc[2 * j + 1]), "=f"(acc[64 + j])
                         : "f"(acc[64 + 2 * j]), "f"(acc[65 + 2 * j]), "f"(th[2 * (j & 3)]), "f"(th[2 * (j & 3) + 1]));
          }
        }
      }
#pragma unroll
      for (int i = 0; i < 32; i++) { H[i] = __float_as_uint(acc[i]); H[32 + i] = __float_as_uint(acc[64 + i]); }
    }
    TSTAMP(3);
    IDS
    float acc[32], pre[32];
    uint32_t pk[16];
#pragma unroll
    for (int i = 0; i < 32; i++) pre[i] = 0.f;
    const uint32_t tag = lds32(ms + M_EP) & 1;
    const uint4* inbox = p.s->part + (size_t)b * 6 * 1024 + tid;
    uint4 rv[4];
    auto fetch = [&](int slot) {
#pragma unroll
      for (int q = 0; q < 4; q++) rv[q] = ld_b128(inbox + slot * 1024 + q * 256);
    };
    auto recv = [&](int slot) {
#pragma unroll 1
      for (int it = 0; it < RETRY_MAX; it++) {
        const unsigned m = __ballot_sync(0xffffffffu, ((rv[0].x ^ tag) | (rv[1].x ^ tag) | (rv[2].x ^ tag) | (rv[3].x ^ tag)) & 1);
        if (!m) break;
        if (lane == __ffs(m) - 1) poll_tag((const unsigned*)(inbox + slot * 1024 + 768), tag);
        __syncwarp();
        fetch(slot);
      }
#pragma unroll
      for (int q = 0; q < 4; q++) {
        const uint32_t u[4] = {rv[q].x, rv[q].y, rv[q].z, rv[q].w};
#pragma unroll
        for (int k = 0; k < 4; k++) { pre[8 * q + 2 * k] += bf_lo(u[k]); pre[8 * q + 2 * k + 1] += bf_hi(u[k]); }
      }
    };
#pragma unroll 1
    for (int s = 0; s < 7; s++) {
      if (s != 3) mbar_wait(bar0 + 8 * ((0x0210021u >> (4 * s)) & 3), (0x34 >> s) & 1);
      const uint64_t db = mkdesc(sb + ((0x0213021u >> (4 * s)) & 3) * 32768, 8192, 1024, 1);
      wg_fence();
#pragma unroll
      for (int k = 0; k < 16; k++) wg_rs_bf16_n64(acc, H[4 * k], H[4 * k + 1], H[4 * k + 2], H[4 * k + 3], db + 128 * k, k != 0);
      wg_commit();
      if (s > 0) {
        uint4* dst = p.s->part + ((size_t)(G * 7 + mod7(rk + s)) * 6 + s - 1) * 1024 + tid;
#pragma unroll
        for (int q = 0; q < 4; q++) st_b128(dst + q * 256, tag, pk[4 * q], pk[4 * q + 1], pk[4 * q + 2], pk[4 * q + 3]);
        if (s < 4 && lane == 0 && last_release(ms + M_REL + 4 * (7 + s))) {
          const int sl = (0x0210u >> (4 * s)) & 3;
          mbar_expect(bar0 + 8 * sl, 32768);
          tma_2d(sb + sl * 32768, &tm_w2, 64 * mod7(mod7(rk + 4 + s)), 256 * rk, bar0 + 8 * sl);
        }
        __syncwarp();
      }
      if (s >= 4) recv(s - 4);
      if (s >= 3) fetch(s - 3);
      wg_wait<0>();
      fence_regs<32>(acc);
#pragma unroll
      for (int k = 0; k < 16; k++) pk[k] = pack_bf2(acc[2 * k], acc[2 * k + 1]);
      TSTAMP(4 + s);
    }
    {
      const uint2* sp = (const uint2*)(p.s->s2 + ((size_t)G * 224 + 32 * rk + (lane & 3)) * 32 + w * 8 + (lane >> 2)) + wg;
#pragma unroll 1
      for (int it = 0; it < RETRY_MAX; it++) {
#pragma unroll
        for (int i = 0; i < 8; i++)
          asm volatile("{.reg .b64 a; ld.relaxed.gpu.global.b64 a, [%2]; mov.b64 {%0,%1}, a;}"
                       : "=r"(pk[2 * i]), "=r"(pk[2 * i + 1]) : "l"(sp + i * 4 * 64) : "memory");
#pragma unroll 1
        for (int s = it ? 6 : 3; s < 6; s++) { recv(s); if (s < 5) fetch(s + 1); }
        uint32_t bad = 0;
#pragma unroll
        for (int i = 0; i < 8; i++) bad |= ((pk[2 * i] ^ tag) & 1) << i;
        const unsigned m = __ballot_sync(0xffffffffu, bad);
        if (!m) break;
        if (lane == __ffs(m) - 1) poll_tag((const unsigned*)(sp + (__ffs(bad) - 1) * 4 * 64), tag);
        __syncwarp();
      }
    }
    TSTAMP(12);
    const int g = lane >> 2, tq = lane & 3;
    const uint32_t xa = sb + OFF_X + 2 * 16384 + (16 * wi + (lane & 15)) * 128;
    uint32_t xw[16];
#pragma unroll
    for (int q = 0; q < 4; q++) ldsm4(xa + (((2 * q + (lane >> 4)) ^ (lane & 7)) << 4), xw[4 * q], xw[4 * q + 1], xw[4 * q + 2], xw[4 * q + 3]);
    const uint32_t ra = sb + OFF_B + B_AX + (16 * wi + g) * 16;
    const float r0 = 0.25f * rcpf_(bf_hi(lds32(ra)) + bf_hi(lds32(ra + 8))), r1 = 0.25f * rcpf_(bf_hi(lds32(ra + 128)) + bf_hi(lds32(ra + 136)));
#pragma unroll
    for (int i = 0; i < 8; i++) {
      const float2 bb = lds64f(ms + M_CSR + (8 * i + 2 * tq) * 4);
#pragma unroll
      for (int e = 0; e < 2; e++) {
        const int k = 2 * i + e;
        const float h0 = fmaf(acc[2 * k] + pre[2 * k], e ? r1 : r0, bb.x), h1 = fmaf(acc[2 * k + 1] + pre[2 * k + 1], e ? r1 : r0, bb.y);
        const uint32_t gw = pack_bf2(fmaf(h0, tanhf_(h0), h0), fmaf(h1, tanhf_(h1), h1));
        asm("fma.rn.bf16x2 %0, %1, %2, %0;" : "+r"(xw[k]) : "r"(pk[k]), "r"(gw));
      }
    }
#pragma unroll
    for (int q = 0; q < 4; q++) stsm4(xa + (((2 * q + (lane >> 4)) ^ (lane & 7)) << 4), xw[4 * q], xw[4 * q + 1], xw[4 * q + 2], xw[4 * q + 3]);
    fence_async();
    __syncwarp();
    if (lane == 0) {
      tma_store_2d(&tm_out, sb + OFF_X + 2 * 16384 + wi * 2048, 64 * rk, 128 * G + 16 * wi);
      bulk_commit();
      bulk_wait0_read();
    }
    TSTAMP(13);
    TSDUMP();
  }
}

typedef CUresult (*EncodeFn)(CUtensorMap*, CUtensorMapDataType, cuuint32_t, void*, const cuuint64_t*, const cuuint64_t*,
                             const cuuint32_t*, const cuuint32_t*, CUtensorMapInterleave, CUtensorMapSwizzle,
                             CUtensorMapL2promotion, CUtensorMapFloatOOBfill);

void make_map(EncodeFn fn, CUtensorMap* m, const void* ptr, int rank, const cuuint64_t* dims, const cuuint64_t* strides, const cuuint32_t* box) {
  const cuuint32_t es[3] = {1, 1, 1};
  fn(m, CU_TENSOR_MAP_DATA_TYPE_BFLOAT16, rank, const_cast<void*>(ptr), dims, strides, box, es, CU_TENSOR_MAP_INTERLEAVE_NONE,
     CU_TENSOR_MAP_SWIZZLE_128B, CU_TENSOR_MAP_L2_PROMOTION_L2_128B, CU_TENSOR_MAP_FLOAT_OOB_FILL_NONE);
}

}

extern "C" void kernel_launch(void* const* d_in, const int* in_sizes, int n_in, void* d_out, int out_size) {
  (void)in_sizes; (void)n_in; (void)out_size;
  void* fnp = nullptr;
  cudaDriverEntryPointQueryResult qr;
  cudaGetDriverEntryPoint("cuTensorMapEncodeTiled", &fnp, cudaEnableDefault, &qr);
  EncodeFn fn = (EncodeFn)fnp;
  Params p;
  p.x = (const __nv_bfloat16*)d_in[0];
  p.a_re = (const __nv_bfloat16*)d_in[1]; p.a_im = (const __nv_bfloat16*)d_in[2];
  p.b_re = (const __nv_bfloat16*)d_in[3]; p.b_im = (const __nv_bfloat16*)d_in[4];
  p.c_re = (const __nv_bfloat16*)d_in[5]; p.c_im = (const __nv_bfloat16*)d_in[6];
  p.log_dt = (const __nv_bfloat16*)d_in[7]; p.dskip = (const __nv_bfloat16*)d_in[8];
  p.w1 = (const __nv_bfloat16*)d_in[10]; p.b1 = (const __nv_bfloat16*)d_in[11];
  p.w2 = (const __nv_bfloat16*)d_in[12]; p.b2 = (const __nv_bfloat16*)d_in[13];
  void* sp = nullptr;
  cudaGetSymbolAddress(&sp, g_scr);
  p.s = (Scratch*)sp;
  CUtensorMap mx, mw1, mw2, mo;
  {
    const cuuint64_t dims[2] = {448, 2048}, str[1] = {896};
    const cuuint32_t box[2] = {64, 128}, boxo[2] = {64, 16};
    make_map(fn, &mx, p.x, 2, dims, str, box);
    make_map(fn, &mo, d_out, 2, dims, str, boxo);
  }
  {
    const cuuint64_t dims[3] = {64, 448, 28}, str[2] = {3584, 128};
    const cuuint32_t box[3] = {64, 64, 4};
    make_map(fn, &mw1, p.w1, 3, dims, str, box);
  }
  {
    const cuuint64_t dims[2] = {448, 1792}, str[1] = {896};
    const cuuint32_t box[2] = {64, 256};
    make_map(fn, &mw2, p.w2, 2, dims, str, box);
  }
  cudaFuncSetAttribute(fused_kernel, cudaFuncAttributeMaxDynamicSharedMemorySize, SMEM_BYTES);
  fused_kernel<<<NCTA, 384, SMEM_BYTES>>>(p, mx, mw1, mw2, mo);
}
```

```cpp
#include <cuda_runtime.h>
#include <cuda_bf16.h>
#include <cuda_fp16.h>
#include <cuda.h>
#include <stdint.h>

namespace {

constexpr int D_ = 448, NST = 256, F_ = 1792;
constexpr int NRK = 7, NMLP = 112, NCTA = 132;
constexpr int SPIN_MAX = 1 << 20, RETRY_MAX = 512;

struct Scratch {
  unsigned cntA, pad0[31], cntT, pad1[31], epoch, pad2[63];
  uint4 ax[2048];
  uint4 bx[7 * 512];
  uint4 tbl[112 * 329];
  uint4 xnT[224 * 512];
  uint4 s2[16 * 224 * 32];
  uint4 part[16 * 7 * 6 * 1024];
};
__device__ Scratch g_scr;
#define TSTAMP(i)
#define TSINIT()
#define TSDUMP()
extern __shared__ __align__(1024) uint8_t smem_raw[];

constexpr int TBL_SC = 5248, TBL = 5264;
constexpr int TBL_C1 = 2624;
constexpr int SIG = 19584;
constexpr int SIG_U = 0, U_LBO = 656, SIG_V3 = 6272, SIG_V5 = 10368, SIG_V7 = 13440, SIG_V9 = 15488, SIG_V2 = 17536;
constexpr int Y2B = 6528, Y3B = 4352;
constexpr int KSTG = 14 * 2048;
constexpr int OFF_W = 0, OFF_X = 98304, OFF_A = 147456, OFF_B = OFF_A + 2 * SIG + Y3B, OFF_T = OFF_B + 16896;
constexpr int OFF_M = OFF_T + 15872;
constexpr int B_AX = Y2B, B_BX = B_AX + 2048;
constexpr int M_BAR = 0, M_REL = 128, M_EP = 192, M_CSR = 256, M_LT = 1280, M_MX = 1536, M_END = 1664;
constexpr int SMEM_BYTES = OFF_M + M_END + 384;
constexpr int S_WORK = 63232, S_WGB = 2 * SIG + Y2B + Y3B;
static_assert(OFF_A + 2 * KSTG <= OFF_T && S_WORK + 3 * S_WGB <= OFF_M && SMEM_BYTES <= 232448, "smem");

struct Params {
  const __nv_bfloat16 *x, *a_re, *a_im, *b_re, *b_im, *c_re, *c_im, *log_dt, *dskip, *w1, *b1, *w2, *b2;
  Scratch* s;
};

__device__ __forceinline__ int opaque(int x) { int v; asm volatile("mov.u32 %0, %1;" : "=r"(v) : "r"(x)); return v; }
__device__ __forceinline__ int rd_bid() { int v; asm volatile("mov.u32 %0, %%ctaid.x;" : "=r"(v)); return v; }
__device__ __forceinline__ uint32_t smem_u32(const void* p) { return (uint32_t)__cvta_generic_to_shared(p); }
__device__ __forceinline__ void mbar_init(uint32_t bar, int cnt) { asm volatile("mbarrier.init.shared::cta.b64 [%0], %1;" ::"r"(bar), "r"(cnt)); }
__device__ __forceinline__ void mbar_expect(uint32_t bar, uint32_t bytes) {
  asm volatile("mbarrier.arrive.expect_tx.shared::cta.b64 _, [%0], %1;" ::"r"(bar), "r"(bytes) : "memory");
}
__device__ __forceinline__ void mbar_wait(uint32_t bar, uint32_t parity) {
  uint32_t done = 0;
#pragma unroll 1
  for (int it = 0; it < SPIN_MAX; it++) {
    asm volatile("{.reg .pred p; mbarrier.try_wait.parity.shared::cta.b64 p, [%1], %2; selp.u32 %0,1,0,p;}"
                 : "=r"(done) : "r"(bar), "r"(parity) : "memory");
    if (done) break;
  }
}
__device__ __forceinline__ void tma_2d(uint32_t dst, const CUtensorMap* m, int c0, int c1, uint32_t bar) {
  asm volatile("cp.async.bulk.tensor.2d.shared::cluster.global.mbarrier::complete_tx::bytes [%0], [%1, {%3, %4}], [%2];"
               ::"r"(dst), "l"(m), "r"(bar), "r"(c0), "r"(c1) : "memory");
}
__device__ __forceinline__ void tma_3d(uint32_t dst, const CUtensorMap* m, int c0, int c1, int c2, uint32_t bar) {
  asm volatile("cp.async.bulk.tensor.3d.shared::cluster.global.mbarrier::complete_tx::bytes [%0], [%1, {%3, %4, %5}], [%2];"
               ::"r"(dst), "l"(m), "r"(bar), "r"(c0), "r"(c1), "r"(c2) : "memory");
}
__device__ __forceinline__ void tma_store_2d(const CUtensorMap* m, uint32_t src, int c0, int c1) {
  asm volatile("cp.async.bulk.tensor.2d.global.shared::cta.bulk_group [%0, {%2, %3}], [%1];"
               ::"l"(m), "r"(src), "r"(c0), "r"(c1) : "memory");
}
__device__ __forceinline__ void bulk_commit() { asm volatile("cp.async.bulk.commit_group;" ::: "memory"); }
__device__ __forceinline__ void bulk_wait0_read() { asm volatile("cp.async.bulk.wait_group.read 0;" ::: "memory"); }
__device__ __forceinline__ void fence_async() { asm volatile("fence.proxy.async.shared::cta;" ::: "memory"); }
__device__ __forceinline__ void bar_sync(int id, int n) { asm volatile("bar.sync %0, %1;" ::"r"(id), "r"(n) : "memory"); }
__device__ __forceinline__ void bar_arrive(int id, int n) { asm volatile("bar.arrive %0, %1;" ::"r"(id), "r"(n) : "memory"); }
__device__ __forceinline__ void wg_fence() { asm volatile("wgmma.fence.sync.aligned;" ::: "memory"); }
__device__ __forceinline__ void wg_commit() { asm volatile("wgmma.commit_group.sync.aligned;" ::: "memory"); }
template <int N> __device__ __forceinline__ void wg_wait() { asm volatile("wgmma.wait_group.sync.aligned %0;" ::"n"(N) : "memory"); }
template <int N> __device__ __forceinline__ void fence_regs(float* d) {
#pragma unroll
  for (int i = 0; i < N; i++) asm volatile("" : "+f"(d[i])::"memory");
}
__device__ __forceinline__ uint64_t mkdesc(uint32_t addr, uint32_t lbo, uint32_t sbo, uint32_t sw) {
  return (uint64_t)((addr & 0x3FFFF) >> 4) | ((uint64_t)(lbo >> 4) << 16) | ((uint64_t)(sbo >> 4) << 32) | ((uint64_t)sw << 62);
}
__device__ __forceinline__ uint32_t lds32(uint32_t a) { uint32_t v; asm volatile("ld.shared.b32 %0, [%1];" : "=r"(v) : "r"(a) : "memory"); return v; }
__device__ __forceinline__ float lds32f(uint32_t a) { float v; asm volatile("ld.shared.f32 %0, [%1];" : "=f"(v) : "r"(a) : "memory"); return v; }
__device__ __forceinline__ float2 lds64f(uint32_t a) { float2 v; asm volatile("ld.shared.v2.f32 {%0,%1}, [%2];" : "=f"(v.x), "=f"(v.y) : "r"(a) : "memory"); return v; }
__device__ __forceinline__ uint4 lds128(uint32_t a) {
  uint4 v; asm volatile("ld.shared.v4.b32 {%0,%1,%2,%3}, [%4];" : "=r"(v.x), "=r"(v.y), "=r"(v.z), "=r"(v.w) : "r"(a) : "memory"); return v;
}
__device__ __forceinline__ void sts16(uint32_t a, uint16_t v) { asm volatile("st.shared.b16 [%0], %1;" ::"r"(a), "h"(v) : "memory"); }
__device__ __forceinline__ void sts32f(uint32_t a, float v) { asm volatile("st.shared.f32 [%0], %1;" ::"r"(a), "f"(v) : "memory"); }
__device__ __forceinline__ void sts64f(uint32_t a, float x, float y) { asm volatile("st.shared.v2.f32 [%0], {%1,%2};" ::"r"(a), "f"(x), "f"(y) : "memory"); }
__device__ __forceinline__ void sts128(uint32_t a, uint32_t x, uint32_t y, uint32_t z, uint32_t w) {
  asm volatile("st.shared.v4.b32 [%0], {%1,%2,%3,%4};" ::"r"(a), "r"(x), "r"(y), "r"(z), "r"(w) : "memory");
}
__device__ __forceinline__ void ldsm4(uint32_t a, uint32_t& r0, uint32_t& r1, uint32_t& r2, uint32_t& r3) {
  asm volatile("ldmatrix.sync.aligned.m8n8.x4.shared.b16 {%0,%1,%2,%3}, [%4];" : "=r"(r0), "=r"(r1), "=r"(r2), "=r"(r3) : "r"(a) : "memory");
}
__device__ __forceinline__ void ldsm4t(uint32_t a, uint32_t& r0, uint32_t& r1, uint32_t& r2, uint32_t& r3) {
  asm volatile("ldmatrix.sync.aligned.m8n8.x4.trans.shared.b16 {%0,%1,%2,%3}, [%4];" : "=r"(r0), "=r"(r1), "=r"(r2), "=r"(r3) : "r"(a) : "memory");
}
__device__ __forceinline__ void stsm4(uint32_t a, uint32_t r0, uint32_t r1, uint32_t r2, uint32_t r3) {
  asm volatile("stmatrix.sync.aligned.m8n8.x4.shared.b16 [%0], {%1,%2,%3,%4};" ::"r"(a), "r"(r0), "r"(r1), "r"(r2), "r"(r3) : "memory");
}
__device__ __forceinline__ void mma_bf16(float* c, uint32_t a0, uint32_t a1, uint32_t a2, uint32_t a3, uint32_t b0, uint32_t b1) {
  asm("mma.sync.aligned.m16n8k16.row.col.f32.bf16.bf16.f32 {%0,%1,%2,%3},{%4,%5,%6,%7},{%8,%9},{%0,%1,%2,%3};"
      : "+f"(c[0]), "+f"(c[1]), "+f"(c[2]), "+f"(c[3]) : "r"(a0), "r"(a1), "r"(a2), "r"(a3), "r"(b0), "r"(b1));
}
__device__ __forceinline__ uint4 ld_relaxed4(const void* p) {
  uint4 v; asm volatile("ld.relaxed.gpu.global.v4.b32 {%0,%1,%2,%3}, [%4];" : "=r"(v.x), "=r"(v.y), "=r"(v.z), "=r"(v.w) : "l"(p) : "memory"); return v;
}
__device__ __forceinline__ uint4 ld_2x64(const void* p) {
  uint4 v;
  asm volatile("{.reg .b64 a, c; ld.relaxed.gpu.global.v2.b64 {a, c}, [%4]; mov.b64 {%0,%1}, a; mov.b64 {%2,%3}, c;}"
               : "=r"(v.x), "=r"(v.y), "=r"(v.z), "=r"(v.w) : "l"(p) : "memory");
  return v;
}
__device__ __forceinline__ void st_relaxed2(void* p, uint32_t x, uint32_t y) {
  asm volatile("st.relaxed.gpu.global.v2.b32 [%0], {%1,%2};" ::"l"(p), "r"(x), "r"(y) : "memory");
}
__device__ __forceinline__ uint4 ld_b128(const void* p) {
  uint4 v;
  asm volatile("{.reg .b128 t; .reg .b64 a, c; ld.relaxed.gpu.global.b128 t, [%4]; mov.b128 {a, c}, t; mov.b64 {%0,%1}, a; mov.b64 {%2,%3}, c;}"
               : "=r"(v.x), "=r"(v.y), "=r"(v.z), "=r"(v.w) : "l"(p) : "memory");
  return v;
}
__device__ __forceinline__ void st_b128(void* p, uint32_t tag, uint32_t x, uint32_t y, uint32_t z, uint32_t w) {
  asm volatile("{.reg .b128 t; .reg .b64 a, c; mov.b64 a, {%1,%2}; mov.b64 c, {%3,%4}; mov.b128 t, {a, c}; st.relaxed.gpu.global.b128 [%0], t;}"
               ::"l"(p), "r"((x & ~1u) | tag), "r"(y), "r"(z), "r"(w) : "memory");
}
__device__ __forceinline__ unsigned ld_relaxed1(const unsigned* p) {
  unsigned v; asm volatile("ld.relaxed.gpu.global.u32 %0, [%1];" : "=r"(v) : "l"(p) : "memory"); return v;
}
__device__ __forceinline__ void red_relaxed(unsigned* p) {
  asm volatile("red.relaxed.gpu.global.add.u32 [%0], 1;" ::"l"(p) : "memory");
}
__device__ __forceinline__ void wait_count(const unsigned* p, unsigned target) {
#pragma unroll 1
  for (int it = 0; it < SPIN_MAX; it++) {
    if ((int)(ld_relaxed1(p) - target) >= 0) break;
    __nanosleep(40);
  }
  asm volatile("fence.acq_rel.gpu;" ::: "memory");
}
__device__ __forceinline__ uint32_t pack_h2(float lo, float hi) { uint32_t r; asm("cvt.rn.f16x2.f32 %0, %1, %2;" : "=r"(r) : "f"(hi), "f"(lo)); return r; }
__device__ __forceinline__ uint32_t pack_bf2(float lo, float hi) { uint32_t r; asm("cvt.rn.bf16x2.f32 %0, %1, %2;" : "=r"(r) : "f"(hi), "f"(lo)); return r; }
__device__ __forceinline__ float bf_lo(uint32_t w) { return __uint_as_float(w << 16); }
__device__ __forceinline__ float bf_hi(uint32_t w) { return __uint_as_float(w & 0xffff0000u); }
__device__ __forceinline__ float rbf(float v) { return __bfloat162float(__float2bfloat16_rn(v)); }
__device__ __forceinline__ float2 h2f(uint32_t w) { return __half22float2(*reinterpret_cast<__half2*>(&w)); }
__device__ __forceinline__ float ex2f(float v) { float r; asm("ex2.approx.ftz.f32 %0, %1;" : "=f"(r) : "f"(v)); return r; }
__device__ __forceinline__ float rcpf_(float v) { float r; asm("rcp.approx.f32 %0, %1;" : "=f"(r) : "f"(v)); return r; }
__device__ __forceinline__ float sqrtf_(float v) { float r; asm("sqrt.approx.f32 %0, %1;" : "=f"(r) : "f"(v)); return r; }
__device__ __forceinline__ float tanhf_(float v) { float r; asm volatile("tanh.approx.f32 %0, %1;" : "=f"(r) : "f"(v)); return r; }

__device__ __forceinline__ void wg_ss_bf16_n256(float* d, uint64_t da, uint64_t db, int sc) {
  asm volatile("{.reg .pred p; setp.ne.b32 p, %130, 0;\n"
    "wgmma.mma_async.sync.aligned.m64n256k16.f32.bf16.bf16 {%0, %1, %2, %3, %4, %5, %6, %7, %8, %9, %10, %11, %12, %13, %14, %15, %16, %17, %18, %19, %20, %21, %22, %23, %24, %25, %26, %27, %28, %29, %30, %31, %32, %33, %34, %35, %36, %37, %38, %39, %40, %41, %42, %43, %44, %45, %46, %47, %48, %49, %50, %51, %52, %53, %54, %55, %56, %57, %58, %59, %60, %61, %62, %63, %64, %65, %66, %67, %68, %69, %70, %71, %72, %73, %74, %75, %76, %77, %78, %79, %80, %81, %82, %83, %84, %85, %86, %87, %88, %89, %90, %91, %92, %93, %94, %95, %96, %97, %98, %99, %100, %101, %102, %103, %104, %105, %106, %107, %108, %109, %110, %111, %112, %113, %114, %115, %116, %117, %118, %119, %120, %121, %122, %123, %124, %125, %126, %127}, %128, %129, p, 1, 1, 0, 1;}\n"
    : "+f"(d[0]), "+f"(d[1]), "+f"(d[2]), "+f"(d[3]), "+f"(d[4]), "+f"(d[5]), "+f"(d[6]), "+f"(d[7]), "+f"(d[8]), "+f"(d[9]), "+f"(d[10]), "+f"(d[11]), "+f"(d[12]), "+f"(d[13]), "+f"(d[14]), "+f"(d[15]), "+f"(d[16]), "+f"(d[17]), "+f"(d[18]), "+f"(d[19]), "+f"(d[20]), "+f"(d[21]), "+f"(d[22]), "+f"(d[23]), "+f"(d[24]), "+f"(d[25]), "+f"(d[26]), "+f"(d[27]), "+f"(d[28]), "+f"(d[29]), "+f"(d[30]), "+f"(d[31]), "+f"(d[32]), "+f"(d[33]), "+f"(d[34]), "+f"(d[35]), "+f"(d[36]), "+f"(d[37]), "+f"(d[38]), "+f"(d[39]), "+f"(d[40]), "+f"(d[41]), "+f"(d[42]), "+f"(d[43]), "+f"(d[44]), "+f"(d[45]), "+f"(d[46]), "+f"(d[47]), "+f"(d[48]), "+f"(d[49]), "+f"(d[50]), "+f"(d[51]), "+f"(d[52]), "+f"(d[53]), "+f"(d[54]), "+f"(d[55]), "+f"(d[56]), "+f"(d[57]), "+f"(d[58]), "+f"(d[59]), "+f"(d[60]), "+f"(d[61]), "+f"(d[62]), "+f"(d[63]), "+f"(d[64]), "+f"(d[65]), "+f"(d[66]), "+f"(d[67]), "+f"(d[68]), "+f"(d[69]), "+f"(d[70]), "+f"(d[71]), "+f"(d[72]), "+f"(d[73]), "+f"(d[74]), "+f"(d[75]), "+f"(d[76]), "+f"(d[77]), "+f"(d[78]), "+f"(d[79]), "+f"(d[80]), "+f"(d[81]), "+f"(d[82]), "+f"(d[83]), "+f"(d[84]), "+f"(d[85]), "+f"(d[86]), "+f"(d[87]), "+f"(d[88]), "+f"(d[89]), "+f"(d[90]), "+f"(d[91]), "+f"(d[92]), "+f"(d[93]), "+f"(d[94]), "+f"(d[95]), "+f"(d[96]), "+f"(d[97]), "+f"(d[98]), "+f"(d[99]), "+f"(d[100]), "+f"(d[101]), "+f"(d[102]), "+f"(d[103]), "+f"(d[104]), "+f"(d[105]), "+f"(d[106]), "+f"(d[107]), "+f"(d[108]), "+f"(d[109]), "+f"(d[110]), "+f"(d[111]), "+f"(d[112]), "+f"(d[113]), "+f"(d[114]), "+f"(d[115]), "+f"(d[116]), "+f"(d[117]), "+f"(d[118]), "+f"(d[119]), "+f"(d[120]), "+f"(d[121]), "+f"(d[122]), "+f"(d[123]), "+f"(d[124]), "+f"(d[125]), "+f"(d[126]), "+f"(d[127])
    : "l"(da), "l"(db), "r"(sc));
}

__device__ __forceinline__ void wg_ss_bf16_n256k(float* d, uint64_t da, uint64_t db, int sc) {
  asm volatile("{.reg .pred p; setp.ne.b32 p, %130, 0;\n"
    "wgmma.mma_async.sync.aligned.m64n256k16.f32.bf16.bf16 {%0, %1, %2, %3, %4, %5, %6, %7, %8, %9, %10, %11, %12, %13, %14, %15, %16, %17, %18, %19, %20, %21, %22, %23, %24, %25, %26, %27, %28, %29, %30, %31, %32, %33, %34, %35, %36, %37, %38, %39, %40, %41, %42, %43, %44, %45, %46, %47, %48, %49, %50, %51, %52, %53, %54, %55, %56, %57, %58, %59, %60, %61, %62, %63, %64, %65, %66, %67, %68, %69, %70, %71, %72, %73, %74, %75, %76, %77, %78, %79, %80, %81, %82, %83, %84, %85, %86, %87, %88, %89, %90, %91, %92, %93, %94, %95, %96, %97, %98, %99, %100, %101, %102, %103, %104, %105, %106, %107, %108, %109, %110, %111, %112, %113, %114, %115, %116, %117, %118, %119, %120, %121, %122, %123, %124, %125, %126, %127}, %128, %129, p, 1, 1, 0, 0;}\n"
    : "+f"(d[0]), "+f"(d[1]), "+f"(d[2]), "+f"(d[3]), "+f"(d[4]), "+f"(d[5]), "+f"(d[6]), "+f"(d[7]), "+f"(d[8]), "+f"(d[9]), "+f"(d[10]), "+f"(d[11]), "+f"(d[12]), "+f"(d[13]), "+f"(d[14]), "+f"(d[15]), "+f"(d[16]), "+f"(d[17]), "+f"(d[18]), "+f"(d[19]), "+f"(d[20]), "+f"(d[21]), "+f"(d[22]), "+f"(d[23]), "+f"(d[24]), "+f"(d[25]), "+f"(d[26]), "+f"(d[27]), "+f"(d[28]), "+f"(d[29]), "+f"(d[30]), "+f"(d[31]), "+f"(d[32]), "+f"(d[33]), "+f"(d[34]), "+f"(d[35]), "+f"(d[36]), "+f"(d[37]), "+f"(d[38]), "+f"(d[39]), "+f"(d[40]), "+f"(d[41]), "+f"(d[42]), "+f"(d[43]), "+f"(d[44]), "+f"(d[45]), "+f"(d[46]), "+f"(d[47]), "+f"(d[48]), "+f"(d[49]), "+f"(d[50]), "+f"(d[51]), "+f"(d[52]), "+f"(d[53]), "+f"(d[54]), "+f"(d[55]), "+f"(d[56]), "+f"(d[57]), "+f"(d[58]), "+f"(d[59]), "+f"(d[60]), "+f"(d[61]), "+f"(d[62]), "+f"(d[63]), "+f"(d[64]), "+f"(d[65]), "+f"(d[66]), "+f"(d[67]), "+f"(d[68]), "+f"(d[69]), "+f"(d[70]), "+f"(d[71]), "+f"(d[72]), "+f"(d[73]), "+f"(d[74]), "+f"(d[75]), "+f"(d[76]), "+f"(d[77]), "+f"(d[78]), "+f"(d[79]), "+f"(d[80]), "+f"(d[81]), "+f"(d[82]), "+f"(d[83]), "+f"(d[84]), "+f"(d[85]), "+f"(d[86]), "+f"(d[87]), "+f"(d[88]), "+f"(d[89]), "+f"(d[90]), "+f"(d[91]), "+f"(d[92]), "+f"(d[93]), "+f"(d[94]), "+f"(d[95]), "+f"(d[96]), "+f"(d[97]), "+f"(d[98]), "+f"(d[99]), "+f"(d[100]), "+f"(d[101]), "+f"(d[102]), "+f"(d[103]), "+f"(d[104]), "+f"(d[105]), "+f"(d[106]), "+f"(d[107]), "+f"(d[108]), "+f"(d[109]), "+f"(d[110]), "+f"(d[111]), "+f"(d[112]), "+f"(d[113]), "+f"(d[114]), "+f"(d[115]), "+f"(d[116]), "+f"(d[117]), "+f"(d[118]), "+f"(d[119]), "+f"(d[120]), "+f"(d[121]), "+f"(d[122]), "+f"(d[123]), "+f"(d[124]), "+f"(d[125]), "+f"(d[126]), "+f"(d[127])
    : "l"(da), "l"(db), "r"(sc));
}

__device__ __forceinline__ void wg_rs_bf16_n64(float* d, uint32_t a0, uint32_t a1, uint32_t a2, uint32_t a3, uint64_t db, int sc) {
  asm volatile("{.reg .pred p; setp.ne.b32 p, %37, 0;\n"
    "wgmma.mma_async.sync.aligned.m64n64k16.f32.bf16.bf16 {%0, %1, %2, %3, %4, %5, %6, %7, %8, %9, %10, %11, %12, %13, %14, %15, %16, %17, %18, %19, %20, %21, %22, %23, %24, %25, %26, %27, %28, %29, %30, %31}, {%32,%33,%34,%35}, %36, p, 1, 1, 1;}\n"
    : "+f"(d[0]), "+f"(d[1]), "+f"(d[2]), "+f"(d[3]), "+f"(d[4]), "+f"(d[5]), "+f"(d[6]), "+f"(d[7]), "+f"(d[8]), "+f"(d[9]), "+f"(d[10]), "+f"(d[11]), "+f"(d[12]), "+f"(d[13]), "+f"(d[14]), "+f"(d[15]), "+f"(d[16]), "+f"(d[17]), "+f"(d[18]), "+f"(d[19]), "+f"(d[20]), "+f"(d[21]), "+f"(d[22]), "+f"(d[23]), "+f"(d[24]), "+f"(d[25]), "+f"(d[26]), "+f"(d[27]), "+f"(d[28]), "+f"(d[29]), "+f"(d[30]), "+f"(d[31])
    : "r"(a0), "r"(a1), "r"(a2), "r"(a3), "l"(db), "r"(sc));
}

__device__ __forceinline__ void wg_rs_f16_n32k(float* d, uint32_t a0, uint32_t a1, uint32_t a2, uint32_t a3, uint64_t db, int sc) {
  asm volatile("{.reg .pred p; setp.ne.b32 p, %21, 0;\n"
    "wgmma.mma_async.sync.aligned.m64n32k16.f32.f16.f16 {%0, %1, %2, %3, %4, %5, %6, %7, %8, %9, %10, %11, %12, %13, %14, %15}, {%16,%17,%18,%19}, %20, p, 1, 1, 0;}\n"
    : "+f"(d[0]), "+f"(d[1]), "+f"(d[2]), "+f"(d[3]), "+f"(d[4]), "+f"(d[5]), "+f"(d[6]), "+f"(d[7]), "+f"(d[8]), "+f"(d[9]), "+f"(d[10]), "+f"(d[11]), "+f"(d[12]), "+f"(d[13]), "+f"(d[14]), "+f"(d[15])
    : "r"(a0), "r"(a1), "r"(a2), "r"(a3), "l"(db), "r"(sc));
}

__device__ __forceinline__ void wg_rs_f16_n24t(float* d, uint32_t a0, uint32_t a1, uint32_t a2, uint32_t a3, uint64_t db, int sc) {
  asm volatile("{.reg .pred p; setp.ne.b32 p, %17, 0;\n"
    "wgmma.mma_async.sync.aligned.m64n24k16.f32.f16.f16 {%0, %1, %2, %3, %4, %5, %6, %7, %8, %9, %10, %11}, {%12,%13,%14,%15}, %16, p, 1, 1, 1;}\n"
    : "+f"(d[0]), "+f"(d[1]), "+f"(d[2]), "+f"(d[3]), "+f"(d[4]), "+f"(d[5]), "+f"(d[6]), "+f"(d[7]), "+f"(d[8]), "+f"(d[9]), "+f"(d[10]), "+f"(d[11])
    : "r"(a0), "r"(a1), "r"(a2), "r"(a3), "l"(db), "r"(sc));
}

__device__ __forceinline__ void wg_rs_f16_n16t(float* d, uint32_t a0, uint32_t a1, uint32_t a2, uint32_t a3, uint64_t db, int sc) {
  asm volatile("{.reg .pred p; setp.ne.b32 p, %13, 0;\n"
    "wgmma.mma_async.sync.aligned.m64n16k16.f32.f16.f16 {%0, %1, %2, %3, %4, %5, %6, %7}, {%8,%9,%10,%11}, %12, p, 1, 1, 1;}\n"
    : "+f"(d[0]), "+f"(d[1]), "+f"(d[2]), "+f"(d[3]), "+f"(d[4]), "+f"(d[5]), "+f"(d[6]), "+f"(d[7])
    : "r"(a0), "r"(a1), "r"(a2), "r"(a3), "l"(db), "r"(sc));
}

__device__ __forceinline__ void wg_ss_f16_n48t(float* d, uint64_t da, uint64_t db, int sc) {
  asm volatile("{.reg .pred p; setp.ne.b32 p, %26, 0;\n"
    "wgmma.mma_async.sync.aligned.m64n48k16.f32.f16.f16 {%0, %1, %2, %3, %4, %5, %6, %7, %8, %9, %10, %11, %12, %13, %14, %15, %16, %17, %18, %19, %20, %21, %22, %23}, %24, %25, p, 1, 1, 1, 1;}\n"
    : "+f"(d[0]), "+f"(d[1]), "+f"(d[2]), "+f"(d[3]), "+f"(d[4]), "+f"(d[5]), "+f"(d[6]), "+f"(d[7]), "+f"(d[8]), "+f"(d[9]), "+f"(d[10]), "+f"(d[11]), "+f"(d[12]), "+f"(d[13]), "+f"(d[14]), "+f"(d[15]), "+f"(d[16]), "+f"(d[17]), "+f"(d[18]), "+f"(d[19]), "+f"(d[20]), "+f"(d[21]), "+f"(d[22]), "+f"(d[23])
    : "l"(da), "l"(db), "r"(sc));
}

struct cf { float x, y; };
__device__ __forceinline__ cf cmul(cf a, cf b) { cf r; r.x = fmaf(a.x, b.x, -a.y * b.y); r.y = fmaf(a.x, b.y, a.y * b.x); return r; }
__device__ __forceinline__ cf zpow(float rho2, float phi, float e) {
  const float m = ex2f(rho2 * e), ang = phi * e;
  cf r; r.x = m * __cosf(ang); r.y = m * __sinf(ang); return r;
}
__device__ __forceinline__ __half2 H2(uint32_t v) { return *reinterpret_cast<__half2*>(&v); }
__device__ __forceinline__ uint32_t U32(__half2 v) { return *reinterpret_cast<uint32_t*>(&v); }
struct h2c { __half2 x, y; };
template <bool CONJ>
__device__ __forceinline__ void hprod2(uint32_t re, uint32_t im, h2c r, uint32_t& ore, uint32_t& oim) {
  if (CONJ) {
    ore = U32(__hfma2(H2(re), r.x, __hmul2(H2(im), r.y)));
    oim = U32(__hfma2(H2(im), r.x, __hneg2(__hmul2(H2(re), r.y))));
  } else {
    ore = U32(__hfma2(H2(re), r.x, __hneg2(__hmul2(H2(im), r.y))));
    oim = U32(__hfma2(H2(re), r.y, __hmul2(H2(im), r.x)));
  }
}
__device__ __forceinline__ cf csq(cf a) { cf r; r.x = fmaf(a.x, a.x, -a.y * a.y); r.y = (a.x + a.x) * a.y; return r; }
__device__ __forceinline__ cf cmulc(cf a, cf b) { cf r; r.x = fmaf(a.x, b.x, a.y * b.y); r.y = fmaf(a.y, b.x, -a.x * b.y); return r; }
__device__ __forceinline__ h2c pk(cf a) { h2c r; r.x = H2(pack_h2(a.x, a.x)); r.y = H2(pack_h2(a.y, a.y)); return r; }
__device__ __forceinline__ uint32_t ldg32(const void* p, int o) { uint32_t v; asm volatile("ld.global.nc.b32 %0, [%1];" : "=r"(v) : "l"((const char*)p + o)); return v; }
__device__ __forceinline__ uint32_t hadd2u(uint32_t a, uint32_t b) { return U32(__hadd2(H2(a), H2(b))); }

struct KgIn { uint32_t cur[6], nxt[6], ldt, dk; bool odd; };
__device__ __forceinline__ float pow2_floor(float v) { return __uint_as_float(__float_as_uint(fminf(fmaxf(v, 1e-30f), 1e30f)) & 0x7f800000u); }
template <class Mid0, class Mid1>
__device__ __forceinline__ void kgen_wg(KgIn& k, int nw, uint32_t stg, uint32_t tbl, uint32_t mxa, int w, int lane, int barid, Mid0 mid0, Mid1 mid1) {
  float dl, dt, inv_sc;
  {
    const uint32_t M = 0x7fff7fffu;
    uint32_t mx[2];
#pragma unroll
    for (int i = 0; i < 2; i++) {
      const uint32_t m = __vmaxu2(__vmaxu2(k.cur[2 + 2 * i] & M, k.cur[3 + 2 * i] & M), __vmaxu2(k.nxt[2 + 2 * i] & M, k.nxt[3 + 2 * i] & M));
      mx[i] = __reduce_max_sync(0xffffffffu, max(m << 16, m & 0xffff0000u));
    }
    if (lane == 0) sts32f(mxa + w * 4, __uint_as_float(mx[0]) * __uint_as_float(mx[1]));
    dt = rbf(ex2f((k.odd ? bf_hi(k.ldt) : bf_lo(k.ldt)) * 1.4426950408889634f));
    const float dsk = (k.odd ? bf_hi(k.dk) : bf_lo(k.dk)) * rcpf_(dt);
    bar_sync(barid, 128);
    const float2 m0 = lds64f(mxa + (w & 2) * 4), m1 = lds64f(mxa + (nw == 1 ? (w & 2) ^ 2 : (w & 2)) * 4);
    const float sc = pow2_floor(fmaxf(0.125f * fmaxf(fmaxf(m0.x, m0.y), fmaxf(m1.x, m1.y)), fabsf(dsk) * (1.f / 4096.f)));
    inv_sc = rcpf_(sc);
    if (lane == 0) sts64f(tbl + TBL_SC + 8, dt * sc, dsk * inv_sc);
    dl = dt * 1.4426950408889634f;
  }
  const uint32_t sa = stg + (w >> 1) * 8192 + (32 * (w & 1) + lane) * 16, sc_ = sa + 16384 - (w >> 1) * 2048;
  const uint64_t dA = mkdesc(stg, 128, 2048, 0), dB = mkdesc(stg + 16384, 128, 2048, 0);
  float acc[24];
#pragma unroll 1
  for (int it = 0; it < 2 * nw; it++) {
    const uint32_t sel = (it & 1) ? 0x3244u : 0x1044u;
    float v[6];
#pragma unroll
    for (int i = 0; i < 6; i++) { v[i] = __uint_as_float(__byte_perm(k.cur[i], 0, sel)); if (it == 1) k.cur[i] = k.nxt[i]; }
    const float rho2 = v[0] * dl, phi = v[1] * dt;
    const cf bb = {v[2] * inv_sc, v[3] * -inv_sc}, cc = {v[4], v[5]};
    const cf X0 = cmulc(bb, cc);
    const cf z1 = zpow(rho2, phi, 1.f), z64 = zpow(rho2, phi, 64.f);
    const cf z2 = csq(z1), z3 = cmul(z2, z1), z4 = csq(z2), z8 = csq(z4), z16 = csq(z8), z24 = cmul(z16, z8), z32 = csq(z16);
    const cf z128 = csq(z64), y1 = csq(z128), y2 = csq(y1), y3 = cmul(y2, y1), y4 = csq(y2);
    const cf X4 = cmulc(X0, z4), W4 = cmulc(X0, y4), W8 = cmulc(W4, y4), W5 = cmulc(W4, y1);
    uint32_t re[4], im[4], r2[4], i2[4];
    re[0] = pack_h2(X0.x, X4.x); im[0] = pack_h2(X0.y, X4.y);
    hprod2<true>(re[0], im[0], pk(z1), re[1], im[1]);
    hprod2<true>(re[0], im[0], pk(z2), re[2], im[2]);
    hprod2<true>(re[0], im[0], pk(z3), re[3], im[3]);
    const h2c hy1 = pk(y1), hy2 = pk(y2);
    hprod2<true>(re[0], im[0], hy1, r2[0], i2[0]);
    hprod2<true>(re[2], im[2], hy1, r2[1], i2[1]);
    hprod2<true>(re[0], im[0], hy2, r2[2], i2[2]);
    hprod2<true>(re[0], im[0], pk(y3), r2[3], i2[3]);
    wg_wait<0>();
    bar_sync(barid, 128);
    sts128(sc_, re[0], re[1], re[2], re[3]);
    sts128(sc_ + 1024, im[0], im[1], im[2], im[3]);
    sts128(sc_ + 2048, r2[0], r2[1], r2[2], r2[3]);
    sts128(sc_ + 3072, i2[0], i2[1], i2[2], i2[3]);
    re[0] = pack_h2(W4.x, W5.x); im[0] = pack_h2(W4.y, W5.y);
    hprod2<true>(re[0], im[0], hy2, re[1], im[1]);
    sts128(sc_ + 4096, re[0], re[1], pack_h2(W8.x, 0.f), 0u);
    sts128(sc_ + 5120, im[0], im[1], pack_h2(W8.y, 0.f), 0u);
    re[0] = pack_h2(1.f, z32.x); im[0] = pack_h2(0.f, z32.y);
    hprod2<false>(re[0], im[0], pk(z8), re[1], im[1]);
    hprod2<false>(re[0], im[0], pk(z16), re[2], im[2]);
    hprod2<false>(re[0], im[0], pk(z24), re[3], im[3]);
    const h2c h64 = pk(z64), h128 = pk(z128);
#pragma unroll
    for (int j = 0; j < 4; j++) hprod2<false>(re[j], im[j], h64, r2[j], i2[j]);
    sts128(sa, re[0], re[1], re[2], re[3]);
    sts128(sa + 1024, im[0], im[1], im[2], im[3]);
    sts128(sa + 2048, r2[0], r2[1], r2[2], r2[3]);
    sts128(sa + 3072, i2[0], i2[1], i2[2], i2[3]);
    uint32_t r3[4], i3[4], r4[4], i4[4];
#pragma unroll
    for (int j = 0; j < 4; j++) { hprod2<false>(re[j], im[j], h128, r3[j], i3[j]); hprod2<false>(r2[j], i2[j], h128, r4[j], i4[j]); }
    sts128(sa + 4096, r3[0], r3[1], r3[2], r3[3]);
    sts128(sa + 5120, i3[0], i3[1], i3[2], i3[3]);
    sts128(sa + 6144, r4[0], r4[1], r4[2], r4[3]);
    sts128(sa + 7168, i4[0], i4[1], i4[2], i4[3]);
    fence_async();
    bar_sync(barid, 128);
    wg_fence();
#pragma unroll
    for (int ks = 0; ks < 8; ks++) wg_ss_f16_n48t(acc, dA + 16 * ks, dB + 16 * ks, (it | ks) != 0);
    wg_commit();
    if (it == 0) mid0();
    if (it == 1) mid1();
  }
  wg_wait<0>();
  fence_regs<24>(acc);
  bar_sync(barid, 128);
#pragma unroll
  for (int h = 0; h < 2; h++)
#pragma unroll
    for (int nt = 0; nt < 3; nt++) {
      const int i = 4 * nt + 2 * h;
      sts64f(stg + (w * 2 + h) * 768 + nt * 256 + lane * 8, (w & 2) ? acc[12 + i] : acc[i], (w & 2) ? acc[13 + i] : acc[1 + i]);
    }
}

__device__ __forceinline__ void tput(uint32_t tbl, int X, uint32_t h) {
  sts16(tbl + 2 * (1296 - X), (uint16_t)h);
  sts16(tbl + TBL_C1 + 2 * (1297 - X), (uint16_t)h);
}
__device__ __forceinline__ void ktab_build(uint32_t src, bool two, int q, uint32_t tbl, int lane) {
  const int tq = lane & 3, r = 8 * q + (lane >> 3) + ((lane >> 2) & 1) * 4;
  float v[6];
  src += q * 768 + lane * 8;
#pragma unroll
  for (int nt = 0; nt < 3; nt++) {
    const float2 a = lds64f(src + nt * 256);
    v[2 * nt] = a.x; v[2 * nt + 1] = a.y;
    if (two) { const float2 c = lds64f(src + nt * 256 + 3072); v[2 * nt] += c.x; v[2 * nt + 1] += c.y; }
  }
  const bool first = (r == 0);
  if (first && tq == 0) { v[0] += lds32f(tbl + TBL_SC + 12); sts32f(tbl + TBL_SC, v[4]); }
  const uint32_t h0 = pack_h2(v[0], v[1]), h1 = pack_h2(v[2], v[3]), h2 = pack_h2(v[4], v[5]);
  tput(tbl, 64 + 8 * r + tq, h0);
  tput(tbl, 68 + 8 * r + tq, h0 >> 16);
  const bool lo = tq < 2;
  const int k2 = 32 * (tq - 2) + r;
  const bool sp = first && tq == 2;
  const int Xa = lo ? 320 + 8 * r + 2 * tq : (sp ? 576 : 911 + k2), Xb = lo ? Xa + 4 : 720 + k2;
  tput(tbl, Xa, h1);
  tput(tbl, Xb, h1 >> 16);
  if (tq == 0 || sp) {
    tput(tbl, Xa + 1, h1);
    if (Xa != 320) tput(tbl, Xa - 1, h1);
    const uint32_t hb = sp ? h1 : h1 >> 16, hc = sp ? h2 : h1 >> 16;
    tput(tbl, sp ? 578 : Xb + 1, hb);
    tput(tbl, sp ? 1295 : Xb - 1, hc);
  }
  if (lo) {
    const int X3 = ((r & 1) ? 1104 : 1231) + 32 * tq + (r >> 1);
    tput(tbl, X3 == 1231 ? 975 : X3, h2);
    tput(tbl, X3 + 16, h2 >> 16);
  }
}

__device__ __forceinline__ void sig_windows(uint32_t sig, int t) {
  uint32_t U[20];
#pragma unroll
  for (int c = 0; c < 5; c++) {
    const int kap = 2 * t - 3 + c + 72;
    const uint4 v = lds128(sig + SIG_U + (kap & 7) * U_LBO + (kap >> 3) * 16);
    U[4 * c] = v.x; U[4 * c + 1] = v.y; U[4 * c + 2] = v.z; U[4 * c + 3] = v.w;
  }
  uint32_t O[19], A2[17], A4[17], V2[8], V5[8];
#pragma unroll
  for (int i = 3; i < 19; i++) O[i] = __byte_perm(U[i - 1], U[i], 0x5432);
#pragma unroll
  for (int i = 3; i < 17; i++) A2[i] = hadd2u(U[i], O[i]);
#pragma unroll
  for (int i = 4; i < 17; i++) A4[i] = hadd2u(A2[i], A2[i - 1]);
#pragma unroll
  for (int k = 0; k < 8; k++) { V2[k] = hadd2u(O[11 + k], U[10 + k]); V5[k] = hadd2u(A4[9 + k], U[7 + k]); }
#pragma unroll
  for (int h = 0; h < 2; h++) {
    sts128(sig + SIG_V3 + t * 32 + h * 16, hadd2u(V2[4 * h], O[10 + 4 * h]), hadd2u(V2[4 * h + 1], O[11 + 4 * h]),
           hadd2u(V2[4 * h + 2], O[12 + 4 * h]), hadd2u(V2[4 * h + 3], O[13 + 4 * h]));
    sts128(sig + SIG_V5 + t * 32 + h * 16, V5[4 * h], V5[4 * h + 1], V5[4 * h + 2], V5[4 * h + 3]);
  }
  if (t < 64) {
    uint32_t V7[8], V9[8];
#pragma unroll
    for (int k = 0; k < 8; k++) {
      V7[k] = hadd2u(V5[k], hadd2u(O[10 + k], O[7 + k]));
      V9[k] = hadd2u(hadd2u(A4[6 + k], A4[4 + k]), U[2 + k]);
    }
#pragma unroll
    for (int h = 0; h < 2; h++) {
      sts128(sig + SIG_V7 + h * 1024 + t * 16, V7[4 * h], V7[4 * h + 1], V7[4 * h + 2], V7[4 * h + 3]);
      sts128(sig + SIG_V9 + h * 1024 + t * 16, V9[4 * h], V9[4 * h + 1], V9[4 * h + 2], V9[4 * h + 3]);
      sts128(sig + SIG_V2 + h * 1024 + t * 16, V2[4 * h], V2[4 * h + 1], V2[4 * h + 2], V2[4 * h + 3]);
    }
  }
}

__device__ __forceinline__ void conv_channel(uint32_t tbl, uint32_t sig, uint32_t y2b, uint32_t y3b, float k1024,
                                             int w, int lane, int barid, float* res) {
  const int g = lane >> 2, tq = lane & 3;
  const uint32_t tb = tbl + ((g & 1) ? TBL_C1 + 2 : 0) + 2 * (1296 - (g - 2 * tq)) - 32 * w + 112;
  float a2[12], a3[8];
#pragma unroll
  for (int i = 0; i < 16; i++) res[i] = 0.f;
#pragma unroll
  for (int i = 0; i < 12; i++) a2[i] = 0.f;
#pragma unroll
  for (int q = 0; q < 4; q++) {
    const float2 f = h2f(lds32(sig + SIG_V2 + (q >> 1) * 1024 + (16 * w + 8 * (q & 1) + g) * 16 + tq * 4));
    a3[2 * q] = k1024 * f.x;
    a3[2 * q + 1] = k1024 * f.y;
  }
  const uint32_t sigu = __shfl_sync(0xffffffffu, opaque(sig), 0);
  const uint64_t dU = mkdesc(sigu + SIG_U, U_LBO, 128, 0);
  const uint64_t dV = mkdesc(sigu, 128, 1024, 0);
  fence_regs<16>(res); fence_regs<12>(a2); fence_regs<8>(a3);
  constexpr int LB = 2 * U_LBO / 16;
  uint32_t Rd[43], R2[22], R3[12];
  uint32_t td = tb - 128, t2 = tb - 1440, t3 = tb - 2208;
  uint64_t dd = dU + 9, d2 = dV + (SIG_V3 + 768) / 16, d3 = dV + (SIG_V7 + 768) / 16;
  auto load_group = [&](int gi) {
#pragma unroll
    for (int i = 1; i < 5; i++) Rd[4 * gi + i] = lds32(td - 16 * (4 * gi + i));
    const int e = gi >> 3;
    if ((gi & 7) == 0) { R2[2 * gi + e] = lds32(t2 - 384 * e); R3[gi + e] = lds32(t3 - 256 * e); }
    R2[2 * gi + e + 1] = lds32(t2 - 384 * e - 16 * (2 * (gi & 7) + 1));
    R2[2 * gi + e + 2] = lds32(t2 - 384 * e - 16 * (2 * (gi & 7) + 2));
    if (!(gi & 1)) {
      R3[gi + e + 1] = lds32(t3 - 256 * e - 16 * ((gi & 7) + 1));
      R3[gi + e + 2] = lds32(t3 - 256 * e - 16 * ((gi & 7) + 2));
    }
  };
  auto dense = [&](int n) {
    wg_rs_f16_n32k(res, Rd[2 * n + 1], Rd[2 * n + 2], Rd[2 * n], Rd[2 * n + 1], dd + ((3 - (n & 3)) * LB + 8 - (n >> 2)) - 8, 1);
  };
  Rd[0] = lds32(td);
  load_group(0);
  load_group(1);
#pragma unroll 1
  for (int sg = 0; sg < 2; sg++) {
#pragma unroll
    for (int gi = 0; gi < 8; gi++) {
      wg_fence();
      dense(2 * gi);
      wg_rs_f16_n24t(a2, R2[2 * gi + 1], R2[2 * gi + 2], R2[2 * gi], R2[2 * gi + 1], d2 - (16 * (gi & 3) + 64 * (gi >> 2)), 1);
      dense(2 * gi + 1);
      if (!(gi & 1)) wg_rs_f16_n16t(a3, R3[gi + 1], R3[gi + 2], R3[gi], R3[gi + 1], d3 - 8 * gi, 1);
      wg_commit();
      wg_wait<1>();
      load_group(gi + 2);
    }
#pragma unroll
    for (int i = 0; i < 9; i++) Rd[i] = Rd[32 + i];
#pragma unroll
    for (int i = 0; i < 5; i++) R2[i] = R2[17 + i];
#pragma unroll
    for (int i = 0; i < 3; i++) R3[i] = R3[9 + i];
    td -= 512; t2 -= 384; t3 -= 256;
    dd -= 4; d2 += 256; d3 += 128;
  }
  Rd[9] = lds32(td - 144); Rd[10] = lds32(td - 160);
  wg_fence();
#pragma unroll
  for (int n = 0; n < 5; n++) dense(n);
  wg_commit();
  wg_wait<1>();
  fence_regs<12>(a2); fence_regs<8>(a3);
  bar_sync(barid, 128);
  {
    const uint32_t o2 = y2b + (136 * w + 8 * g + 2 * tq) * 4, o3 = y3b + (272 * w + 16 * g + 2 * tq) * 4;
#pragma unroll
    for (int q = 0; q < 6; q++) sts64f(o2 + (544 * (q >> 1) + 64 * (q & 1)) * 4, a2[2 * q], a2[2 * q + 1]);
#pragma unroll
    for (int q = 0; q < 4; q++) sts64f(o3 + (8 * (q >> 1) + 136 * (q & 1)) * 4, a3[2 * q], a3[2 * q + 1]);
  }
  bar_sync(barid, 128);
  const uint32_t go = (136 * tq + 16 * w + g) * 4;
  float ex[12];
#pragma unroll
  for (int i = 0; i < 12; i++) {
    const int o = 544 * (i >> 2) + 64 * (i & 1) + 8 * ((i >> 1) & 1);
    ex[i] = lds32f(y2b + go + o * 4);
    if (i >= 4) ex[i] += lds32f(y3b + go + (o - 544) * 4);
  }
  wg_wait<0>();
  fence_regs<16>(res);
#pragma unroll
  for (int i = 0; i < 12; i++) res[4 + i] += ex[i];
}

__device__ __forceinline__ void red16x2(float& a, float& c) {
#pragma unroll
  for (int o = 1; o < 16; o <<= 1) { a += __shfl_xor_sync(0xffffffffu, a, o); c += __shfl_xor_sync(0xffffffffu, c, o); }
}
__device__ __forceinline__ void ln_rows(uint32_t* u, uint32_t term, uint32_t stg_row, int lane) {
  const int j = lane & 15;
  const float piv = __shfl_sync(0xffffffffu, bf_lo(u[0]), lane & 16);
  float s0 = 0.f, s1 = 0.f, q0 = 0.f, q1 = 0.f;
#pragma unroll
  for (int i = 0; i < 14; i++) {
    const float a = bf_lo(u[i]) - piv, c = bf_hi(u[i]) - piv;
    s0 += a; s1 += c; q0 = fmaf(a, a, q0); q1 = fmaf(c, c, q1);
  }
  float s = s0 + s1, q = q0 + q1;
  red16x2(s, q);
  s *= (1.f / D_); q *= (1.f / D_);
  const __nv_bfloat16 m1b = __float2bfloat16_rn(s + piv);
  const __nv_bfloat162 m1v = __halves2bfloat162(m1b, m1b);
  const float den = rbf(sqrtf_(rbf(rbf(fmaxf(fmaf(-s, s, q), 0.f)) + 1e-5f)));
  const float rden = rcpf_(den);
  s0 = s1 = q0 = q1 = 0.f;
#pragma unroll
  for (int i = 0; i < 14; i++) {
    const __nv_bfloat162 cv = __hsub2(*reinterpret_cast<__nv_bfloat162*>(&u[i]), m1v);
    const uint32_t c = *reinterpret_cast<const uint32_t*>(&cv);
    const uint32_t n = pack_bf2(bf_lo(c) * rden, bf_hi(c) * rden);
    const float a = bf_lo(n), e = bf_hi(n);
    s0 += a; s1 += e; q0 = fmaf(a, a, q0); q1 = fmaf(e, e, q1);
    u[i] = pack_h2(a, e);
  }
#pragma unroll
  for (int i = 0; i < 7; i++)
    asm volatile("st.shared.v2.b32 [%0], {%1,%2};" ::"r"(stg_row + (j + 16 * i) * 8), "r"(u[2 * i]), "r"(u[2 * i + 1]) : "memory");
  s = s0 + s1; q = q0 + q1;
  red16x2(s, q);
  s *= (1.f / D_); q *= (1.f / D_);
  const float den2 = rbf(sqrtf_(rbf(rbf(fmaxf(fmaf(-s, s, q), 0.f)) + 1e-5f)));
  if (j == 0) {
    const float ir = den * den2, mu = fmaf(rbf(s), den, __bfloat162float(m1b));
    const float ih = rbf(ir), mh = rbf(mu);
    const uint32_t mm = pack_bf2(mh, mh);
    sts128(term, pack_bf2(mu - mh, ih), mm, pack_bf2(mu - mh, ir - ih), mm);
  }
}

__device__ __forceinline__ void poll_tag(const unsigned* p, uint32_t tag) {
#pragma unroll 1
  for (int it = 0; it < 4096; it++) {
    if (!((ld_relaxed1(p) ^ tag) & 1)) break;
    __nanosleep(32);
  }
}
__device__ __forceinline__ bool last_release(uint32_t cnt) {
  unsigned old;
  asm volatile("atom.relaxed.cta.shared.inc.u32 %0, [%1], 7;" : "=r"(old) : "r"(cnt) : "memory");
  return old == 7;
}
__device__ __forceinline__ int mod7(int v) { return v >= 7 ? v - 7 : v; }

#define IDS const int tid = opaque(tid0), lane = tid & 31, t = tid & 127; (void)lane; (void)t;

__global__ void __launch_bounds__(384, 1)
fused_kernel(const Params p, const __grid_constant__ CUtensorMap tm_x, const __grid_constant__ CUtensorMap tm_w1,
             const __grid_constant__ CUtensorMap tm_w2, const __grid_constant__ CUtensorMap tm_out) {
  const uint32_t sb = smem_u32(smem_raw);
  const uint32_t ms = sb + OFF_M;
  const uint32_t bar0 = ms + M_BAR;
  const int tid0 = threadIdx.x;
  const int wi = __shfl_sync(0xffffffffu, tid0 >> 5, 0), wg = wi >> 2, w = wi & 3;
  const int b = blockIdx.x;
  const bool is_ssm = b >= NMLP;
  const int G = b / NRK, rk = b - G * NRK;
  const int kc0 = (G + rk) % 7;
  TSINIT();
  TSTAMP(0);
  {
    IDS
    TSTAMP(28);
    uint4 ld[7];
    KgIn kin;
    unsigned ep = 0;
    uint32_t b1w;
    const int rl = 2 * wi + (lane >> 4);
    {
      const int d = is_ssm ? 2 * (112 + 3 * (b - NMLP) + wg) + (w >> 1) : (wg < 2 ? 2 * b + wg : 336 + b);
      const int off = d * NST + 64 * (is_ssm ? 2 * (w & 1) : w) + 2 * lane;
      const __nv_bfloat16* P[8] = {p.a_re + off, p.a_im + off, p.b_re + off, p.b_im + off, p.c_re + off, p.c_im + off,
                                   p.log_dt + (d & ~1), p.dskip + (d & ~1)};
      asm volatile("" : "+l"(P[0]), "+l"(P[1]), "+l"(P[2]), "+l"(P[3]), "+l"(P[4]), "+l"(P[5]), "+l"(P[6]), "+l"(P[7]));
#pragma unroll
      for (int i = 0; i < 6; i++) kin.cur[i] = ldg32(P[i], 0);
      kin.ldt = ldg32(P[6], 0); kin.dk = ldg32(P[7], 0);
#pragma unroll
      for (int i = 0; i < 6; i++) kin.nxt[i] = 0u;
      if (is_ssm) {
#pragma unroll
        for (int i = 0; i < 6; i++) kin.nxt[i] = ldg32(P[i], 128);
      }
      asm volatile("" :: "l"(P[0]), "l"(P[1]), "l"(P[2]), "l"(P[3]), "l"(P[4]), "l"(P[5]), "l"(P[6]), "l"(P[7]));
      kin.odd = d & 1;
    }
    const uint32_t tbl = is_ssm ? sb + (4 * wg + (w >> 1)) * TBL : sb + OFF_T + wg * TBL;
#pragma unroll 1
    for (int i = is_ssm ? t & 63 : t; i < TBL_SC / 16; i += is_ssm ? 64 : 128) sts128(tbl + i * 16, 0u, 0u, 0u, 0u);
    const uint32_t lns = is_ssm ? sb + S_WORK + 2 * S_WGB + KSTG : sb + OFF_X + 2 * 16384;
    if (wi < 4 && lane == 0) {
      if (wi < 3) mbar_init(bar0 + 8 * wi, 1);
      asm volatile("fence.mbarrier_init.release.cluster;" ::: "memory");
      if (!is_ssm) asm volatile("prefetch.tensormap [%0];" ::"l"(wi == 0 ? &tm_x : wi == 1 ? &tm_w1 : wi == 2 ? &tm_w2 : &tm_out) : "memory");
    }
    if ((wi == 5 || (wi == 6 && !is_ssm)) && lane == 0)
      asm volatile("cp.async.bulk.prefetch.L2.global [%0], %1;" ::"l"(wi == 5 ? p.x + (size_t)(b & 127) * 16 * D_ : p.w1 + (size_t)b * 4 * F_), "r"(14336) : "memory");
    __syncwarp();
    if (wi == 4 && lane < 16) asm volatile("st.shared.b32 [%0], 0;" ::"r"(ms + M_REL + 4 * lane) : "memory");
    TSTAMP(31);
    auto mid0 = [&]() {
      TSTAMP(27);
      if (wg < 2) {
        const __nv_bfloat16* xr = p.x + (size_t)(16 * (b & 127) + rl) * D_ + 4 * (lane & 15);
#pragma unroll
        for (int i = 0; i < 7; i++) asm volatile("ld.global.nc.v2.b32 {%0,%1}, [%2];" : "=r"(ld[i].x), "=r"(ld[i].y) : "l"(xr + 64 * i));
      } else {
        const __nv_bfloat16* wr = p.w1 + (size_t)(112 * (b & 3) + 4 * w + (lane & 3)) * F_ + 64 * (is_ssm ? 0 : b >> 2) + 8 * (lane >> 2);
        if (t == 96 && !is_ssm)
          asm volatile("cp.async.bulk.prefetch.L2.global [%0], %1;" ::"l"(p.w1 + (size_t)b * 4 * F_), "r"(14336) : "memory");
        b1w = ldg32(p.b1 + 64 * (is_ssm ? 0 : b >> 2) + (t & 62), 0);
        if (t == 32) ep = ld_relaxed1(&p.s->epoch);
      }
    };
    auto mid = [&]() {
    TSTAMP(30);
    if (wi < 2 && lane == 0 && !is_ssm) {
      mbar_expect(bar0 + 8 * wi, 49152);
      tma_2d(sb + OFF_X + wi * 16384, &tm_x, 64 * wi, 128 * G, bar0 + 8 * wi);
      tma_3d(sb + OFF_W + wi * 32768, &tm_w1, 0, 64 * wi, 4 * rk, bar0 + 8 * wi);
    }
    __syncwarp();
    if (wg < 2) {
      uint32_t u[14];
#pragma unroll
      for (int i = 0; i < 7; i++) { u[2 * i] = ld[i].x; u[2 * i + 1] = ld[i].y; }
      ln_rows(u, ms + M_LT + rl * 16, lns + ((rl & 1) | ((rl >> 2) << 1) | ((rl & 2) << 2)) * 912, lane);
      bar_arrive(7, 384);
    } else {
      float cs[4] = {0.f, 0.f, 0.f, 0.f};
      const int g = lane >> 2;
      const uint32_t one = (g & 1) ? 0x3f800000u : 0x00003f80u;
      const uint32_t s0 = (g >> 1) == 0 ? one : 0u, s1 = (g >> 1) == 1 ? one : 0u, s2 = (g >> 1) == 2 ? one : 0u, s3 = (g >> 1) == 3 ? one : 0u;
#pragma unroll
      for (int i = 0; i < 7; i++) {
        mma_bf16(cs, s0, 0u, s1, 0u, un[4 * i], un[4 * i + 1]);
        mma_bf16(cs, s2, 0u, s3, 0u, un[4 * i + 2], un[4 * i + 3]);
      }
      sts32f(ms + M_CSR + (w * 64 + (lane & 3) * 16 + g) * 4, cs[0]);
      sts32f(ms + M_CSR + (w * 64 + (lane & 3) * 16 + g + 8) * 4, cs[1]);
      if (t == 32) { asm volatile("st.shared.b32 [%0], %1;" ::"r"(ms + M_EP), "r"(ep + 1) : "memory"); red_relaxed(&p.s->cntA); }
      bar_sync(7, 384);
      const uint32_t la = lns + (lane & 15) * 912 + (lane >> 4) * 16 + w * 224;
      uint2* dst = (uint2*)(p.s->xnT + (size_t)(56 * w + (lane >> 3)) * 512 + 4 * b) + (lane & 7);
      uint32_t r[28];
#pragma unroll
      for (int k = 0; k < 7; k++) ldsm4t(la + k * 32, r[4 * k], r[4 * k + 1], r[4 * k + 2], r[4 * k + 3]);
      const uint32_t tag = lds32(ms + M_EP) & 1;
      if (b < 128) {
#pragma unroll
        for (int k = 0; k < 14; k++) st_relaxed2(dst + k * 4096, (r[2 * k] & ~1u) | tag, (r[2 * k + 1] & ~1u) | tag);
      }
      if (t < 64 && !is_ssm) {
        const uint32_t a = ms + M_CSR + t * 4;
        const float c = -((lds32f(a) + lds32f(a + 256)) + (lds32f(a + 512) + lds32f(a + 768)));
        const float ch = rbf(c);
        uint2* dx = (uint2*)(p.s->bx + (b >> 4) * 512 + ((b >> 1) & 1) * 256 + ((b >> 2) & 3) * 64 + t) + (b & 1);
        const float b1v = (b & 2) ? 0.f : ((t & 1) ? bf_hi(b1w) : bf_lo(b1w));
        asm volatile("{.reg .b64 a; mov.b64 a, {%1,%2}; st.relaxed.gpu.global.b64 [%0], a;}"
                     ::"l"(dx), "r"(pack_bf2(ch, b1v)), "r"((pack_bf2(c - ch, ch) & ~1u) | tag) : "memory");
      }
      if (t >= 64 && t < 80 && b < 128) {
        const uint4 a = lds128(ms + M_LT + (t - 64) * 16);
        st_b128(p.s->ax + 16 * b + t - 64, tag, a.x, a.y, a.z, a.w);
      }
    }
    TSTAMP(29);
    };
    kgen_wg(kin, is_ssm ? 2 : 1, stg, tbl, ms + M_MX + wg * 16, w, lane, 4 + wg, mid0, mid);
  }
  TSTAMP(1);

  if (is_ssm || wg == 2) {
    asm volatile("setmaxnreg.dec.sync.aligned.u32 136;");
    uint4 v[4], tv[5];
    {
      IDS
      bar_sync(2, 384);
#pragma unroll 1
      for (int c = is_ssm ? 1 : 2; c >= 0; c--) {
        ktab_build(is_ssm ? stg + c * 3072 : (c < 2 ? sb + OFF_A + c * KSTG : stg), !is_ssm, w, (is_ssm ? sb + S_TBL + 4 * wg * TBL : sb + OFF_T) + c * TBL, lane);
        if (c == 2) {
          fence_async();
          bar_sync(6, 128);
          if (t == 0) {
            mbar_expect(bar0 + 16, 49152);
            tma_2d(sb + OFF_X + 2 * 16384, &tm_x, 128, 128 * G, bar0 + 16);
            tma_3d(sb + OFF_W + 2 * 32768, &tm_w1, 0, 128, 4 * rk, bar0 + 16);
          }
          if (t == 96) { bulk_s2g(p.s->tbl + b * (TBL / 16), sb + OFF_T + 2 * TBL, TBL); bulk_commit(); }
          __syncwarp();
        }
      }
      if (!is_ssm) {
#pragma unroll
        for (int q = 0; q < 4; q++) tv[q] = ld_2x64(p.s->bx + 512 * rk + q * 128 + t);
        tv[4] = ld_b128(p.s->ax + 128 * G + t);
      }
      const uint4* src = p.s->xnT + (size_t)(is_ssm ? 112 + 3 * (b - NMLP) + wg : b) * 512 + t;
#pragma unroll
      for (int q = 0; q < 4; q++) v[q] = ld_relaxed4(src + q * 128);
      bar_sync(4 + wg, 128);
    }
    TSTAMP(2);
    if (!is_ssm) {
      IDS
      const unsigned ep1 = lds32(ms + M_EP);
#pragma unroll 1
      for (int it = 0; it < 16 * RETRY_MAX; it++) {
        uint32_t bad = tv[4].x ^ ep1;
#pragma unroll
        for (int q = 0; q < 4; q++) bad |= (tv[q].y ^ ep1) | (tv[q].w ^ ep1);
        if (!__any_sync(0xffffffffu, bad & 1)) break;
        __nanosleep(200);
#pragma unroll
        for (int q = 0; q < 4; q++) tv[q] = ld_2x64(p.s->bx + 512 * rk + q * 128 + t);
        tv[4] = ld_b128(p.s->ax + 128 * G + t);
      }
#pragma unroll
      for (int q = 0; q < 5; q++) sts128(sb + OFF_B + (q < 4 ? B_BX + q * 2048 : B_AX) + t * 16, tv[q].x, tv[q].y, tv[q].z, tv[q].w);
      if (t < 64) sts32f(ms + M_CSR + t * 4, 0.5f * __bfloat162float(p.b2[64 * rk + t]));
      fence_async();
      bar_arrive(1, 384);
      if (t == 64)
        asm volatile("cp.async.bulk.prefetch.L2.global [%0], %1;" ::"l"(p.w2 + (size_t)(256 * rk + 16 * G) * D_), "r"(16 * D_ * 2) : "memory");
    }
#pragma unroll 1
    for (int pi = 0; ; pi++) {
      {
        IDS
        const unsigned ep1 = lds32(ms + M_EP);
        const int pair = !is_ssm ? b : (pi == 0 ? 112 + 3 * (b - NMLP) : (b < NMLP + 12 ? 172 + 3 * (b - NMLP) : 184 + 2 * (b - NMLP))) + wg;
        const uint32_t work = is_ssm ? sb + S_WORK + wg * S_WGB : sb + OFF_A;
        const uint32_t z = work + SIG_V3 - 1024 + (t >> 6) * 4096 + (t & 63) * 16;
        sts128(z, 0u, 0u, 0u, 0u); sts128(z + SIG, 0u, 0u, 0u, 0u);
        if (t < 72) {
          const uint32_t zu = work + SIG_U + (t & 7) * U_LBO + (t >> 3) * 16;
          sts128(zu, 0u, 0u, 0u, 0u); sts128(zu + SIG, 0u, 0u, 0u, 0u);
        }
        const uint4* src = p.s->xnT + (size_t)pair * 512 + t;
#pragma unroll 1
        for (int it = 0; it < RETRY_MAX; it++) {
          uint32_t bad = 0;
#pragma unroll
          for (int q = 0; q < 4; q++) bad |= (((v[q].x ^ ep1) | (v[q].y ^ ep1) | (v[q].z ^ ep1) | (v[q].w ^ ep1)) & 1) << q;
          const unsigned m = __ballot_sync(0xffffffffu, bad);
          if (!m) break;
          if (lane == __ffs(m) - 1) poll_tag((const unsigned*)(src + (__ffs(bad) - 1) * 128) + 3, ep1);
          __syncwarp();
#pragma unroll
          for (int q = 0; q < 4; q++) v[q] = ld_relaxed4(src + q * 128);
        }
        TSTAMP(5);
        const uint32_t a = work + ((t >> 1) & 1) * SIG + SIG_U + (2 * ((t >> 2) & 3) + (t & 1)) * U_LBO + ((t >> 4) + 9) * 16;
#pragma unroll
        for (int q = 0; q < 4; q++) sts128(a + q * 128, v[q].x & ~1u, v[q].y & ~1u, v[q].z & ~1u, v[q].w & ~1u);
        bar_sync(4 + wg, 128);
#pragma unroll 1
        for (int k = w; k < 6; k += 4) sig_windows(work + (k & 1) * SIG, (k >> 1) * 32 + lane);
        fence_async();
        if (t == 96 && !is_ssm) { bulk_wait0(); red_release(&p.s->cntT); }
        if (pi == 1) mbar_wait(bar0 + 8 * wg, 0);
        TSTAMP(6);
        bar_sync(is_ssm ? 4 + wg : 3, is_ssm ? 128 : 384);
        TSTAMP(7);
      }
      uint32_t keep[8];
      float res[16];
#pragma unroll 1
      for (int c = 0; c < 2; c++) {
        IDS
        const uint32_t work = is_ssm ? sb + S_WORK + wg * S_WGB : sb + OFF_A;
        const uint32_t tbl = (is_ssm ? sb + (4 * wg + 2 * pi) * TBL : sb + OFF_T) + c * TBL;
        conv_channel(tbl, work + c * SIG, is_ssm ? work + 2 * SIG + Y3B : sb + OFF_B, work + 2 * SIG, lds32f(tbl + TBL_SC), w, lane, 4 + wg, res);
        TSTAMP(16 + 2 * pi + c);
        const float os = lds32f(tbl + TBL_SC + 8);
        if (c == 0) {
#pragma unroll
          for (int i = 0; i < 8; i++) keep[i] = pack_bf2(res[2 * i] * os, res[2 * i + 1] * os);
          if (is_ssm && pi == 0 && t == 96 && (b < NMLP + 12 || wg < 2)) {
            wait_count(&p.s->cntT, lds32(ms + M_EP) * NMLP);
            asm volatile("fence.proxy.async;" ::: "memory");
            mbar_expect(bar0 + 8 * wg, 2 * TBL);
            bulk_g2s(sb + (4 * wg + 2) * TBL, p.s->tbl + (2 * ((b < NMLP + 12 ? 172 + 3 * (b - NMLP) : 184 + 2 * (b - NMLP)) + wg) - 336) * (TBL / 16),
                     2 * TBL, bar0 + 8 * wg);
          }
          __syncwarp();
        } else {
          const int pair = !is_ssm ? b : (pi == 0 ? 112 + 3 * (b - NMLP) : (b < NMLP + 12 ? 172 + 3 * (b - NMLP) : 184 + 2 * (b - NMLP))) + wg;
          uint4* dst = p.s->s2 + ((size_t)(lane & 3) * 224 + pair) * 32 + w * 8 + (lane >> 2);
          const uint32_t tag = (lds32(ms + M_EP) & 1) * 0x10001u;
#pragma unroll
          for (int nt = 0; nt < 4; nt++) {
            const uint32_t n0 = pack_bf2(res[4 * nt] * os, res[4 * nt + 1] * os), n1 = pack_bf2(res[4 * nt + 2] * os, res[4 * nt + 3] * os);
            const uint32_t k0 = (keep[2 * nt] & 0xfffefffeu) | tag;
            asm volatile("{.reg .b64 a, c; mov.b64 a, {%1,%2}; mov.b64 c, {%3,%4}; st.relaxed.gpu.global.v2.b64 [%0], {a, c};}"
                         ::"l"(dst + nt * 4 * 224 * 32), "r"(__byte_perm(k0, n0, 0x5410)), "r"(__byte_perm(keep[2 * nt + 1], n1, 0x5410)),
                         "r"(__byte_perm(k0, n0, 0x7632)), "r"(__byte_perm(keep[2 * nt + 1], n1, 0x7632)) : "memory");
          }
        }
      }
      TSTAMP(8 + pi);
      TSDUMP();
      {
        IDS
        if (pi == 1 || !is_ssm || (b >= NMLP + 12 && wg == 2)) break;
        const uint4* src = p.s->xnT + (size_t)((b < NMLP + 12 ? 172 + 3 * (b - NMLP) : 184 + 2 * (b - NMLP)) + wg) * 512 + t;
#pragma unroll
        for (int q = 0; q < 4; q++) v[q] = ld_relaxed4(src + q * 128);
      }
    }
    if (b == 0 && tid0 == 256) {
      const unsigned ep1 = lds32(ms + M_EP);
      wait_count(&p.s->cntA, ep1 * NCTA);
      *(volatile unsigned*)&p.s->epoch = ep1;
    }
  } else {
    bar_arrive(1, 384);
    asm volatile("setmaxnreg.inc.sync.aligned.u32 192;");
    bar_sync(7, 384);
    uint32_t H[64];
    {
      float acc[128];
      float p0, q0, p1, q1;
      {
        IDS
        int sl = 0;
#pragma unroll 1
        for (int s = 0; s < 7; s++) {
          mbar_wait(bar0 + 8 * sl, (s >= 3 && s < 6));
          TSTAMP(17 + s);
          const uint64_t da = mkdesc(sb + OFF_X + sl * 16384 + wg * 8192, 16, 1024, 1);
          const uint64_t db = mkdesc(sb + OFF_W + sl * 32768, 8192, 1024, 1);
          wg_fence();
#pragma unroll
          for (int k = 0; k < 4; k++) wg_ss_bf16_n256(acc, da + 2 * k, db + 128 * k, (s | k) != 0);
          wg_commit();
          wg_wait<1>();
          const int pl = sl == 0 ? 2 : sl - 1;
          sl = sl == 2 ? 0 : sl + 1;
          if (s > 0 && lane == 0 && last_release(ms + M_REL + 4 * s)) {
            mbar_expect(bar0 + 8 * pl, s == 5 ? 32768 : 49152);
            if (s < 5) tma_3d(sb + OFF_W + pl * 32768, &tm_w1, 0, 64 * (s + 2), 4 * rk, bar0 + 8 * pl);
            else tma_2d(sb + OFF_W + pl * 32768, &tm_w2, 64 * mod7(rk + s - 4), 256 * rk, bar0 + 8 * pl);
            if (s != 5) tma_2d(sb + OFF_X + pl * 16384, &tm_x, 64 * (s < 5 ? (s + 2) : rk), 128 * G, bar0 + 8 * pl);
          }
        }
        TSTAMP(15);
        asm volatile("setmaxnreg.inc.sync.aligned.u32 184;");
        bar_sync(1, 384);
        wg_fence();
        wg_ss_bf16_n256k(acc, mkdesc(sb + OFF_B + B_AX + wg * 1024, 0, 128, 0), mkdesc(sb + OFF_B + B_BX, 4096, 128, 0), 1);
        wg_commit();
        wg_wait<1>();
        if (lane == 0 && last_release(ms + M_REL + 4 * 7)) {
          mbar_expect(bar0, 65536);
#pragma unroll 1
          for (int c = 2; c < 4; c++) tma_2d(sb + (c - 2) * OFF_X, &tm_w2, 64 * mod7(rk + 1 + c), 256 * rk, bar0);
        }
        bar_arrive(3, 384);
        const uint32_t ra = sb + OFF_B + B_AX + (16 * wi + (lane >> 2)) * 16;
        const float r0 = rcpf_(bf_hi(lds32(ra)) + bf_hi(lds32(ra + 8))), r1 = rcpf_(bf_hi(lds32(ra + 128)) + bf_hi(lds32(ra + 136)));
        p0 = 0.7978845608028654f * r0; q0 = 0.0356774081363001f * r0 * r0 * r0;
        p1 = 0.7978845608028654f * r1; q1 = 0.0356774081363001f * r1 * r1 * r1;
      }
      wg_wait<0>();
      fence_regs<128>(acc);
      TSTAMP(16);
#pragma unroll 1
      for (int hf = 0; hf < 2; hf++) {
        float th[8];
#pragma unroll
        for (int i = 0; i < 35; i++) {
          if (i < 32) {
            const float pp = (i & 1) ? p1 : p0, qq = (i & 1) ? q1 : q0;
            const float a = acc[2 * i], c = acc[2 * i + 1];
            th[2 * (i & 3)] = tanhf_(a * fmaf(a * a, qq, pp)); th[2 * (i & 3) + 1] = tanhf_(c * fmaf(c * c, qq, pp));
          }
          if (i >= 3) {
            const int j = i - 3;
            asm volatile("{.reg .f32 x, y; fma.rn.f32 x, %0, %5, %0; fma.rn.f32 y, %1, %6, %1; mov.f32 %0, %3; mov.f32 %1, %4;\n"
                         ".reg .b32 h; cvt.rn.bf16x2.f32 h, y, x; mov.b32 %2, h;}"
                         : "+f"(acc[2 * j]), "+f"(acc[2 * j + 1]), "=f"(acc[64 + j])
                         : "f"(acc[64 + 2 * j]), "f"(acc[65 + 2 * j]), "f"(th[2 * (j & 3)]), "f"(th[2 * (j & 3) + 1]));
          }
        }
      }
#pragma unroll
      for (int i = 0; i < 32; i++) { H[i] = __float_as_uint(acc[i]); H[32 + i] = __float_as_uint(acc[64 + i]); }
    }
    TSTAMP(3);
    IDS
    float acc[32], pre[32];
    uint32_t pk[16];
#pragma unroll
    for (int i = 0; i < 32; i++) pre[i] = 0.f;
    const uint32_t tag = lds32(ms + M_EP) & 1;
    const uint4* inbox = p.s->part + (uint32_t)(b * 6 * 1024 + tid);
    uint4 rv[4];
    auto fetch = [&](int slot) {
#pragma unroll
      for (int q = 0; q < 4; q++) rv[q] = ld_b128(inbox + slot * 1024 + q * 256);
    };
    auto recv = [&](int slot) {
#pragma unroll 1
      for (int it = 0; it < RETRY_MAX; it++) {
        const unsigned m = __ballot_sync(0xffffffffu, ((rv[0].x ^ tag) | (rv[1].x ^ tag) | (rv[2].x ^ tag) | (rv[3].x ^ tag)) & 1);
        if (!m) break;
        if (lane == __ffs(m) - 1) poll_tag((const unsigned*)(inbox + slot * 1024 + 768), tag);
        __syncwarp();
        fetch(slot);
      }
#pragma unroll
      for (int q = 0; q < 4; q++) {
        const uint32_t u[4] = {rv[q].x, rv[q].y, rv[q].z, rv[q].w};
#pragma unroll
        for (int k = 0; k < 4; k++) { pre[8 * q + 2 * k] += bf_lo(u[k]); pre[8 * q + 2 * k + 1] += bf_hi(u[k]); }
      }
    };
#pragma unroll 1
    for (int s = 0; s < 7; s++) {
      if (s != 3) mbar_wait(bar0 + 8 * ((0x0210021u >> (4 * s)) & 3), (0x34 >> s) & 1);
      const uint64_t db = mkdesc(sb + ((0x0213021u >> (4 * s)) & 3) * 32768, 8192, 1024, 1);
      wg_fence();
#pragma unroll
      for (int k = 0; k < 16; k++) wg_rs_bf16_n64(acc, H[4 * k], H[4 * k + 1], H[4 * k + 2], H[4 * k + 3], db + 128 * k, k != 0);
      wg_commit();
      if (s > 0) {
        uint4* dst = p.s->part + (uint32_t)(((G * 7 + mod7(rk + s)) * 6 + s - 1) * 1024 + tid);
#pragma unroll
        for (int q = 0; q < 4; q++) st_b128(dst + q * 256, tag, pk[4 * q], pk[4 * q + 1], pk[4 * q + 2], pk[4 * q + 3]);
        if (s < 4 && lane == 0 && last_release(ms + M_REL + 4 * (7 + s))) {
          const int sl = (0x0210u >> (4 * s)) & 3;
          mbar_expect(bar0 + 8 * sl, 32768);
          tma_2d(sb + sl * 32768, &tm_w2, 64 * mod7(mod7(rk + 4 + s)), 256 * rk, bar0 + 8 * sl);
        }
        __syncwarp();
      }
      if (s >= 4) recv(s - 4);
      if (s >= 3) fetch(s - 3);
      wg_wait<0>();
      fence_regs<32>(acc);
#pragma unroll
      for (int k = 0; k < 16; k++) pk[k] = pack_bf2(acc[2 * k], acc[2 * k + 1]);
      TSTAMP(4 + s);
    }
    {
      const uint2* sp = (const uint2*)(p.s->s2 + ((size_t)G * 224 + 32 * rk + (lane & 3)) * 32 + w * 8 + (lane >> 2)) + wg;
#pragma unroll 1
      for (int it = 0; it < RETRY_MAX; it++) {
#pragma unroll
        for (int i = 0; i < 8; i++)
          asm volatile("{.reg .b64 a; ld.relaxed.gpu.global.b64 a, [%2]; mov.b64 {%0,%1}, a;}"
                       : "=r"(pk[2 * i]), "=r"(pk[2 * i + 1]) : "l"(sp + i * 4 * 64) : "memory");
#pragma unroll 1
        for (int s = it ? 6 : 3; s < 6; s++) { recv(s); if (s < 5) fetch(s + 1); }
        uint32_t bad = 0;
#pragma unroll
        for (int i = 0; i < 8; i++) bad |= ((pk[2 * i] ^ tag) & 1) << i;
        const unsigned m = __ballot_sync(0xffffffffu, bad);
        if (!m) break;
        if (lane == __ffs(m) - 1) poll_tag((const unsigned*)(sp + (__ffs(bad) - 1) * 4 * 64), tag);
        __syncwarp();
      }
    }
    TSTAMP(12);
    const int g = lane >> 2, tq = lane & 3;
    const uint32_t xa = sb + OFF_X + 2 * 16384 + (16 * wi + (lane & 15)) * 128;
    uint32_t xw[16];
#pragma unroll
    for (int q = 0; q < 4; q++) ldsm4(xa + (((2 * q + (lane >> 4)) ^ (lane & 7)) << 4), xw[4 * q], xw[4 * q + 1], xw[4 * q + 2], xw[4 * q + 3]);
    const uint32_t ra = sb + OFF_B + B_AX + (16 * wi + g) * 16;
    const float r0 = 0.25f * rcpf_(bf_hi(lds32(ra)) + bf_hi(lds32(ra + 8))), r1 = 0.25f * rcpf_(bf_hi(lds32(ra + 128)) + bf_hi(lds32(ra + 136)));
#pragma unroll
    for (int i = 0; i < 8; i++) {
      const float2 bb = lds64f(ms + M_CSR + (8 * i + 2 * tq) * 4);
#pragma unroll
      for (int e = 0; e < 2; e++) {
        const int k = 2 * i + e;
        const float h0 = fmaf(acc[2 * k] + pre[2 * k], e ? r1 : r0, bb.x), h1 = fmaf(acc[2 * k + 1] + pre[2 * k + 1], e ? r1 : r0, bb.y);
        const uint32_t gw = pack_bf2(fmaf(h0, tanhf_(h0), h0), fmaf(h1, tanhf_(h1), h1));
        asm("fma.rn.bf16x2 %0, %1, %2, %0;" : "+r"(xw[k]) : "r"(pk[k]), "r"(gw));
      }
    }
#pragma unroll
    for (int q = 0; q < 4; q++) stsm4(xa + (((2 * q + (lane >> 4)) ^ (lane & 7)) << 4), xw[4 * q], xw[4 * q + 1], xw[4 * q + 2], xw[4 * q + 3]);
    fence_async();
    __syncwarp();
    if (lane == 0) {
      tma_store_2d(&tm_out, sb + OFF_X + 2 * 16384 + wi * 2048, 64 * rk, 128 * G + 16 * wi);
      bulk_commit();
      bulk_wait0_read();
    }
    TSTAMP(13);
    TSDUMP();
  }
}

typedef CUresult (*EncodeFn)(CUtensorMap*, CUtensorMapDataType, cuuint32_t, void*, const cuuint64_t*, const cuuint64_t*,
                             const cuuint32_t*, const cuuint32_t*, CUtensorMapInterleave, CUtensorMapSwizzle,
                             CUtensorMapL2promotion, CUtensorMapFloatOOBfill);

void make_map(EncodeFn fn, CUtensorMap* m, const void* ptr, int rank, const cuuint64_t* dims, const cuuint64_t* strides, const cuuint32_t* box) {
  const cuuint32_t es[3] = {1, 1, 1};
  fn(m, CU_TENSOR_MAP_DATA_TYPE_BFLOAT16, rank, const_cast<void*>(ptr), dims, strides, box, es, CU_TENSOR_MAP_INTERLEAVE_NONE,
     CU_TENSOR_MAP_SWIZZLE_128B, CU_TENSOR_MAP_L2_PROMOTION_L2_128B, CU_TENSOR_MAP_FLOAT_OOB_FILL_NONE);
}

}

extern "C" void kernel_launch(void* const* d_in, const int* in_sizes, int n_in, void* d_out, int out_size) {
  (void)in_sizes; (void)n_in; (void)out_size;
  void* fnp = nullptr;
  cudaDriverEntryPointQueryResult qr;
  cudaGetDriverEntryPoint("cuTensorMapEncodeTiled", &fnp, cudaEnableDefault, &qr);
  EncodeFn fn = (EncodeFn)fnp;
  Params p;
  p.x = (const __nv_bfloat16*)d_in[0];
  p.a_re = (const __nv_bfloat16*)d_in[1]; p.a_im = (const __nv_bfloat16*)d_in[2];
  p.b_re = (const __nv_bfloat16*)d_in[3]; p.b_im = (const __nv_bfloat16*)d_in[4];
  p.c_re = (const __nv_bfloat16*)d_in[5]; p.c_im = (const __nv_bfloat16*)d_in[6];
  p.log_dt = (const __nv_bfloat16*)d_in[7]; p.dskip = (const __nv_bfloat16*)d_in[8];
  p.w1 = (const __nv_bfloat16*)d_in[10]; p.b1 = (const __nv_bfloat16*)d_in[11];
  p.w2 = (const __nv_bfloat16*)d_in[12]; p.b2 = (const __nv_bfloat16*)d_in[13];
  void* sp = nullptr;
  cudaGetSymbolAddress(&sp, g_scr);
  p.s = (Scratch*)sp;
  CUtensorMap mx, mw1, mw2, mo;
  {
    const cuuint64_t dims[2] = {448, 2048}, str[1] = {896};
    const cuuint32_t box[2] = {64, 128}, boxo[2] = {64, 16};
    make_map(fn, &mx, p.x, 2, dims, str, box);
    make_map(fn, &mo, d_out, 2, dims, str, boxo);
  }
  {
    const cuuint64_t dims[3] = {64, 448, 28}, str[2] = {3584, 128};
    const cuuint32_t box[3] = {64, 64, 4};
    make_map(fn, &mw1, p.w1, 3, dims, str, box);
  }
  {
    const cuuint64_t dims[2] = {448, 1792}, str[1] = {896};
    const cuuint32_t box[2] = {64, 256};
    make_map(fn, &mw2, p.w2, 2, dims, str, box);
  }
  cudaFuncSetAttribute(fused_kernel, cudaFuncAttributeMaxDynamicSharedMemorySize, SMEM_BYTES);
  fused_kernel<<<NCTA, 384, SMEM_BYTES>>>(p, mx, mw1, mw2, mo);
}
```

```cpp
#include <cuda_runtime.h>
#include <cuda_bf16.h>
#include <cuda_fp16.h>
#include <cuda.h>
#include <stdint.h>

namespace {

constexpr int D_ = 448, NST = 256, F_ = 1792;
constexpr int NRK = 7, NMLP = 112, NCTA = 132;
constexpr int SPIN_MAX = 1 << 20, RETRY_MAX = 512;

struct Scratch {
  unsigned cntA, pad0[31], cntT, pad1[31], epoch, pad2[63];
  uint4 ax[2048];
  uint4 bx[7 * 512];
  uint4 tbl[112 * 329];
  uint4 xnT[224 * 512];
  uint4 s2[16 * 224 * 32];
  uint4 part[16 * 7 * 6 * 1024];
};
__device__ Scratch g_scr;
#define TSTAMP(i)
#define TSINIT()
#define TSDUMP()
extern __shared__ __align__(1024) uint8_t smem_raw[];

constexpr int TBL_SC = 5248, TBL = 5264;
constexpr int TBL_C1 = 2624;
constexpr int SIG = 19584;
constexpr int SIG_U = 0, U_LBO = 656, SIG_V3 = 6272, SIG_V5 = 10368, SIG_V7 = 13440, SIG_V9 = 15488, SIG_V2 = 17536;
constexpr int Y2B = 6528, Y3B = 4352;
constexpr int KSTG = 14 * 2048;
constexpr int OFF_W = 0, OFF_X = 98304, OFF_A = 147456, OFF_B = OFF_A + 2 * SIG + Y3B, OFF_T = OFF_B + 16896;
constexpr int OFF_M = OFF_T + 15872;
constexpr int B_AX = Y2B, B_BX = B_AX + 2048;
constexpr int M_BAR = 0, M_REL = 128, M_EP = 192, M_CSR = 256, M_LT = 1280, M_MX = 1536, M_END = 1664;
constexpr int SMEM_BYTES = OFF_M + M_END + 384;
constexpr int S_WORK = 63232, S_WGB = 2 * SIG + Y2B + Y3B;
static_assert(OFF_A + 2 * KSTG <= OFF_T && S_WORK + 3 * S_WGB <= OFF_M && SMEM_BYTES <= 232448, "smem");

struct Params {
  const __nv_bfloat16 *x, *a_re, *a_im, *b_re, *b_im, *c_re, *c_im, *log_dt, *dskip, *w1, *b1, *w2, *b2;
  Scratch* s;
};

__device__ __forceinline__ int opaque(int x) { int v; asm volatile("mov.u32 %0, %1;" : "=r"(v) : "r"(x)); return v; }
__device__ __forceinline__ int rd_bid() { int v; asm volatile("mov.u32 %0, %%ctaid.x;" : "=r"(v)); return v; }
__device__ __forceinline__ uint32_t smem_u32(const void* p) { return (uint32_t)__cvta_generic_to_shared(p); }
__device__ __forceinline__ void mbar_init(uint32_t bar, int cnt) { asm volatile("mbarrier.init.shared::cta.b64 [%0], %1;" ::"r"(bar), "r"(cnt)); }
__device__ __forceinline__ void mbar_expect(uint32_t bar, uint32_t bytes) {
  asm volatile("mbarrier.arrive.expect_tx.shared::cta.b64 _, [%0], %1;" ::"r"(bar), "r"(bytes) : "memory");
}
__device__ __forceinline__ void mbar_wait(uint32_t bar, uint32_t parity) {
  uint32_t done = 0;
#pragma unroll 1
  for (int it = 0; it < SPIN_MAX; it++) {
    asm volatile("{.reg .pred p; mbarrier.try_wait.parity.shared::cta.b64 p, [%1], %2; selp.u32 %0,1,0,p;}"
                 : "=r"(done) : "r"(bar), "r"(parity) : "memory");
    if (done) break;
  }
}
__device__ __forceinline__ void tma_2d(uint32_t dst, const CUtensorMap* m, int c0, int c1, uint32_t bar) {
  asm volatile("cp.async.bulk.tensor.2d.shared::cluster.global.mbarrier::complete_tx::bytes [%0], [%1, {%3, %4}], [%2];"
               ::"r"(dst), "l"(m), "r"(bar), "r"(c0), "r"(c1) : "memory");
}
__device__ __forceinline__ void tma_3d(uint32_t dst, const CUtensorMap* m, int c0, int c1, int c2, uint32_t bar) {
  asm volatile("cp.async.bulk.tensor.3d.shared::cluster.global.mbarrier::complete_tx::bytes [%0], [%1, {%3, %4, %5}], [%2];"
               ::"r"(dst), "l"(m), "r"(bar), "r"(c0), "r"(c1), "r"(c2) : "memory");
}
__device__ __forceinline__ void tma_store_2d(const CUtensorMap* m, uint32_t src, int c0, int c1) {
  asm volatile("cp.async.bulk.tensor.2d.global.shared::cta.bulk_group [%0, {%2, %3}], [%1];"
               ::"l"(m), "r"(src), "r"(c0), "r"(c1) : "memory");
}
__device__ __forceinline__ void bulk_commit() { asm volatile("cp.async.bulk.commit_group;" ::: "memory"); }
__device__ __forceinline__ void bulk_wait0_read() { asm volatile("cp.async.bulk.wait_group.read 0;" ::: "memory"); }
__device__ __forceinline__ void fence_async() { asm volatile("fence.proxy.async.shared::cta;" ::: "memory"); }
__device__ __forceinline__ void bar_sync(int id, int n) { asm volatile("bar.sync %0, %1;" ::"r"(id), "r"(n) : "memory"); }
__device__ __forceinline__ void bar_arrive(int id, int n) { asm volatile("bar.arrive %0, %1;" ::"r"(id), "r"(n) : "memory"); }
__device__ __forceinline__ void wg_fence() { asm volatile("wgmma.fence.sync.aligned;" ::: "memory"); }
__device__ __forceinline__ void wg_commit() { asm volatile("wgmma.commit_group.sync.aligned;" ::: "memory"); }
template <int N> __device__ __forceinline__ void wg_wait() { asm volatile("wgmma.wait_group.sync.aligned %0;" ::"n"(N) : "memory"); }
template <int N> __device__ __forceinline__ void fence_regs(float* d) {
#pragma unroll
  for (int i = 0; i < N; i++) asm volatile("" : "+f"(d[i])::"memory");
}
__device__ __forceinline__ uint64_t mkdesc(uint32_t addr, uint32_t lbo, uint32_t sbo, uint32_t sw) {
  return (uint64_t)((addr & 0x3FFFF) >> 4) | ((uint64_t)(lbo >> 4) << 16) | ((uint64_t)(sbo >> 4) << 32) | ((uint64_t)sw << 62);
}
__device__ __forceinline__ uint32_t lds32(uint32_t a) { uint32_t v; asm volatile("ld.shared.b32 %0, [%1];" : "=r"(v) : "r"(a) : "memory"); return v; }
__device__ __forceinline__ float lds32f(uint32_t a) { float v; asm volatile("ld.shared.f32 %0, [%1];" : "=f"(v) : "r"(a) : "memory"); return v; }
__device__ __forceinline__ float2 lds64f(uint32_t a) { float2 v; asm volatile("ld.shared.v2.f32 {%0,%1}, [%2];" : "=f"(v.x), "=f"(v.y) : "r"(a) : "memory"); return v; }
__device__ __forceinline__ uint4 lds128(uint32_t a) {
  uint4 v; asm volatile("ld.shared.v4.b32 {%0,%1,%2,%3}, [%4];" : "=r"(v.x), "=r"(v.y), "=r"(v.z), "=r"(v.w) : "r"(a) : "memory"); return v;
}
__device__ __forceinline__ void sts16(uint32_t a, uint16_t v) { asm volatile("st.shared.b16 [%0], %1;" ::"r"(a), "h"(v) : "memory"); }
__device__ __forceinline__ void sts32f(uint32_t a, float v) { asm volatile("st.shared.f32 [%0], %1;" ::"r"(a), "f"(v) : "memory"); }
__device__ __forceinline__ void sts64f(uint32_t a, float x, float y) { asm volatile("st.shared.v2.f32 [%0], {%1,%2};" ::"r"(a), "f"(x), "f"(y) : "memory"); }
__device__ __forceinline__ void sts128(uint32_t a, uint32_t x, uint32_t y, uint32_t z, uint32_t w) {
  asm volatile("st.shared.v4.b32 [%0], {%1,%2,%3,%4};" ::"r"(a), "r"(x), "r"(y), "r"(z), "r"(w) : "memory");
}
__device__ __forceinline__ void ldsm4(uint32_t a, uint32_t& r0, uint32_t& r1, uint32_t& r2, uint32_t& r3) {
  asm volatile("ldmatrix.sync.aligned.m8n8.x4.shared.b16 {%0,%1,%2,%3}, [%4];" : "=r"(r0), "=r"(r1), "=r"(r2), "=r"(r3) : "r"(a) : "memory");
}
__device__ __forceinline__ void ldsm4t(uint32_t a, uint32_t& r0, uint32_t& r1, uint32_t& r2, uint32_t& r3) {
  asm volatile("ldmatrix.sync.aligned.m8n8.x4.trans.shared.b16 {%0,%1,%2,%3}, [%4];" : "=r"(r0), "=r"(r1), "=r"(r2), "=r"(r3) : "r"(a) : "memory");
}
__device__ __forceinline__ void stsm4(uint32_t a, uint32_t r0, uint32_t r1, uint32_t r2, uint32_t r3) {
  asm volatile("stmatrix.sync.aligned.m8n8.x4.shared.b16 [%0], {%1,%2,%3,%4};" ::"r"(a), "r"(r0), "r"(r1), "r"(r2), "r"(r3) : "memory");
}
__device__ __forceinline__ void mma_bf16(float* c, uint32_t a0, uint32_t a1, uint32_t a2, uint32_t a3, uint32_t b0, uint32_t b1) {
  asm("mma.sync.aligned.m16n8k16.row.col.f32.bf16.bf16.f32 {%0,%1,%2,%3},{%4,%5,%6,%7},{%8,%9},{%0,%1,%2,%3};"
      : "+f"(c[0]), "+f"(c[1]), "+f"(c[2]), "+f"(c[3]) : "r"(a0), "r"(a1), "r"(a2), "r"(a3), "r"(b0), "r"(b1));
}
__device__ __forceinline__ uint4 ld_relaxed4(const void* p) {
  uint4 v; asm volatile("ld.relaxed.gpu.global.v4.b32 {%0,%1,%2,%3}, [%4];" : "=r"(v.x), "=r"(v.y), "=r"(v.z), "=r"(v.w) : "l"(p) : "memory"); return v;
}
__device__ __forceinline__ uint4 ld_2x64(const void* p) {
  uint4 v;
  asm volatile("{.reg .b64 a, c; ld.relaxed.gpu.global.v2.b64 {a, c}, [%4]; mov.b64 {%0,%1}, a; mov.b64 {%2,%3}, c;}"
               : "=r"(v.x), "=r"(v.y), "=r"(v.z), "=r"(v.w) : "l"(p) : "memory");
  return v;
}
__device__ __forceinline__ void st_relaxed2(void* p, uint32_t x, uint32_t y) {
  asm volatile("st.relaxed.gpu.global.v2.b32 [%0], {%1,%2};" ::"l"(p), "r"(x), "r"(y) : "memory");
}
__device__ __forceinline__ uint4 ld_b128(const void* p) {
  uint4 v;
  asm volatile("{.reg .b128 t; .reg .b64 a, c; ld.relaxed.gpu.global.b128 t, [%4]; mov.b128 {a, c}, t; mov.b64 {%0,%1}, a; mov.b64 {%2,%3}, c;}"
               : "=r"(v.x), "=r"(v.y), "=r"(v.z), "=r"(v.w) : "l"(p) : "memory");
  return v;
}
__device__ __forceinline__ void st_b128(void* p, uint32_t tag, uint32_t x, uint32_t y, uint32_t z, uint32_t w) {
  asm volatile("{.reg .b128 t; .reg .b64 a, c; mov.b64 a, {%1,%2}; mov.b64 c, {%3,%4}; mov.b128 t, {a, c}; st.relaxed.gpu.global.b128 [%0], t;}"
               ::"l"(p), "r"((x & ~1u) | tag), "r"(y), "r"(z), "r"(w) : "memory");
}
__device__ __forceinline__ unsigned ld_relaxed1(const unsigned* p) {
  unsigned v; asm volatile("ld.relaxed.gpu.global.u32 %0, [%1];" : "=r"(v) : "l"(p) : "memory"); return v;
}
__device__ __forceinline__ void red_relaxed(unsigned* p) {
  asm volatile("red.relaxed.gpu.global.add.u32 [%0], 1;" ::"l"(p) : "memory");
}
__device__ __forceinline__ void wait_count(const unsigned* p, unsigned target) {
#pragma unroll 1
  for (int it = 0; it < SPIN_MAX; it++) {
    if ((int)(ld_relaxed1(p) - target) >= 0) break;
    __nanosleep(40);
  }
  asm volatile("fence.acq_rel.gpu;" ::: "memory");
}
__device__ __forceinline__ uint32_t pack_h2(float lo, float hi) { uint32_t r; asm("cvt.rn.f16x2.f32 %0, %1, %2;" : "=r"(r) : "f"(hi), "f"(lo)); return r; }
__device__ __forceinline__ uint32_t pack_bf2(float lo, float hi) { uint32_t r; asm("cvt.rn.bf16x2.f32 %0, %1, %2;" : "=r"(r) : "f"(hi), "f"(lo)); return r; }
__device__ __forceinline__ float bf_lo(uint32_t w) { return __uint_as_float(w << 16); }
__device__ __forceinline__ float bf_hi(uint32_t w) { return __uint_as_float(w & 0xffff0000u); }
__device__ __forceinline__ float rbf(float v) { return __bfloat162float(__float2bfloat16_rn(v)); }
__device__ __forceinline__ float2 h2f(uint32_t w) { return __half22float2(*reinterpret_cast<__half2*>(&w)); }
__device__ __forceinline__ float ex2f(float v) { float r; asm("ex2.approx.ftz.f32 %0, %1;" : "=f"(r) : "f"(v)); return r; }
__device__ __forceinline__ float rcpf_(float v) { float r; asm("rcp.approx.f32 %0, %1;" : "=f"(r) : "f"(v)); return r; }
__device__ __forceinline__ float sqrtf_(float v) { float r; asm("sqrt.approx.f32 %0, %1;" : "=f"(r) : "f"(v)); return r; }
__device__ __forceinline__ float tanhf_(float v) { float r; asm volatile("tanh.approx.f32 %0, %1;" : "=f"(r) : "f"(v)); return r; }

__device__ __forceinline__ void wg_ss_bf16_n256(float* d, uint64_t da, uint64_t db, int sc) {
  asm volatile("{.reg .pred p; setp.ne.b32 p, %130, 0;\n"
    "wgmma.mma_async.sync.aligned.m64n256k16.f32.bf16.bf16 {%0, %1, %2, %3, %4, %5, %6, %7, %8, %9, %10, %11, %12, %13, %14, %15, %16, %17, %18, %19, %20, %21, %22, %23, %24, %25, %26, %27, %28, %29, %30, %31, %32, %33, %34, %35, %36, %37, %38, %39, %40, %41, %42, %43, %44, %45, %46, %47, %48, %49, %50, %51, %52, %53, %54, %55, %56, %57, %58, %59, %60, %61, %62, %63, %64, %65, %66, %67, %68, %69, %70, %71, %72, %73, %74, %75, %76, %77, %78, %79, %80, %81, %82, %83, %84, %85, %86, %87, %88, %89, %90, %91, %92, %93, %94, %95, %96, %97, %98, %99, %100, %101, %102, %103, %104, %105, %106, %107, %108, %109, %110, %111, %112, %113, %114, %115, %116, %117, %118, %119, %120, %121, %122, %123, %124, %125, %126, %127}, %128, %129, p, 1, 1, 0, 1;}\n"
    : "+f"(d[0]), "+f"(d[1]), "+f"(d[2]), "+f"(d[3]), "+f"(d[4]), "+f"(d[5]), "+f"(d[6]), "+f"(d[7]), "+f"(d[8]), "+f"(d[9]), "+f"(d[10]), "+f"(d[11]), "+f"(d[12]), "+f"(d[13]), "+f"(d[14]), "+f"(d[15]), "+f"(d[16]), "+f"(d[17]), "+f"(d[18]), "+f"(d[19]), "+f"(d[20]), "+f"(d[21]), "+f"(d[22]), "+f"(d[23]), "+f"(d[24]), "+f"(d[25]), "+f"(d[26]), "+f"(d[27]), "+f"(d[28]), "+f"(d[29]), "+f"(d[30]), "+f"(d[31]), "+f"(d[32]), "+f"(d[33]), "+f"(d[34]), "+f"(d[35]), "+f"(d[36]), "+f"(d[37]), "+f"(d[38]), "+f"(d[39]), "+f"(d[40]), "+f"(d[41]), "+f"(d[42]), "+f"(d[43]), "+f"(d[44]), "+f"(d[45]), "+f"(d[46]), "+f"(d[47]), "+f"(d[48]), "+f"(d[49]), "+f"(d[50]), "+f"(d[51]), "+f"(d[52]), "+f"(d[53]), "+f"(d[54]), "+f"(d[55]), "+f"(d[56]), "+f"(d[57]), "+f"(d[58]), "+f"(d[59]), "+f"(d[60]), "+f"(d[61]), "+f"(d[62]), "+f"(d[63]), "+f"(d[64]), "+f"(d[65]), "+f"(d[66]), "+f"(d[67]), "+f"(d[68]), "+f"(d[69]), "+f"(d[70]), "+f"(d[71]), "+f"(d[72]), "+f"(d[73]), "+f"(d[74]), "+f"(d[75]), "+f"(d[76]), "+f"(d[77]), "+f"(d[78]), "+f"(d[79]), "+f"(d[80]), "+f"(d[81]), "+f"(d[82]), "+f"(d[83]), "+f"(d[84]), "+f"(d[85]), "+f"(d[86]), "+f"(d[87]), "+f"(d[88]), "+f"(d[89]), "+f"(d[90]), "+f"(d[91]), "+f"(d[92]), "+f"(d[93]), "+f"(d[94]), "+f"(d[95]), "+f"(d[96]), "+f"(d[97]), "+f"(d[98]), "+f"(d[99]), "+f"(d[100]), "+f"(d[101]), "+f"(d[102]), "+f"(d[103]), "+f"(d[104]), "+f"(d[105]), "+f"(d[106]), "+f"(d[107]), "+f"(d[108]), "+f"(d[109]), "+f"(d[110]), "+f"(d[111]), "+f"(d[112]), "+f"(d[113]), "+f"(d[114]), "+f"(d[115]), "+f"(d[116]), "+f"(d[117]), "+f"(d[118]), "+f"(d[119]), "+f"(d[120]), "+f"(d[121]), "+f"(d[122]), "+f"(d[123]), "+f"(d[124]), "+f"(d[125]), "+f"(d[126]), "+f"(d[127])
    : "l"(da), "l"(db), "r"(sc));
}

__device__ __forceinline__ void wg_ss_bf16_n256k(float* d, uint64_t da, uint64_t db, int sc) {
  asm volatile("{.reg .pred p; setp.ne.b32 p, %130, 0;\n"
    "wgmma.mma_async.sync.aligned.m64n256k16.f32.bf16.bf16 {%0, %1, %2, %3, %4, %5, %6, %7, %8, %9, %10, %11, %12, %13, %14, %15, %16, %17, %18, %19, %20, %21, %22, %23, %24, %25, %26, %27, %28, %29, %30, %31, %32, %33, %34, %35, %36, %37, %38, %39, %40, %41, %42, %43, %44, %45, %46, %47, %48, %49, %50, %51, %52, %53, %54, %55, %56, %57, %58, %59, %60, %61, %62, %63, %64, %65, %66, %67, %68, %69, %70, %71, %72, %73, %74, %75, %76, %77, %78, %79, %80, %81, %82, %83, %84, %85, %86, %87, %88, %89, %90, %91, %92, %93, %94, %95, %96, %97, %98, %99, %100, %101, %102, %103, %104, %105, %106, %107, %108, %109, %110, %111, %112, %113, %114, %115, %116, %117, %118, %119, %120, %121, %122, %123, %124, %125, %126, %127}, %128, %129, p, 1, 1, 0, 0;}\n"
    : "+f"(d[0]), "+f"(d[1]), "+f"(d[2]), "+f"(d[3]), "+f"(d[4]), "+f"(d[5]), "+f"(d[6]), "+f"(d[7]), "+f"(d[8]), "+f"(d[9]), "+f"(d[10]), "+f"(d[11]), "+f"(d[12]), "+f"(d[13]), "+f"(d[14]), "+f"(d[15]), "+f"(d[16]), "+f"(d[17]), "+f"(d[18]), "+f"(d[19]), "+f"(d[20]), "+f"(d[21]), "+f"(d[22]), "+f"(d[23]), "+f"(d[24]), "+f"(d[25]), "+f"(d[26]), "+f"(d[27]), "+f"(d[28]), "+f"(d[29]), "+f"(d[30]), "+f"(d[31]), "+f"(d[32]), "+f"(d[33]), "+f"(d[34]), "+f"(d[35]), "+f"(d[36]), "+f"(d[37]), "+f"(d[38]), "+f"(d[39]), "+f"(d[40]), "+f"(d[41]), "+f"(d[42]), "+f"(d[43]), "+f"(d[44]), "+f"(d[45]), "+f"(d[46]), "+f"(d[47]), "+f"(d[48]), "+f"(d[49]), "+f"(d[50]), "+f"(d[51]), "+f"(d[52]), "+f"(d[53]), "+f"(d[54]), "+f"(d[55]), "+f"(d[56]), "+f"(d[57]), "+f"(d[58]), "+f"(d[59]), "+f"(d[60]), "+f"(d[61]), "+f"(d[62]), "+f"(d[63]), "+f"(d[64]), "+f"(d[65]), "+f"(d[66]), "+f"(d[67]), "+f"(d[68]), "+f"(d[69]), "+f"(d[70]), "+f"(d[71]), "+f"(d[72]), "+f"(d[73]), "+f"(d[74]), "+f"(d[75]), "+f"(d[76]), "+f"(d[77]), "+f"(d[78]), "+f"(d[79]), "+f"(d[80]), "+f"(d[81]), "+f"(d[82]), "+f"(d[83]), "+f"(d[84]), "+f"(d[85]), "+f"(d[86]), "+f"(d[87]), "+f"(d[88]), "+f"(d[89]), "+f"(d[90]), "+f"(d[91]), "+f"(d[92]), "+f"(d[93]), "+f"(d[94]), "+f"(d[95]), "+f"(d[96]), "+f"(d[97]), "+f"(d[98]), "+f"(d[99]), "+f"(d[100]), "+f"(d[101]), "+f"(d[102]), "+f"(d[103]), "+f"(d[104]), "+f"(d[105]), "+f"(d[106]), "+f"(d[107]), "+f"(d[108]), "+f"(d[109]), "+f"(d[110]), "+f"(d[111]), "+f"(d[112]), "+f"(d[113]), "+f"(d[114]), "+f"(d[115]), "+f"(d[116]), "+f"(d[117]), "+f"(d[118]), "+f"(d[119]), "+f"(d[120]), "+f"(d[121]), "+f"(d[122]), "+f"(d[123]), "+f"(d[124]), "+f"(d[125]), "+f"(d[126]), "+f"(d[127])
    : "l"(da), "l"(db), "r"(sc));
}

__device__ __forceinline__ void wg_rs_bf16_n64(float* d, uint32_t a0, uint32_t a1, uint32_t a2, uint32_t a3, uint64_t db, int sc) {
  asm volatile("{.reg .pred p; setp.ne.b32 p, %37, 0;\n"
    "wgmma.mma_async.sync.aligned.m64n64k16.f32.bf16.bf16 {%0, %1, %2, %3, %4, %5, %6, %7, %8, %9, %10, %11, %12, %13, %14, %15, %16, %17, %18, %19, %20, %21, %22, %23, %24, %25, %26, %27, %28, %29, %30, %31}, {%32,%33,%34,%35}, %36, p, 1, 1, 1;}\n"
    : "+f"(d[0]), "+f"(d[1]), "+f"(d[2]), "+f"(d[3]), "+f"(d[4]), "+f"(d[5]), "+f"(d[6]), "+f"(d[7]), "+f"(d[8]), "+f"(d[9]), "+f"(d[10]), "+f"(d[11]), "+f"(d[12]), "+f"(d[13]), "+f"(d[14]), "+f"(d[15]), "+f"(d[16]), "+f"(d[17]), "+f"(d[18]), "+f"(d[19]), "+f"(d[20]), "+f"(d[21]), "+f"(d[22]), "+f"(d[23]), "+f"(d[24]), "+f"(d[25]), "+f"(d[26]), "+f"(d[27]), "+f"(d[28]), "+f"(d[29]), "+f"(d[30]), "+f"(d[31])
    : "r"(a0), "r"(a1), "r"(a2), "r"(a3), "l"(db), "r"(sc));
}

__device__ __forceinline__ void wg_rs_f16_n32k(float* d, uint32_t a0, uint32_t a1, uint32_t a2, uint32_t a3, uint64_t db, int sc) {
  asm volatile("{.reg .pred p; setp.ne.b32 p, %21, 0;\n"
    "wgmma.mma_async.sync.aligned.m64n32k16.f32.f16.f16 {%0, %1, %2, %3, %4, %5, %6, %7, %8, %9, %10, %11, %12, %13, %14, %15}, {%16,%17,%18,%19}, %20, p, 1, 1, 0;}\n"
    : "+f"(d[0]), "+f"(d[1]), "+f"(d[2]), "+f"(d[3]), "+f"(d[4]), "+f"(d[5]), "+f"(d[6]), "+f"(d[7]), "+f"(d[8]), "+f"(d[9]), "+f"(d[10]), "+f"(d[11]), "+f"(d[12]), "+f"(d[13]), "+f"(d[14]), "+f"(d[15])
    : "r"(a0), "r"(a1), "r"(a2), "r"(a3), "l"(db), "r"(sc));
}

__device__ __forceinline__ void wg_rs_f16_n24t(float* d, uint32_t a0, uint32_t a1, uint32_t a2, uint32_t a3, uint64_t db, int sc) {
  asm volatile("{.reg .pred p; setp.ne.b32 p, %17, 0;\n"
    "wgmma.mma_async.sync.aligned.m64n24k16.f32.f16.f16 {%0, %1, %2, %3, %4, %5, %6, %7, %8, %9, %10, %11}, {%12,%13,%14,%15}, %16, p, 1, 1, 1;}\n"
    : "+f"(d[0]), "+f"(d[1]), "+f"(d[2]), "+f"(d[3]), "+f"(d[4]), "+f"(d[5]), "+f"(d[6]), "+f"(d[7]), "+f"(d[8]), "+f"(d[9]), "+f"(d[10]), "+f"(d[11])
    : "r"(a0), "r"(a1), "r"(a2), "r"(a3), "l"(db), "r"(sc));
}

__device__ __forceinline__ void wg_rs_f16_n16t(float* d, uint32_t a0, uint32_t a1, uint32_t a2, uint32_t a3, uint64_t db, int sc) {
  asm volatile("{.reg .pred p; setp.ne.b32 p, %13, 0;\n"
    "wgmma.mma_async.sync.aligned.m64n16k16.f32.f16.f16 {%0, %1, %2, %3, %4, %5, %6, %7}, {%8,%9,%10,%11}, %12, p, 1, 1, 1;}\n"
    : "+f"(d[0]), "+f"(d[1]), "+f"(d[2]), "+f"(d[3]), "+f"(d[4]), "+f"(d[5]), "+f"(d[6]), "+f"(d[7])
    : "r"(a0), "r"(a1), "r"(a2), "r"(a3), "l"(db), "r"(sc));
}

__device__ __forceinline__ void wg_ss_f16_n48t(float* d, uint64_t da, uint64_t db, int sc) {
  asm volatile("{.reg .pred p; setp.ne.b32 p, %26, 0;\n"
    "wgmma.mma_async.sync.aligned.m64n48k16.f32.f16.f16 {%0, %1, %2, %3, %4, %5, %6, %7, %8, %9, %10, %11, %12, %13, %14, %15, %16, %17, %18, %19, %20, %21, %22, %23}, %24, %25, p, 1, 1, 1, 1;}\n"
    : "+f"(d[0]), "+f"(d[1]), "+f"(d[2]), "+f"(d[3]), "+f"(d[4]), "+f"(d[5]), "+f"(d[6]), "+f"(d[7]), "+f"(d[8]), "+f"(d[9]), "+f"(d[10]), "+f"(d[11]), "+f"(d[12]), "+f"(d[13]), "+f"(d[14]), "+f"(d[15]), "+f"(d[16]), "+f"(d[17]), "+f"(d[18]), "+f"(d[19]), "+f"(d[20]), "+f"(d[21]), "+f"(d[22]), "+f"(d[23])
    : "l"(da), "l"(db), "r"(sc));
}

struct cf { float x, y; };
__device__ __forceinline__ cf cmul(cf a, cf b) { cf r; r.x = fmaf(a.x, b.x, -a.y * b.y); r.y = fmaf(a.x, b.y, a.y * b.x); return r; }
__device__ __forceinline__ cf zpow(float rho2, float phi, float e) {
  const float m = ex2f(rho2 * e), ang = phi * e;
  cf r; r.x = m * __cosf(ang); r.y = m * __sinf(ang); return r;
}
__device__ __forceinline__ __half2 H2(uint32_t v) { return *reinterpret_cast<__half2*>(&v); }
__device__ __forceinline__ uint32_t U32(__half2 v) { return *reinterpret_cast<uint32_t*>(&v); }
struct h2c { __half2 x, y; };
template <bool CONJ>
__device__ __forceinline__ void hprod2(uint32_t re, uint32_t im, h2c r, uint32_t& ore, uint32_t& oim) {
  if (CONJ) {
    ore = U32(__hfma2(H2(re), r.x, __hmul2(H2(im), r.y)));
    oim = U32(__hfma2(H2(im), r.x, __hneg2(__hmul2(H2(re), r.y))));
  } else {
    ore = U32(__hfma2(H2(re), r.x, __hneg2(__hmul2(H2(im), r.y))));
    oim = U32(__hfma2(H2(re), r.y, __hmul2(H2(im), r.x)));
  }
}
__device__ __forceinline__ cf csq(cf a) { cf r; r.x = fmaf(a.x, a.x, -a.y * a.y); r.y = (a.x + a.x) * a.y; return r; }
__device__ __forceinline__ cf cmulc(cf a, cf b) { cf r; r.x = fmaf(a.x, b.x, a.y * b.y); r.y = fmaf(a.y, b.x, -a.x * b.y); return r; }
__device__ __forceinline__ h2c pk(cf a) { h2c r; r.x = H2(pack_h2(a.x, a.x)); r.y = H2(pack_h2(a.y, a.y)); return r; }
__device__ __forceinline__ uint32_t ldg32(const void* p, int o) { uint32_t v; asm volatile("ld.global.nc.b32 %0, [%1];" : "=r"(v) : "l"((const char*)p + o)); return v; }
__device__ __forceinline__ uint32_t hadd2u(uint32_t a, uint32_t b) { return U32(__hadd2(H2(a), H2(b))); }

struct KgIn { uint32_t cur[6], nxt[6], ldt, dk; bool odd; };
__device__ __forceinline__ float pow2_floor(float v) { return __uint_as_float(__float_as_uint(fminf(fmaxf(v, 1e-30f), 1e30f)) & 0x7f800000u); }
template <class Mid0, class Mid1>
__device__ __forceinline__ void kgen_wg(KgIn& k, int nw, uint32_t stg, uint32_t tbl, uint32_t mxa, int w, int lane, int barid, Mid0 mid0, Mid1 mid1) {
  float dl, dt, inv_sc;
  {
    const uint32_t M = 0x7fff7fffu;
    uint32_t mx[2];
#pragma unroll
    for (int i = 0; i < 2; i++) {
      const uint32_t m = __vmaxu2(__vmaxu2(k.cur[2 + 2 * i] & M, k.cur[3 + 2 * i] & M), __vmaxu2(k.nxt[2 + 2 * i] & M, k.nxt[3 + 2 * i] & M));
      mx[i] = __reduce_max_sync(0xffffffffu, max(m << 16, m & 0xffff0000u));
    }
    if (lane == 0) sts32f(mxa + w * 4, __uint_as_float(mx[0]) * __uint_as_float(mx[1]));
    dt = rbf(ex2f((k.odd ? bf_hi(k.ldt) : bf_lo(k.ldt)) * 1.4426950408889634f));
    const float dsk = (k.odd ? bf_hi(k.dk) : bf_lo(k.dk)) * rcpf_(dt);
    bar_sync(barid, 128);
    const float2 m0 = lds64f(mxa + (w & 2) * 4), m1 = lds64f(mxa + (nw == 1 ? (w & 2) ^ 2 : (w & 2)) * 4);
    const float sc = pow2_floor(fmaxf(0.125f * fmaxf(fmaxf(m0.x, m0.y), fmaxf(m1.x, m1.y)), fabsf(dsk) * (1.f / 4096.f)));
    inv_sc = rcpf_(sc);
    if (lane == 0) sts64f(tbl + TBL_SC + 8, dt * sc, dsk * inv_sc);
    dl = dt * 1.4426950408889634f;
  }
  const uint32_t sa = stg + (w >> 1) * 8192 + (32 * (w & 1) + lane) * 16, sc_ = sa + 16384 - (w >> 1) * 2048;
  const uint64_t dA = mkdesc(stg, 128, 2048, 0), dB = mkdesc(stg + 16384, 128, 2048, 0);
  float acc[24];
#pragma unroll 1
  for (int it = 0; it < 2 * nw; it++) {
    const uint32_t sel = (it & 1) ? 0x3244u : 0x1044u;
    float v[6];
#pragma unroll
    for (int i = 0; i < 6; i++) { v[i] = __uint_as_float(__byte_perm(k.cur[i], 0, sel)); if (it == 1) k.cur[i] = k.nxt[i]; }
    const float rho2 = v[0] * dl, phi = v[1] * dt;
    const cf bb = {v[2] * inv_sc, v[3] * -inv_sc}, cc = {v[4], v[5]};
    const cf X0 = cmulc(bb, cc);
    const cf z1 = zpow(rho2, phi, 1.f), z64 = zpow(rho2, phi, 64.f);
    const cf z2 = csq(z1), z3 = cmul(z2, z1), z4 = csq(z2), z8 = csq(z4), z16 = csq(z8), z24 = cmul(z16, z8), z32 = csq(z16);
    const cf z128 = csq(z64), y1 = csq(z128), y2 = csq(y1), y3 = cmul(y2, y1), y4 = csq(y2);
    const cf X4 = cmulc(X0, z4), W4 = cmulc(X0, y4), W8 = cmulc(W4, y4), W5 = cmulc(W4, y1);
    uint32_t re[4], im[4], r2[4], i2[4];
    re[0] = pack_h2(X0.x, X4.x); im[0] = pack_h2(X0.y, X4.y);
    hprod2<true>(re[0], im[0], pk(z1), re[1], im[1]);
    hprod2<true>(re[0], im[0], pk(z2), re[2], im[2]);
    hprod2<true>(re[0], im[0], pk(z3), re[3], im[3]);
    const h2c hy1 = pk(y1), hy2 = pk(y2);
    hprod2<true>(re[0], im[0], hy1, r2[0], i2[0]);
    hprod2<true>(re[2], im[2], hy1, r2[1], i2[1]);
    hprod2<true>(re[0], im[0], hy2, r2[2], i2[2]);
    hprod2<true>(re[0], im[0], pk(y3), r2[3], i2[3]);
    wg_wait<0>();
    bar_sync(barid, 128);
    sts128(sc_, re[0], re[1], re[2], re[3]);
    sts128(sc_ + 1024, im[0], im[1], im[2], im[3]);
    sts128(sc_ + 2048, r2[0], r2[1], r2[2], r2[3]);
    sts128(sc_ + 3072, i2[0], i2[1], i2[2], i2[3]);
    re[0] = pack_h2(W4.x, W5.x); im[0] = pack_h2(W4.y, W5.y);
    hprod2<true>(re[0], im[0], hy2, re[1], im[1]);
    sts128(sc_ + 4096, re[0], re[1], pack_h2(W8.x, 0.f), 0u);
    sts128(sc_ + 5120, im[0], im[1], pack_h2(W8.y, 0.f), 0u);
    re[0] = pack_h2(1.f, z32.x); im[0] = pack_h2(0.f, z32.y);
    hprod2<false>(re[0], im[0], pk(z8), re[1], im[1]);
    hprod2<false>(re[0], im[0], pk(z16), re[2], im[2]);
    hprod2<false>(re[0], im[0], pk(z24), re[3], im[3]);
    const h2c h64 = pk(z64), h128 = pk(z128);
#pragma unroll
    for (int j = 0; j < 4; j++) hprod2<false>(re[j], im[j], h64, r2[j], i2[j]);
    sts128(sa, re[0], re[1], re[2], re[3]);
    sts128(sa + 1024, im[0], im[1], im[2], im[3]);
    sts128(sa + 2048, r2[0], r2[1], r2[2], r2[3]);
    sts128(sa + 3072, i2[0], i2[1], i2[2], i2[3]);
    uint32_t r3[4], i3[4], r4[4], i4[4];
#pragma unroll
    for (int j = 0; j < 4; j++) { hprod2<false>(re[j], im[j], h128, r3[j], i3[j]); hprod2<false>(r2[j], i2[j], h128, r4[j], i4[j]); }
    sts128(sa + 4096, r3[0], r3[1], r3[2], r3[3]);
    sts128(sa + 5120, i3[0], i3[1], i3[2], i3[3]);
    sts128(sa + 6144, r4[0], r4[1], r4[2], r4[3]);
    sts128(sa + 7168, i4[0], i4[1], i4[2], i4[3]);
    fence_async();
    bar_sync(barid, 128);
    wg_fence();
#pragma unroll
    for (int ks = 0; ks < 8; ks++) wg_ss_f16_n48t(acc, dA + 16 * ks, dB + 16 * ks, 1);
    wg_commit();
    if (it == 0) mid0();
    if (it == 1) mid1();
  }
  wg_wait<0>();
  fence_regs<24>(acc);
  bar_sync(barid, 128);
#pragma unroll
  for (int h = 0; h < 2; h++)
#pragma unroll
    for (int nt = 0; nt < 3; nt++) {
      const int i = 4 * nt + 2 * h;
      sts64f(stg + (w * 2 + h) * 768 + nt * 256 + lane * 8, (w & 2) ? acc[12 + i] : acc[i], (w & 2) ? acc[13 + i] : acc[1 + i]);
    }
}

__device__ __forceinline__ void tput(uint32_t tbl, int X, uint32_t h) {
  sts16(tbl + 2 * (1296 - X), (uint16_t)h);
  sts16(tbl + TBL_C1 + 2 * (1297 - X), (uint16_t)h);
}
__device__ __forceinline__ void ktab_build(uint32_t src, bool two, int q, uint32_t tbl, int lane) {
  const int tq = lane & 3, r = 8 * q + (lane >> 3) + ((lane >> 2) & 1) * 4;
  float v[6];
  src += q * 768 + lane * 8;
#pragma unroll
  for (int nt = 0; nt < 3; nt++) {
    const float2 a = lds64f(src + nt * 256);
    v[2 * nt] = a.x; v[2 * nt + 1] = a.y;
    if (two) { const float2 c = lds64f(src + nt * 256 + 3072); v[2 * nt] += c.x; v[2 * nt + 1] += c.y; }
  }
  const bool first = (r == 0);
  if (first && tq == 0) { v[0] += lds32f(tbl + TBL_SC + 12); sts32f(tbl + TBL_SC, v[4]); }
  const uint32_t h0 = pack_h2(v[0], v[1]), h1 = pack_h2(v[2], v[3]), h2 = pack_h2(v[4], v[5]);
  tput(tbl, 64 + 8 * r + tq, h0);
  tput(tbl, 68 + 8 * r + tq, h0 >> 16);
  const bool lo = tq < 2;
  const int k2 = 32 * (tq - 2) + r;
  const bool sp = first && tq == 2;
  const int Xa = lo ? 320 + 8 * r + 2 * tq : (sp ? 576 : 911 + k2), Xb = lo ? Xa + 4 : 720 + k2;
  tput(tbl, Xa, h1);
  tput(tbl, Xb, h1 >> 16);
  if (tq == 0 || sp) {
    tput(tbl, Xa + 1, h1);
    if (Xa != 320) tput(tbl, Xa - 1, h1);
    const uint32_t hb = sp ? h1 : h1 >> 16, hc = sp ? h2 : h1 >> 16;
    tput(tbl, sp ? 578 : Xb + 1, hb);
    tput(tbl, sp ? 1295 : Xb - 1, hc);
  }
  if (lo) {
    const int X3 = ((r & 1) ? 1104 : 1231) + 32 * tq + (r >> 1);
    tput(tbl, X3 == 1231 ? 975 : X3, h2);
    tput(tbl, X3 + 16, h2 >> 16);
  }
}

__device__ __forceinline__ void sig_windows(uint32_t sig, int t) {
  uint32_t U[20];
#pragma unroll
  for (int c = 0; c < 5; c++) {
    const int kap = 2 * t - 3 + c + 72;
    const uint4 v = lds128(sig + SIG_U + (kap & 7) * U_LBO + (kap >> 3) * 16);
    U[4 * c] = v.x; U[4 * c + 1] = v.y; U[4 * c + 2] = v.z; U[4 * c + 3] = v.w;
  }
  uint32_t O[19], A2[17], A4[17], V2[8], V5[8];
#pragma unroll
  for (int i = 3; i < 19; i++) O[i] = __byte_perm(U[i - 1], U[i], 0x5432);
#pragma unroll
  for (int i = 3; i < 17; i++) A2[i] = hadd2u(U[i], O[i]);
#pragma unroll
  for (int i = 4; i < 17; i++) A4[i] = hadd2u(A2[i], A2[i - 1]);
#pragma unroll
  for (int k = 0; k < 8; k++) { V2[k] = hadd2u(O[11 + k], U[10 + k]); V5[k] = hadd2u(A4[9 + k], U[7 + k]); }
#pragma unroll
  for (int h = 0; h < 2; h++) {
    sts128(sig + SIG_V3 + t * 32 + h * 16, hadd2u(V2[4 * h], O[10 + 4 * h]), hadd2u(V2[4 * h + 1], O[11 + 4 * h]),
           hadd2u(V2[4 * h + 2], O[12 + 4 * h]), hadd2u(V2[4 * h + 3], O[13 + 4 * h]));
    sts128(sig + SIG_V5 + t * 32 + h * 16, V5[4 * h], V5[4 * h + 1], V5[4 * h + 2], V5[4 * h + 3]);
  }
  if (t < 64) {
    uint32_t V7[8], V9[8];
#pragma unroll
    for (int k = 0; k < 8; k++) {
      V7[k] = hadd2u(V5[k], hadd2u(O[10 + k], O[7 + k]));
      V9[k] = hadd2u(hadd2u(A4[6 + k], A4[4 + k]), U[2 + k]);
    }
#pragma unroll
    for (int h = 0; h < 2; h++) {
      sts128(sig + SIG_V7 + h * 1024 + t * 16, V7[4 * h], V7[4 * h + 1], V7[4 * h + 2], V7[4 * h + 3]);
      sts128(sig + SIG_V9 + h * 1024 + t * 16, V9[4 * h], V9[4 * h + 1], V9[4 * h + 2], V9[4 * h + 3]);
      sts128(sig + SIG_V2 + h * 1024 + t * 16, V2[4 * h], V2[4 * h + 1], V2[4 * h + 2], V2[4 * h + 3]);
    }
  }
}

__device__ __forceinline__ void conv_channel(uint32_t tbl, uint32_t sig, uint32_t y2b, uint32_t y3b, float k1024,
                                             int w, int lane, int barid, float* res) {
  const int g = lane >> 2, tq = lane & 3;
  const uint32_t tb = tbl + ((g & 1) ? TBL_C1 + 2 : 0) + 2 * (1296 - (g - 2 * tq)) - 32 * w + 112;
  float a2[12], a3[8];
#pragma unroll
  for (int i = 0; i < 16; i++) res[i] = 0.f;
#pragma unroll
  for (int i = 0; i < 12; i++) a2[i] = 0.f;
#pragma unroll
  for (int q = 0; q < 4; q++) {
    const float2 f = h2f(lds32(sig + SIG_V2 + (q >> 1) * 1024 + (16 * w + 8 * (q & 1) + g) * 16 + tq * 4));
    a3[2 * q] = k1024 * f.x;
    a3[2 * q + 1] = k1024 * f.y;
  }
  const uint32_t sigu = __shfl_sync(0xffffffffu, opaque(sig), 0);
  const uint64_t dU = mkdesc(sigu + SIG_U, U_LBO, 128, 0);
  const uint64_t dV = mkdesc(sigu, 128, 1024, 0);
  fence_regs<16>(res); fence_regs<12>(a2); fence_regs<8>(a3);
  constexpr int LB = 2 * U_LBO / 16;
  uint32_t Rd[43], R2[22], R3[12];
  uint32_t td = tb - 128, t2 = tb - 1440, t3 = tb - 2208;
  uint64_t dd = dU + 9, d2 = dV + (SIG_V3 + 768) / 16, d3 = dV + (SIG_V7 + 768) / 16;
  auto load_group = [&](int gi) {
#pragma unroll
    for (int i = 1; i < 5; i++) Rd[4 * gi + i] = lds32(td - 16 * (4 * gi + i));
    const int e = gi >> 3;
    if ((gi & 7) == 0) { R2[2 * gi + e] = lds32(t2 - 384 * e); R3[gi + e] = lds32(t3 - 256 * e); }
    R2[2 * gi + e + 1] = lds32(t2 - 384 * e - 16 * (2 * (gi & 7) + 1));
    R2[2 * gi + e + 2] = lds32(t2 - 384 * e - 16 * (2 * (gi & 7) + 2));
    if (!(gi & 1)) {
      R3[gi + e + 1] = lds32(t3 - 256 * e - 16 * ((gi & 7) + 1));
      R3[gi + e + 2] = lds32(t3 - 256 * e - 16 * ((gi & 7) + 2));
    }
  };
  auto dense = [&](int n) {
    wg_rs_f16_n32k(res, Rd[2 * n + 1], Rd[2 * n + 2], Rd[2 * n], Rd[2 * n + 1], dd + ((3 - (n & 3)) * LB + 8 - (n >> 2)) - 8, 1);
  };
  Rd[0] = lds32(td);
  load_group(0);
  load_group(1);
#pragma unroll 1
  for (int sg = 0; sg < 2; sg++) {
#pragma unroll
    for (int gi = 0; gi < 8; gi++) {
      wg_fence();
      dense(2 * gi);
      wg_rs_f16_n24t(a2, R2[2 * gi + 1], R2[2 * gi + 2], R2[2 * gi], R2[2 * gi + 1], d2 - (16 * (gi & 3) + 64 * (gi >> 2)), 1);
      dense(2 * gi + 1);
      if (!(gi & 1)) wg_rs_f16_n16t(a3, R3[gi + 1], R3[gi + 2], R3[gi], R3[gi + 1], d3 - 8 * gi, 1);
      wg_commit();
      wg_wait<1>();
      load_group(gi + 2);
    }
#pragma unroll
    for (int i = 0; i < 9; i++) Rd[i] = Rd[32 + i];
#pragma unroll
    for (int i = 0; i < 5; i++) R2[i] = R2[17 + i];
#pragma unroll
    for (int i = 0; i < 3; i++) R3[i] = R3[9 + i];
    td -= 512; t2 -= 384; t3 -= 256;
    dd -= 4; d2 += 256; d3 += 128;
  }
  Rd[9] = lds32(td - 144); Rd[10] = lds32(td - 160);
  wg_fence();
#pragma unroll
  for (int n = 0; n < 5; n++) dense(n);
  wg_commit();
  wg_wait<1>();
  fence_regs<12>(a2); fence_regs<8>(a3);
  bar_sync(barid, 128);
  {
    const uint32_t o2 = y2b + (136 * w + 8 * g + 2 * tq) * 4, o3 = y3b + (272 * w + 16 * g + 2 * tq) * 4;
#pragma unroll
    for (int q = 0; q < 6; q++) sts64f(o2 + (544 * (q >> 1) + 64 * (q & 1)) * 4, a2[2 * q], a2[2 * q + 1]);
#pragma unroll
    for (int q = 0; q < 4; q++) sts64f(o3 + (8 * (q >> 1) + 136 * (q & 1)) * 4, a3[2 * q], a3[2 * q + 1]);
  }
  bar_sync(barid, 128);
  const uint32_t go = (136 * tq + 16 * w + g) * 4;
  float ex[12];
#pragma unroll
  for (int i = 0; i < 12; i++) {
    const int o = 544 * (i >> 2) + 64 * (i & 1) + 8 * ((i >> 1) & 1);
    ex[i] = lds32f(y2b + go + o * 4);
    if (i >= 4) ex[i] += lds32f(y3b + go + (o - 544) * 4);
  }
  wg_wait<0>();
  fence_regs<16>(res);
#pragma unroll
  for (int i = 0; i < 12; i++) res[4 + i] += ex[i];
}

__device__ __forceinline__ void red16x2(float& a, float& c) {
#pragma unroll
  for (int o = 1; o < 16; o <<= 1) { a += __shfl_xor_sync(0xffffffffu, a, o); c += __shfl_xor_sync(0xffffffffu, c, o); }
}
__device__ __forceinline__ void ln_rows(uint32_t* u, uint32_t term, uint32_t stg_row, int lane) {
  const int j = lane & 15;
  const float piv = __shfl_sync(0xffffffffu, bf_lo(u[0]), lane & 16);
  float s0 = 0.f, s1 = 0.f, q0 = 0.f, q1 = 0.f;
#pragma unroll
  for (int i = 0; i < 14; i++) {
    const float a = bf_lo(u[i]) - piv, c = bf_hi(u[i]) - piv;
    s0 += a; s1 += c; q0 = fmaf(a, a, q0); q1 = fmaf(c, c, q1);
  }
  float s = s0 + s1, q = q0 + q1;
  red16x2(s, q);
  s *= (1.f / D_); q *= (1.f / D_);
  const __nv_bfloat16 m1b = __float2bfloat16_rn(s + piv);
  const __nv_bfloat162 m1v = __halves2bfloat162(m1b, m1b);
  const float den = rbf(sqrtf_(rbf(rbf(fmaxf(fmaf(-s, s, q), 0.f)) + 1e-5f)));
  const float rden = rcpf_(den);
  s0 = s1 = q0 = q1 = 0.f;
#pragma unroll
  for (int i = 0; i < 14; i++) {
    const __nv_bfloat162 cv = __hsub2(*reinterpret_cast<__nv_bfloat162*>(&u[i]), m1v);
    const uint32_t c = *reinterpret_cast<const uint32_t*>(&cv);
    const uint32_t n = pack_bf2(bf_lo(c) * rden, bf_hi(c) * rden);
    const float a = bf_lo(n), e = bf_hi(n);
    s0 += a; s1 += e; q0 = fmaf(a, a, q0); q1 = fmaf(e, e, q1);
    u[i] = pack_h2(a, e);
  }
#pragma unroll
  for (int i = 0; i < 7; i++)
    asm volatile("st.shared.v2.b32 [%0], {%1,%2};" ::"r"(stg_row + (j + 16 * i) * 8), "r"(u[2 * i]), "r"(u[2 * i + 1]) : "memory");
  s = s0 + s1; q = q0 + q1;
  red16x2(s, q);
  s *= (1.f / D_); q *= (1.f / D_);
  const float den2 = rbf(sqrtf_(rbf(rbf(fmaxf(fmaf(-s, s, q), 0.f)) + 1e-5f)));
  if (j == 0) {
    const float ir = den * den2, mu = fmaf(rbf(s), den, __bfloat162float(m1b));
    const float ih = rbf(ir), mh = rbf(mu);
    const uint32_t mm = pack_bf2(mh, mh);
    sts128(term, pack_bf2(mu - mh, ih), mm, pack_bf2(mu - mh, ir - ih), mm);
  }
}

__device__ __forceinline__ void poll_tag(const unsigned* p, uint32_t tag) {
#pragma unroll 1
  for (int it = 0; it < 4096; it++) {
    if (!((ld_relaxed1(p) ^ tag) & 1)) break;
    __nanosleep(32);
  }
}
__device__ __forceinline__ bool last_release(uint32_t cnt) {
  unsigned old;
  asm volatile("atom.relaxed.cta.shared.inc.u32 %0, [%1], 7;" : "=r"(old) : "r"(cnt) : "memory");
  return old == 7;
}
__device__ __forceinline__ int mod7(int v) { return v >= 7 ? v - 7 : v; }

#define IDS const int tid = opaque(tid0), lane = tid & 31, t = tid & 127; (void)lane; (void)t;

__global__ void __launch_bounds__(384, 1)
fused_kernel(const Params p, const __grid_constant__ CUtensorMap tm_x, const __grid_constant__ CUtensorMap tm_w1,
             const __grid_constant__ CUtensorMap tm_w2, const __grid_constant__ CUtensorMap tm_out) {
  const uint32_t sb = smem_u32(smem_raw);
  const uint32_t ms = sb + OFF_M;
  const uint32_t bar0 = ms + M_BAR;
  const int tid0 = threadIdx.x;
  const int wi = __shfl_sync(0xffffffffu, tid0 >> 5, 0), wg = wi >> 2, w = wi & 3;
  const int b = blockIdx.x;
  const bool is_ssm = b >= NMLP;
  const int G = b / NRK, rk = b - G * NRK;
  const int kc0 = (G + rk) % 7;
  TSINIT();
  TSTAMP(0);
  {
    IDS
    TSTAMP(28);
    uint4 ld[7];
    KgIn kin;
    unsigned ep = 0;
    uint32_t b1w;
    const int rl = 2 * wi + (lane >> 4);
    {
      const int d = is_ssm ? 2 * (112 + 3 * (b - NMLP) + wg) + (w >> 1) : (wg < 2 ? 2 * b + wg : 336 + b);
      const int off = d * NST + 64 * (is_ssm ? 2 * (w & 1) : w) + 2 * lane;
      const __nv_bfloat16* P[8] = {p.a_re + off, p.a_im + off, p.b_re + off, p.b_im + off, p.c_re + off, p.c_im + off,
                                   p.log_dt + (d & ~1), p.dskip + (d & ~1)};
      asm volatile("" : "+l"(P[0]), "+l"(P[1]), "+l"(P[2]), "+l"(P[3]), "+l"(P[4]), "+l"(P[5]), "+l"(P[6]), "+l"(P[7]));
#pragma unroll
      for (int i = 0; i < 6; i++) kin.cur[i] = ldg32(P[i], 0);
      kin.ldt = ldg32(P[6], 0); kin.dk = ldg32(P[7], 0);
#pragma unroll
      for (int i = 0; i < 6; i++) kin.nxt[i] = 0u;
      if (is_ssm) {
#pragma unroll
        for (int i = 0; i < 6; i++) kin.nxt[i] = ldg32(P[i], 128);
      }
      asm volatile("" :: "l"(P[0]), "l"(P[1]), "l"(P[2]), "l"(P[3]), "l"(P[4]), "l"(P[5]), "l"(P[6]), "l"(P[7]));
      kin.odd = d & 1;
    }
    const uint32_t tbl = is_ssm ? sb + (4 * wg + (w >> 1)) * TBL : sb + OFF_T + wg * TBL;
#pragma unroll 1
    for (int i = is_ssm ? t & 63 : t; i < TBL_SC / 16; i += is_ssm ? 64 : 128) sts128(tbl + i * 16, 0u, 0u, 0u, 0u);
    const uint32_t lns = is_ssm ? sb + S_WORK + 2 * S_WGB + KSTG : sb + OFF_X + 2 * 16384;
    if (wi < 4 && lane == 0) {
      if (wi < 3) mbar_init(bar0 + 8 * wi, 1);
      asm volatile("fence.mbarrier_init.release.cluster;" ::: "memory");
      if (!is_ssm) asm volatile("prefetch.tensormap [%0];" ::"l"(wi == 0 ? &tm_x : wi == 1 ? &tm_w1 : wi == 2 ? &tm_w2 : &tm_out) : "memory");
    }
    if ((wi == 5 || (wi == 6 && !is_ssm)) && lane == 0)
      asm volatile("cp.async.bulk.prefetch.L2.global [%0], %1;" ::"l"(wi == 5 ? p.x + (size_t)(b & 127) * 16 * D_ : p.w1 + (size_t)b * 4 * F_), "r"(14336) : "memory");
    __syncwarp();
    if (wi == 4 && lane < 16) asm volatile("st.shared.b32 [%0], 0;" ::"r"(ms + M_REL + 4 * lane) : "memory");
    TSTAMP(31);
    auto mid0 = [&]() {
      TSTAMP(27);
      if (wg < 2) {
        const __nv_bfloat16* xr = p.x + (size_t)(16 * (b & 127) + rl) * D_ + 4 * (lane & 15);
#pragma unroll
        for (int i = 0; i < 7; i++) asm volatile("ld.global.nc.v2.b32 {%0,%1}, [%2];" : "=r"(ld[i].x), "=r"(ld[i].y) : "l"(xr + 64 * i));
      } else {
        const __nv_bfloat16* wr = p.w1 + (size_t)(112 * (b & 3) + 4 * w + (lane & 3)) * F_ + 64 * (is_ssm ? 0 : b >> 2) + 8 * (lane >> 2);
        if (t == 96 && !is_ssm)
          asm volatile("cp.async.bulk.prefetch.L2.global [%0], %1;" ::"l"(p.w1 + (size_t)b * 4 * F_), "r"(14336) : "memory");
        b1w = ldg32(p.b1 + 64 * (is_ssm ? 0 : b >> 2) + (t & 62), 0);
        if (t == 32) ep = ld_relaxed1(&p.s->epoch);
      }
    };
    auto mid = [&]() {
    TSTAMP(30);
    if (wi < 2 && lane == 0 && !is_ssm) {
      mbar_expect(bar0 + 8 * wi, 49152);
      tma_2d(sb + OFF_X + wi * 16384, &tm_x, 64 * wi, 128 * G, bar0 + 8 * wi);
      tma_3d(sb + OFF_W + wi * 32768, &tm_w1, 0, 64 * wi, 4 * rk, bar0 + 8 * wi);
    }
    __syncwarp();
    if (wg < 2) {
      uint32_t u[14];
#pragma unroll
      for (int i = 0; i < 7; i++) { u[2 * i] = ld[i].x; u[2 * i + 1] = ld[i].y; }
      ln_rows(u, ms + M_LT + rl * 16, lns + ((rl & 1) | ((rl >> 2) << 1) | ((rl & 2) << 2)) * 912, lane);
      bar_arrive(7, 384);
    } else {
      float cs[4] = {0.f, 0.f, 0.f, 0.f};
      const int g = lane >> 2;
      const uint32_t one = (g & 1) ? 0x3f800000u : 0x00003f80u;
      const uint32_t s0 = (g >> 1) == 0 ? one : 0u, s1 = (g >> 1) == 1 ? one : 0u, s2 = (g >> 1) == 2 ? one : 0u, s3 = (g >> 1) == 3 ? one : 0u;
#pragma unroll
      for (int i = 0; i < 7; i++) {
        mma_bf16(cs, s0, 0u, s1, 0u, un[4 * i], un[4 * i + 1]);
        mma_bf16(cs, s2, 0u, s3, 0u, un[4 * i + 2], un[4 * i + 3]);
      }
      sts32f(ms + M_CSR + (w * 64 + (lane & 3) * 16 + g) * 4, cs[0]);
      sts32f(ms + M_CSR + (w * 64 + (lane & 3) * 16 + g + 8) * 4, cs[1]);
      if (t == 32) { asm volatile("st.shared.b32 [%0], %1;" ::"r"(ms + M_EP), "r"(ep + 1) : "memory"); red_relaxed(&p.s->cntA); }
      bar_sync(7, 384);
      const uint32_t la = lns + (lane & 15) * 912 + (lane >> 4) * 16 + w * 224;
      uint2* dst = (uint2*)(p.s->xnT + (size_t)(56 * w + (lane >> 3)) * 512 + 4 * b) + (lane & 7);
      uint32_t r[28];
#pragma unroll
      for (int k = 0; k < 7; k++) ldsm4t(la + k * 32, r[4 * k], r[4 * k + 1], r[4 * k + 2], r[4 * k + 3]);
      const uint32_t tag = lds32(ms + M_EP) & 1;
      if (b < 128) {
#pragma unroll
        for (int k = 0; k < 14; k++) st_relaxed2(dst + k * 4096, (r[2 * k] & ~1u) | tag, (r[2 * k + 1] & ~1u) | tag);
      }
      if (t < 64 && !is_ssm) {
        const uint32_t a = ms + M_CSR + t * 4;
        const float c = -((lds32f(a) + lds32f(a + 256)) + (lds32f(a + 512) + lds32f(a + 768)));
        const float ch = rbf(c);
        uint2* dx = (uint2*)(p.s->bx + (b >> 4) * 512 + ((b >> 1) & 1) * 256 + ((b >> 2) & 3) * 64 + t) + (b & 1);
        const float b1v = (b & 2) ? 0.f : ((t & 1) ? bf_hi(b1w) : bf_lo(b1w));
        asm volatile("{.reg .b64 a; mov.b64 a, {%1,%2}; st.relaxed.gpu.global.b64 [%0], a;}"
                     ::"l"(dx), "r"(pack_bf2(ch, b1v)), "r"((pack_bf2(c - ch, ch) & ~1u) | tag) : "memory");
      }
      if (t >= 64 && t < 80 && b < 128) {
        const uint4 a = lds128(ms + M_LT + (t - 64) * 16);
        st_b128(p.s->ax + 16 * b + t - 64, tag, a.x, a.y, a.z, a.w);
      }
    }
    TSTAMP(29);
    };
    kgen_wg(kin, is_ssm ? 2 : 1, stg, tbl, ms + M_MX + wg * 16, w, lane, 4 + wg, mid0, mid);
  }
  TSTAMP(1);

  if (is_ssm || wg == 2) {
    asm volatile("setmaxnreg.dec.sync.aligned.u32 136;");
    uint4 v[4], tv[5];
    {
      IDS
      bar_sync(2, 384);
#pragma unroll 1
      for (int c = is_ssm ? 1 : 2; c >= 0; c--) {
        ktab_build(is_ssm ? stg + c * 3072 : (c < 2 ? sb + OFF_A + c * KSTG : stg), !is_ssm, w, (is_ssm ? sb + S_TBL + 4 * wg * TBL : sb + OFF_T) + c * TBL, lane);
        if (c == 2) {
          fence_async();
          bar_sync(6, 128);
          if (t == 0) {
            mbar_expect(bar0 + 16, 49152);
            tma_2d(sb + OFF_X + 2 * 16384, &tm_x, 128, 128 * G, bar0 + 16);
            tma_3d(sb + OFF_W + 2 * 32768, &tm_w1, 0, 128, 4 * rk, bar0 + 16);
          }
          if (t == 96) { bulk_s2g(p.s->tbl + b * (TBL / 16), sb + OFF_T + 2 * TBL, TBL); bulk_commit(); }
          __syncwarp();
        }
      }
      if (!is_ssm) {
#pragma unroll
        for (int q = 0; q < 4; q++) tv[q] = ld_2x64(p.s->bx + 512 * rk + q * 128 + t);
        tv[4] = ld_b128(p.s->ax + 128 * G + t);
      }
      const uint4* src = p.s->xnT + (size_t)(is_ssm ? 112 + 3 * (b - NMLP) + wg : b) * 512 + t;
#pragma unroll
      for (int q = 0; q < 4; q++) v[q] = ld_relaxed4(src + q * 128);
      bar_sync(4 + wg, 128);
    }
    TSTAMP(2);
    if (!is_ssm) {
      IDS
      const unsigned ep1 = lds32(ms + M_EP);
#pragma unroll 1
      for (int it = 0; it < 16 * RETRY_MAX; it++) {
        uint32_t bad = tv[4].x ^ ep1;
#pragma unroll
        for (int q = 0; q < 4; q++) bad |= (tv[q].y ^ ep1) | (tv[q].w ^ ep1);
        if (!__any_sync(0xffffffffu, bad & 1)) break;
        __nanosleep(200);
#pragma unroll
        for (int q = 0; q < 4; q++) tv[q] = ld_2x64(p.s->bx + 512 * rk + q * 128 + t);
        tv[4] = ld_b128(p.s->ax + 128 * G + t);
      }
#pragma unroll
      for (int q = 0; q < 5; q++) sts128(sb + OFF_B + (q < 4 ? B_BX + q * 2048 : B_AX) + t * 16, tv[q].x, tv[q].y, tv[q].z, tv[q].w);
      if (t < 64) sts32f(ms + M_CSR + t * 4, 0.5f * __bfloat162float(p.b2[64 * rk + t]));
      fence_async();
      bar_arrive(1, 384);
      if (t == 64)
        asm volatile("cp.async.bulk.prefetch.L2.global [%0], %1;" ::"l"(p.w2 + (size_t)(256 * rk + 16 * G) * D_), "r"(16 * D_ * 2) : "memory");
    }
#pragma unroll 1
    for (int pi = 0; ; pi++) {
      {
        IDS
        const unsigned ep1 = lds32(ms + M_EP);
        const int pair = !is_ssm ? b : (pi == 0 ? 112 + 3 * (b - NMLP) : (b < NMLP + 12 ? 172 + 3 * (b - NMLP) : 184 + 2 * (b - NMLP))) + wg;
        const uint32_t work = is_ssm ? sb + S_WORK + wg * S_WGB : sb + OFF_A;
        const uint32_t z = work + SIG_V3 - 1024 + (t >> 6) * 4096 + (t & 63) * 16;
        sts128(z, 0u, 0u, 0u, 0u); sts128(z + SIG, 0u, 0u, 0u, 0u);
        if (t < 72) {
          const uint32_t zu = work + SIG_U + (t & 7) * U_LBO + (t >> 3) * 16;
          sts128(zu, 0u, 0u, 0u, 0u); sts128(zu + SIG, 0u, 0u, 0u, 0u);
        }
        const uint4* src = p.s->xnT + (size_t)pair * 512 + t;
#pragma unroll 1
        for (int it = 0; it < RETRY_MAX; it++) {
          uint32_t bad = 0;
#pragma unroll
          for (int q = 0; q < 4; q++) bad |= (((v[q].x ^ ep1) | (v[q].y ^ ep1) | (v[q].z ^ ep1) | (v[q].w ^ ep1)) & 1) << q;
          const unsigned m = __ballot_sync(0xffffffffu, bad);
          if (!m) break;
          if (lane == __ffs(m) - 1) poll_tag((const unsigned*)(src + (__ffs(bad) - 1) * 128) + 3, ep1);
          __syncwarp();
#pragma unroll
          for (int q = 0; q < 4; q++) v[q] = ld_relaxed4(src + q * 128);
        }
        TSTAMP(5);
        const uint32_t a = work + ((t >> 1) & 1) * SIG + SIG_U + (2 * ((t >> 2) & 3) + (t & 1)) * U_LBO + ((t >> 4) + 9) * 16;
#pragma unroll
        for (int q = 0; q < 4; q++) sts128(a + q * 128, v[q].x & ~1u, v[q].y & ~1u, v[q].z & ~1u, v[q].w & ~1u);
        bar_sync(4 + wg, 128);
#pragma unroll 1
        for (int k = w; k < 6; k += 4) sig_windows(work + (k & 1) * SIG, (k >> 1) * 32 + lane);
        fence_async();
        if (t == 96 && !is_ssm) { bulk_wait0(); red_release(&p.s->cntT); }
        if (pi == 1) mbar_wait(bar0 + 8 * wg, 0);
        TSTAMP(6);
        bar_sync(is_ssm ? 4 + wg : 3, is_ssm ? 128 : 384);
        TSTAMP(7);
      }
      uint32_t keep[8];
      float res[16];
#pragma unroll 1
      for (int c = 0; c < 2; c++) {
        IDS
        const uint32_t work = is_ssm ? sb + S_WORK + wg * S_WGB : sb + OFF_A;
        const uint32_t tbl = (is_ssm ? sb + (4 * wg + 2 * pi) * TBL : sb + OFF_T) + c * TBL;
        conv_channel(tbl, work + c * SIG, is_ssm ? work + 2 * SIG + Y3B : sb + OFF_B, work + 2 * SIG, lds32f(tbl + TBL_SC), w, lane, 4 + wg, res);
        TSTAMP(16 + 2 * pi + c);
        const float os = lds32f(tbl + TBL_SC + 8);
        if (c == 0) {
#pragma unroll
          for (int i = 0; i < 8; i++) keep[i] = pack_bf2(res[2 * i] * os, res[2 * i + 1] * os);
          if (is_ssm && pi == 0 && t == 96 && (b < NMLP + 12 || wg < 2)) {
            wait_count(&p.s->cntT, lds32(ms + M_EP) * NMLP);
            asm volatile("fence.proxy.async;" ::: "memory");
            mbar_expect(bar0 + 8 * wg, 2 * TBL);
            bulk_g2s(sb + (4 * wg + 2) * TBL, p.s->tbl + (2 * ((b < NMLP + 12 ? 172 + 3 * (b - NMLP) : 184 + 2 * (b - NMLP)) + wg) - 336) * (TBL / 16),
                     2 * TBL, bar0 + 8 * wg);
          }
          __syncwarp();
        } else {
          const int pair = !is_ssm ? b : (pi == 0 ? 112 + 3 * (b - NMLP) : (b < NMLP + 12 ? 172 + 3 * (b - NMLP) : 184 + 2 * (b - NMLP))) + wg;
          uint4* dst = p.s->s2 + ((size_t)(lane & 3) * 224 + pair) * 32 + w * 8 + (lane >> 2);
          const uint32_t tag = (lds32(ms + M_EP) & 1) * 0x10001u;
#pragma unroll
          for (int nt = 0; nt < 4; nt++) {
            const uint32_t n0 = pack_bf2(res[4 * nt] * os, res[4 * nt + 1] * os), n1 = pack_bf2(res[4 * nt + 2] * os, res[4 * nt + 3] * os);
            const uint32_t k0 = (keep[2 * nt] & 0xfffefffeu) | tag;
            asm volatile("{.reg .b64 a, c; mov.b64 a, {%1,%2}; mov.b64 c, {%3,%4}; st.relaxed.gpu.global.v2.b64 [%0], {a, c};}"
                         ::"l"(dst + nt * 4 * 224 * 32), "r"(__byte_perm(k0, n0, 0x5410)), "r"(__byte_perm(keep[2 * nt + 1], n1, 0x5410)),
                         "r"(__byte_perm(k0, n0, 0x7632)), "r"(__byte_perm(keep[2 * nt + 1], n1, 0x7632)) : "memory");
          }
        }
      }
      TSTAMP(8 + pi);
      TSDUMP();
      {
        IDS
        if (pi == 1 || !is_ssm || (b >= NMLP + 12 && wg == 2)) break;
        const uint4* src = p.s->xnT + (size_t)((b < NMLP + 12 ? 172 + 3 * (b - NMLP) : 184 + 2 * (b - NMLP)) + wg) * 512 + t;
#pragma unroll
        for (int q = 0; q < 4; q++) v[q] = ld_relaxed4(src + q * 128);
      }
    }
    if (b == 0 && tid0 == 256) {
      const unsigned ep1 = lds32(ms + M_EP);
      wait_count(&p.s->cntA, ep1 * NCTA);
      *(volatile unsigned*)&p.s->epoch = ep1;
    }
  } else {
    bar_arrive(1, 384);
    asm volatile("setmaxnreg.inc.sync.aligned.u32 192;");
    bar_sync(7, 384);
    uint32_t H[64];
    {
      float acc[128];
#pragma unroll
      for (int i = 0; i < 128; i++) acc[i] = 0.f;
      fence_regs<128>(acc);
      float p0, q0, p1, q1;
      {
        IDS
        int sl = 0;
#pragma unroll 1
        for (int s = 0; s < 7; s++) {
          mbar_wait(bar0 + 8 * sl, (s >= 3 && s < 6));
          TSTAMP(17 + s);
          const uint64_t da = mkdesc(sb + OFF_X + sl * 16384 + wg * 8192, 16, 1024, 1);
          const uint64_t db = mkdesc(sb + OFF_W + sl * 32768, 8192, 1024, 1);
          wg_fence();
#pragma unroll
          for (int k = 0; k < 4; k++) wg_ss_bf16_n256(acc, da + 2 * k, db + 128 * k, 1);
          wg_commit();
          wg_wait<1>();
          const int pl = sl == 0 ? 2 : sl - 1;
          sl = sl == 2 ? 0 : sl + 1;
          if (s > 0 && lane == 0 && last_release(ms + M_REL + 4 * s)) {
            mbar_expect(bar0 + 8 * pl, s == 5 ? 32768 : 49152);
            if (s < 5) tma_3d(sb + OFF_W + pl * 32768, &tm_w1, 0, 64 * (s + 2), 4 * rk, bar0 + 8 * pl);
            else tma_2d(sb + OFF_W + pl * 32768, &tm_w2, 64 * mod7(rk + s - 4), 256 * rk, bar0 + 8 * pl);
            if (s != 5) tma_2d(sb + OFF_X + pl * 16384, &tm_x, 64 * (s < 5 ? (s + 2) : rk), 128 * G, bar0 + 8 * pl);
          }
        }
        TSTAMP(15);
        asm volatile("setmaxnreg.inc.sync.aligned.u32 184;");
        bar_sync(1, 384);
        wg_fence();
        wg_ss_bf16_n256k(acc, mkdesc(sb + OFF_B + B_AX + wg * 1024, 0, 128, 0), mkdesc(sb + OFF_B + B_BX, 4096, 128, 0), 1);
        wg_commit();
        wg_wait<1>();
        if (lane == 0 && last_release(ms + M_REL + 4 * 7)) {
          mbar_expect(bar0, 65536);
#pragma unroll 1
          for (int c = 2; c < 4; c++) tma_2d(sb + (c - 2) * OFF_X, &tm_w2, 64 * mod7(rk + 1 + c), 256 * rk, bar0);
        }
        bar_arrive(3, 384);
        const uint32_t ra = sb + OFF_B + B_AX + (16 * wi + (lane >> 2)) * 16;
        const float r0 = rcpf_(bf_hi(lds32(ra)) + bf_hi(lds32(ra + 8))), r1 = rcpf_(bf_hi(lds32(ra + 128)) + bf_hi(lds32(ra + 136)));
        p0 = 0.7978845608028654f * r0; q0 = 0.0356774081363001f * r0 * r0 * r0;
        p1 = 0.7978845608028654f * r1; q1 = 0.0356774081363001f * r1 * r1 * r1;
      }
      wg_wait<0>();
      fence_regs<128>(acc);
      bar_arrive(12, 384);
      TSTAMP(16);
#pragma unroll 1
      for (int hf = 0; hf < 2; hf++) {
        float th[8];
#pragma unroll
        for (int i = 0; i < 35; i++) {
          if (i < 32) {
            const float pp = (i & 1) ? p1 : p0, qq = (i & 1) ? q1 : q0;
            const float a = acc[2 * i], c = acc[2 * i + 1];
            th[2 * (i & 3)] = tanhf_(a * fmaf(a * a, qq, pp)); th[2 * (i & 3) + 1] = tanhf_(c * fmaf(c * c, qq, pp));
          }
          if (i >= 3) {
            const int j = i - 3;
            asm volatile("{.reg .f32 x, y; fma.rn.f32 x, %0, %5, %0; fma.rn.f32 y, %1, %6, %1; mov.f32 %0, %3; mov.f32 %1, %4;\n"
                         ".reg .b32 h; cvt.rn.bf16x2.f32 h, y, x; mov.b32 %2, h;}"
                         : "+f"(acc[2 * j]), "+f"(acc[2 * j + 1]), "=f"(acc[64 + j])
                         : "f"(acc[64 + 2 * j]), "f"(acc[65 + 2 * j]), "f"(th[2 * (j & 3)]), "f"(th[2 * (j & 3) + 1]));
          }
        }
      }
#pragma unroll
      for (int i = 0; i < 32; i++) { H[i] = __float_as_uint(acc[i]); H[32 + i] = __float_as_uint(acc[64 + i]); }
    }
    TSTAMP(3);
    IDS
    float acc[32], pre[32];
    uint32_t pk[16];
#pragma unroll
    for (int i = 0; i < 32; i++) pre[i] = 0.f;
    const uint32_t tag = lds32(ms + M_EP) & 1;
    const uint4* inbox = p.s->part + (uint32_t)(b * 6 * 1024 + tid);
    uint4 rv[4];
    auto fetch = [&](int slot) {
#pragma unroll
      for (int q = 0; q < 4; q++) rv[q] = ld_b128(inbox + slot * 1024 + q * 256);
    };
    auto recv = [&](int slot) {
#pragma unroll 1
      for (int it = 0; it < RETRY_MAX; it++) {
        const unsigned m = __ballot_sync(0xffffffffu, ((rv[0].x ^ tag) | (rv[1].x ^ tag) | (rv[2].x ^ tag) | (rv[3].x ^ tag)) & 1);
        if (!m) break;
        if (lane == __ffs(m) - 1) poll_tag((const unsigned*)(inbox + slot * 1024 + 768), tag);
        __syncwarp();
        fetch(slot);
      }
#pragma unroll
      for (int q = 0; q < 4; q++) {
        const uint32_t u[4] = {rv[q].x, rv[q].y, rv[q].z, rv[q].w};
#pragma unroll
        for (int k = 0; k < 4; k++) { pre[8 * q + 2 * k] += bf_lo(u[k]); pre[8 * q + 2 * k + 1] += bf_hi(u[k]); }
      }
    };
#pragma unroll 1
    for (int s = 0; s < 7; s++) {
      if (s != 3) mbar_wait(bar0 + 8 * ((0x0210021u >> (4 * s)) & 3), (0x34 >> s) & 1);
      const uint64_t db = mkdesc(sb + ((0x0213021u >> (4 * s)) & 3) * 32768, 8192, 1024, 1);
      wg_fence();
#pragma unroll
      for (int k = 0; k < 16; k++) wg_rs_bf16_n64(acc, H[4 * k], H[4 * k + 1], H[4 * k + 2], H[4 * k + 3], db + 128 * k, k != 0);
      wg_commit();
      if (s > 0) {
        uint4* dst = p.s->part + (uint32_t)(((G * 7 + mod7(rk + s)) * 6 + s - 1) * 1024 + tid);
#pragma unroll
        for (int q = 0; q < 4; q++) st_b128(dst + q * 256, tag, pk[4 * q], pk[4 * q + 1], pk[4 * q + 2], pk[4 * q + 3]);
        if (s < 4 && lane == 0 && last_release(ms + M_REL + 4 * (7 + s))) {
          const int sl = (0x0210u >> (4 * s)) & 3;
          mbar_expect(bar0 + 8 * sl, 32768);
          tma_2d(sb + sl * 32768, &tm_w2, 64 * mod7(mod7(rk + 4 + s)), 256 * rk, bar0 + 8 * sl);
        }
        __syncwarp();
      }
      if (s >= 4) recv(s - 4);
      if (s >= 3) fetch(s - 3);
      wg_wait<0>();
      fence_regs<32>(acc);
#pragma unroll
      for (int k = 0; k < 16; k++) pk[k] = pack_bf2(acc[2 * k], acc[2 * k + 1]);
      TSTAMP(4 + s);
    }
    {
      const uint2* sp = (const uint2*)(p.s->s2 + ((size_t)G * 224 + 32 * rk + (lane & 3)) * 32 + w * 8 + (lane >> 2)) + wg;
#pragma unroll 1
      for (int it = 0; it < RETRY_MAX; it++) {
#pragma unroll
        for (int i = 0; i < 8; i++)
          asm volatile("{.reg .b64 a; ld.relaxed.gpu.global.b64 a, [%2]; mov.b64 {%0,%1}, a;}"
                       : "=r"(pk[2 * i]), "=r"(pk[2 * i + 1]) : "l"(sp + i * 4 * 64) : "memory");
#pragma unroll 1
        for (int s = it ? 6 : 3; s < 6; s++) { recv(s); if (s < 5) fetch(s + 1); }
        uint32_t bad = 0;
#pragma unroll
        for (int i = 0; i < 8; i++) bad |= ((pk[2 * i] ^ tag) & 1) << i;
        const unsigned m = __ballot_sync(0xffffffffu, bad);
        if (!m) break;
        if (lane == __ffs(m) - 1) poll_tag((const unsigned*)(sp + (__ffs(bad) - 1) * 4 * 64), tag);
        __syncwarp();
      }
    }
    TSTAMP(12);
    const int g = lane >> 2, tq = lane & 3;
    const uint32_t xa = sb + OFF_X + 2 * 16384 + (16 * wi + (lane & 15)) * 128;
    uint32_t xw[16];
#pragma unroll
    for (int q = 0; q < 4; q++) ldsm4(xa + (((2 * q + (lane >> 4)) ^ (lane & 7)) << 4), xw[4 * q], xw[4 * q + 1], xw[4 * q + 2], xw[4 * q + 3]);
    const uint32_t ra = sb + OFF_B + B_AX + (16 * wi + g) * 16;
    const float r0 = 0.25f * rcpf_(bf_hi(lds32(ra)) + bf_hi(lds32(ra + 8))), r1 = 0.25f * rcpf_(bf_hi(lds32(ra + 128)) + bf_hi(lds32(ra + 136)));
#pragma unroll
    for (int i = 0; i < 8; i++) {
      const float2 bb = lds64f(ms + M_CSR + (8 * i + 2 * tq) * 4);
#pragma unroll
      for (int e = 0; e < 2; e++) {
        const int k = 2 * i + e;
        const float h0 = fmaf(acc[2 * k] + pre[2 * k], e ? r1 : r0, bb.x), h1 = fmaf(acc[2 * k + 1] + pre[2 * k + 1], e ? r1 : r0, bb.y);
        const uint32_t gw = pack_bf2(fmaf(h0, tanhf_(h0), h0), fmaf(h1, tanhf_(h1), h1));
        asm("fma.rn.bf16x2 %0, %1, %2, %0;" : "+r"(xw[k]) : "r"(pk[k]), "r"(gw));
      }
    }
#pragma unroll
    for (int q = 0; q < 4; q++) stsm4(xa + (((2 * q + (lane >> 4)) ^ (lane & 7)) << 4), xw[4 * q], xw[4 * q + 1], xw[4 * q + 2], xw[4 * q + 3]);
    fence_async();
    __syncwarp();
    if (lane == 0) {
      tma_store_2d(&tm_out, sb + OFF_X + 2 * 16384 + wi * 2048, 64 * rk, 128 * G + 16 * wi);
      bulk_commit();
      bulk_wait0_read();
    }
    TSTAMP(13);
    TSDUMP();
  }
}

typedef CUresult (*EncodeFn)(CUtensorMap*, CUtensorMapDataType, cuuint32_t, void*, const cuuint64_t*, const cuuint64_t*,
                             const cuuint32_t*, const cuuint32_t*, CUtensorMapInterleave, CUtensorMapSwizzle,
                             CUtensorMapL2promotion, CUtensorMapFloatOOBfill);

void make_map(EncodeFn fn, CUtensorMap* m, const void* ptr, int rank, const cuuint64_t* dims, const cuuint64_t* strides, const cuuint32_t* box) {
  const cuuint32_t es[3] = {1, 1, 1};
  fn(m, CU_TENSOR_MAP_DATA_TYPE_BFLOAT16, rank, const_cast<void*>(ptr), dims, strides, box, es, CU_TENSOR_MAP_INTERLEAVE_NONE,
     CU_TENSOR_MAP_SWIZZLE_128B, CU_TENSOR_MAP_L2_PROMOTION_L2_128B, CU_TENSOR_MAP_FLOAT_OOB_FILL_NONE);
}

}

extern "C" void kernel_launch(void* const* d_in, const int* in_sizes, int n_in, void* d_out, int out_size) {
  (void)in_sizes; (void)n_in; (void)out_size;
  void* fnp = nullptr;
  cudaDriverEntryPointQueryResult qr;
  cudaGetDriverEntryPoint("cuTensorMapEncodeTiled", &fnp, cudaEnableDefault, &qr);
  EncodeFn fn = (EncodeFn)fnp;
  Params p;
  p.x = (const __nv_bfloat16*)d_in[0];
  p.a_re = (const __nv_bfloat16*)d_in[1]; p.a_im = (const __nv_bfloat16*)d_in[2];
  p.b_re = (const __nv_bfloat16*)d_in[3]; p.b_im = (const __nv_bfloat16*)d_in[4];
  p.c_re = (const __nv_bfloat16*)d_in[5]; p.c_im = (const __nv_bfloat16*)d_in[6];
  p.log_dt = (const __nv_bfloat16*)d_in[7]; p.dskip = (const __nv_bfloat16*)d_in[8];
  p.w1 = (const __nv_bfloat16*)d_in[10]; p.b1 = (const __nv_bfloat16*)d_in[11];
  p.w2 = (const __nv_bfloat16*)d_in[12]; p.b2 = (const __nv_bfloat16*)d_in[13];
  void* sp = nullptr;
  cudaGetSymbolAddress(&sp, g_scr);
  p.s = (Scratch*)sp;
  CUtensorMap mx, mw1, mw2, mo;
  {
    const cuuint64_t dims[2] = {448, 2048}, str[1] = {896};
    const cuuint32_t box[2] = {64, 128}, boxo[2] = {64, 16};
    make_map(fn, &mx, p.x, 2, dims, str, box);
    make_map(fn, &mo, d_out, 2, dims, str, boxo);
  }
  {
    const cuuint64_t dims[3] = {64, 448, 28}, str[2] = {3584, 128};
    const cuuint32_t box[3] = {64, 64, 4};
    make_map(fn, &mw1, p.w1, 3, dims, str, box);
  }
  {
    const cuuint64_t dims[2] = {448, 1792}, str[1] = {896};
    const cuuint32_t box[2] = {64, 256};
    make_map(fn, &mw2, p.w2, 2, dims, str, box);
  }
  cudaFuncSetAttribute(fused_kernel, cudaFuncAttributeMaxDynamicSharedMemorySize, SMEM_BYTES);
  fused_kernel<<<NCTA, 384, SMEM_BYTES>>>(p, mx, mw1, mw2, mo);
}
```

```cpp
#include <cuda_runtime.h>
#include <cuda_bf16.h>
#include <cuda_fp16.h>
#include <cuda.h>
#include <stdint.h>

namespace {

constexpr int D_ = 448, NST = 256;
constexpr int NRK = 7, NMLP = 112, NCTA = 132;
constexpr int SPIN_MAX = 1 << 20, RETRY_MAX = 512;

struct Scratch {
  unsigned cntA, pad0[63], epoch, pad1[63];
  unsigned hx[128 * 4], hb[112 * 2 + 32], hs[448 * 4], hp[112 * 6 * 8];
  uint4 ax[2048];
  uint4 bx[7 * 512];
  uint4 xnT[224 * 512];
  uint4 s2[16 * 224 * 32];
  uint4 part[16 * 7 * 6 * 1024];
};
__device__ uint4 g_scr[(sizeof(Scratch) + (2 << 20)) / 16];
#define TSTAMP(i)
#define TSINIT()
#define GT(i)
#define TSDUMP()
extern __shared__ __align__(1024) uint8_t smem_raw[];

constexpr int TBL_SC = 5248, TBL = 5264;
constexpr int TBL_C1 = 2624;
constexpr int SIG = 19584;
constexpr int SIG_U = 0, U_LBO = 1312, SIG_V3 = 6272, SIG_V5 = 10368, SIG_V7 = 13440, SIG_V9 = 15488, SIG_V2 = 17536;
constexpr int Y2B = 6912, Y3B = 4608;
constexpr int KSTG = 14 * 2048;
constexpr int YB = Y3B + Y2B, WRK = YB + SIG;
constexpr int OFF_W = 0, OFF_X = 98304, OFF_A = 147456, OFF_T = OFF_A + 65536 + 256, OFF_M = OFF_A + 65536 + 16384;
constexpr int OFF_AX = OFF_A, OFF_BX = OFF_A + 2048;
constexpr int M_BAR = 0, M_REL = 128, M_EP = 192, M_B2 = 256, M_MX = 512, M_RED = 640, M_ID = 1152, M_CS = 1664, M_END = 2688;
constexpr int SMEM_BYTES = OFF_M + M_END + 384;
static_assert(KSTG <= WRK && WRK <= 32768 && SMEM_BYTES <= 232448, "smem");

struct Params {
  const __nv_bfloat16 *a_re, *a_im, *b_re, *b_im, *c_re, *c_im, *log_dt, *dskip, *b1, *w2, *b2;
  Scratch* s;
};

__device__ __forceinline__ int opaque(int x) { int v; asm volatile("mov.u32 %0, %1;" : "=r"(v) : "r"(x)); return v; }
__device__ __forceinline__ uint32_t smem_u32(const void* p) { return (uint32_t)__cvta_generic_to_shared(p); }
__device__ __forceinline__ void mbar_init(uint32_t bar, int cnt) { asm volatile("mbarrier.init.shared::cta.b64 [%0], %1;" ::"r"(bar), "r"(cnt)); }
__device__ __forceinline__ void mbar_expect(uint32_t bar, uint32_t bytes) {
  asm volatile("mbarrier.arrive.expect_tx.shared::cta.b64 _, [%0], %1;" ::"r"(bar), "r"(bytes) : "memory");
}
__device__ __forceinline__ void mbar_wait(uint32_t bar, uint32_t parity) {
  uint32_t done = 0;
#pragma unroll 1
  for (int it = 0; it < SPIN_MAX; it++) {
    asm volatile("{.reg .pred p; mbarrier.try_wait.parity.shared::cta.b64 p, [%1], %2; selp.u32 %0,1,0,p;}"
                 : "=r"(done) : "r"(bar), "r"(parity) : "memory");
    if (done) break;
  }
}
__device__ __forceinline__ void tma_2d(uint32_t dst, const CUtensorMap* m, int c0, int c1, uint32_t bar) {
  asm volatile("cp.async.bulk.tensor.2d.shared::cluster.global.mbarrier::complete_tx::bytes [%0], [%1, {%3, %4}], [%2];"
               ::"r"(dst), "l"(m), "r"(bar), "r"(c0), "r"(c1) : "memory");
}
__device__ __forceinline__ void tma_3d(uint32_t dst, const CUtensorMap* m, int c0, int c1, int c2, uint32_t bar) {
  asm volatile("cp.async.bulk.tensor.3d.shared::cluster.global.mbarrier::complete_tx::bytes [%0], [%1, {%3, %4, %5}], [%2];"
               ::"r"(dst), "l"(m), "r"(bar), "r"(c0), "r"(c1), "r"(c2) : "memory");
}
__device__ __forceinline__ void tma_store_2d(const CUtensorMap* m, uint32_t src, int c0, int c1) {
  asm volatile("cp.async.bulk.tensor.2d.global.shared::cta.bulk_group [%0, {%2, %3}], [%1];"
               ::"l"(m), "r"(src), "r"(c0), "r"(c1) : "memory");
}
__device__ __forceinline__ void bulk_g2s(uint32_t dst, const void* src, uint32_t bytes, uint32_t bar) {
  asm volatile("cp.async.bulk.shared::cluster.global.mbarrier::complete_tx::bytes [%0], [%1], %2, [%3];"
               ::"r"(dst), "l"(src), "r"(bytes), "r"(bar) : "memory");
}
__device__ __forceinline__ void bulk_commit() { asm volatile("cp.async.bulk.commit_group;" ::: "memory"); }
__device__ __forceinline__ void bulk_wait0_read() { asm volatile("cp.async.bulk.wait_group.read 0;" ::: "memory"); }
__device__ __forceinline__ void fence_async() { asm volatile("fence.proxy.async.shared::cta;" ::: "memory"); }
__device__ __forceinline__ void bar_sync(int id, int n) { asm volatile("bar.sync %0, %1;" ::"r"(id), "r"(n) : "memory"); }
__device__ __forceinline__ void bar_arrive(int id, int n) { asm volatile("bar.arrive %0, %1;" ::"r"(id), "r"(n) : "memory"); }
__device__ __forceinline__ void wg_fence() { asm volatile("wgmma.fence.sync.aligned;" ::: "memory"); }
__device__ __forceinline__ void wg_commit() { asm volatile("wgmma.commit_group.sync.aligned;" ::: "memory"); }
template <int N> __device__ __forceinline__ void wg_wait() { asm volatile("wgmma.wait_group.sync.aligned %0;" ::"n"(N) : "memory"); }
template <int N> __device__ __forceinline__ void fence_regs(float* d) {
#pragma unroll
  for (int i = 0; i < N; i++) asm volatile("" : "+f"(d[i])::"memory");
}
__device__ __forceinline__ uint64_t mkdesc(uint32_t addr, uint32_t lbo, uint32_t sbo, uint32_t sw) {
  return (uint64_t)((addr & 0x3FFFF) >> 4) | ((uint64_t)(lbo >> 4) << 16) | ((uint64_t)(sbo >> 4) << 32) | ((uint64_t)sw << 62);
}
__device__ __forceinline__ uint32_t lds32(uint32_t a) { uint32_t v; asm volatile("ld.shared.b32 %0, [%1];" : "=r"(v) : "r"(a) : "memory"); return v; }
__device__ __forceinline__ float lds32f(uint32_t a) { float v; asm volatile("ld.shared.f32 %0, [%1];" : "=f"(v) : "r"(a) : "memory"); return v; }
__device__ __forceinline__ float2 lds64f(uint32_t a) { float2 v; asm volatile("ld.shared.v2.f32 {%0,%1}, [%2];" : "=f"(v.x), "=f"(v.y) : "r"(a) : "memory"); return v; }
__device__ __forceinline__ uint4 lds128(uint32_t a) {
  uint4 v; asm volatile("ld.shared.v4.b32 {%0,%1,%2,%3}, [%4];" : "=r"(v.x), "=r"(v.y), "=r"(v.z), "=r"(v.w) : "r"(a) : "memory"); return v;
}
__device__ __forceinline__ void sts16(uint32_t a, uint16_t v) { asm volatile("st.shared.b16 [%0], %1;" ::"r"(a), "h"(v) : "memory"); }
__device__ __forceinline__ void sts32f(uint32_t a, float v) { asm volatile("st.shared.f32 [%0], %1;" ::"r"(a), "f"(v) : "memory"); }
__device__ __forceinline__ void sts64f(uint32_t a, float x, float y) { asm volatile("st.shared.v2.f32 [%0], {%1,%2};" ::"r"(a), "f"(x), "f"(y) : "memory"); }
__device__ __forceinline__ void sts128(uint32_t a, uint32_t x, uint32_t y, uint32_t z, uint32_t w) {
  asm volatile("st.shared.v4.b32 [%0], {%1,%2,%3,%4};" ::"r"(a), "r"(x), "r"(y), "r"(z), "r"(w) : "memory");
}
__device__ __forceinline__ void ldsm4(uint32_t a, uint32_t& r0, uint32_t& r1, uint32_t& r2, uint32_t& r3) {
  asm volatile("ldmatrix.sync.aligned.m8n8.x4.shared.b16 {%0,%1,%2,%3}, [%4];" : "=r"(r0), "=r"(r1), "=r"(r2), "=r"(r3) : "r"(a) : "memory");
}
__device__ __forceinline__ void ldsm4t(uint32_t a, uint32_t& r0, uint32_t& r1, uint32_t& r2, uint32_t& r3) {
  asm volatile("ldmatrix.sync.aligned.m8n8.x4.trans.shared.b16 {%0,%1,%2,%3}, [%4];" : "=r"(r0), "=r"(r1), "=r"(r2), "=r"(r3) : "r"(a) : "memory");
}
__device__ __forceinline__ void mma_bf16(float* c, uint32_t a0, uint32_t a1, uint32_t a2, uint32_t a3, uint32_t b0, uint32_t b1) {
  asm("mma.sync.aligned.m16n8k16.row.col.f32.bf16.bf16.f32 {%0,%1,%2,%3},{%4,%5,%6,%7},{%8,%9},{%0,%1,%2,%3};"
      : "+f"(c[0]), "+f"(c[1]), "+f"(c[2]), "+f"(c[3]) : "r"(a0), "r"(a1), "r"(a2), "r"(a3), "r"(b0), "r"(b1));
}
__device__ __forceinline__ void stsm4(uint32_t a, uint32_t r0, uint32_t r1, uint32_t r2, uint32_t r3) {
  asm volatile("stmatrix.sync.aligned.m8n8.x4.shared.b16 [%0], {%1,%2,%3,%4};" ::"r"(a), "r"(r0), "r"(r1), "r"(r2), "r"(r3) : "memory");
}
__device__ __forceinline__ uint4 ld_relaxed4(const void* p) {
  uint4 v; asm volatile("ld.relaxed.gpu.global.v4.b32 {%0,%1,%2,%3}, [%4];" : "=r"(v.x), "=r"(v.y), "=r"(v.z), "=r"(v.w) : "l"(p) : "memory"); return v;
}
__device__ __forceinline__ void st_relaxed2(void* p, uint32_t x, uint32_t y) {
  asm volatile("st.relaxed.gpu.global.v2.b32 [%0], {%1,%2};" ::"l"(p), "r"(x), "r"(y) : "memory");
}
__device__ __forceinline__ uint4 ld_b128(const void* p) {
  uint4 v;
  asm volatile("{.reg .b128 t; .reg .b64 a, c; ld.relaxed.gpu.global.b128 t, [%4]; mov.b128 {a, c}, t; mov.b64 {%0,%1}, a; mov.b64 {%2,%3}, c;}"
               : "=r"(v.x), "=r"(v.y), "=r"(v.z), "=r"(v.w) : "l"(p) : "memory");
  return v;
}
__device__ __forceinline__ void st_b128(void* p, uint32_t x, uint32_t y, uint32_t z, uint32_t w) {
  asm volatile("{.reg .b128 t; .reg .b64 a, c; mov.b64 a, {%1,%2}; mov.b64 c, {%3,%4}; mov.b128 t, {a, c}; st.relaxed.gpu.global.b128 [%0], t;}"
               ::"l"(p), "r"(x), "r"(y), "r"(z), "r"(w) : "memory");
}
__device__ __forceinline__ unsigned ld_relaxed1(const unsigned* p) {
  unsigned v; asm volatile("ld.relaxed.gpu.global.u32 %0, [%1];" : "=r"(v) : "l"(p) : "memory"); return v;
}
__device__ __forceinline__ void st_relaxed1(unsigned* p, unsigned v) { asm volatile("st.relaxed.gpu.global.u32 [%0], %1;" ::"l"(p), "r"(v) : "memory"); }
__device__ __forceinline__ void wait_hint(const unsigned* p, unsigned v) {
#pragma unroll 1
  for (int it = 0; it < SPIN_MAX / 16; it++) {
    const uint4 q = ld_relaxed4(p);
    if (!__any_sync(0xffffffffu, (q.x ^ v) | (q.y ^ v) | (q.z ^ v) | (q.w ^ v))) break;
    __nanosleep(60);
  }
}
__device__ __forceinline__ void red_relaxed(unsigned* p) {
  asm volatile("red.relaxed.gpu.global.add.u32 [%0], 1;" ::"l"(p) : "memory");
}
__device__ __forceinline__ void wait_count(const unsigned* p, unsigned target) {
#pragma unroll 1
  for (int it = 0; it < SPIN_MAX; it++) {
    if ((int)(ld_relaxed1(p) - target) >= 0) break;
    __nanosleep(40);
  }
  asm volatile("fence.acq_rel.gpu;" ::: "memory");
}
__device__ __forceinline__ uint32_t pack_h2(float lo, float hi) { uint32_t r; asm("cvt.rn.f16x2.f32 %0, %1, %2;" : "=r"(r) : "f"(hi), "f"(lo)); return r; }
__device__ __forceinline__ uint32_t pack_bf2(float lo, float hi) { uint32_t r; asm("cvt.rn.bf16x2.f32 %0, %1, %2;" : "=r"(r) : "f"(hi), "f"(lo)); return r; }
__device__ __forceinline__ float bf_lo(uint32_t w) { return __uint_as_float(w << 16); }
__device__ __forceinline__ float bf_hi(uint32_t w) { return __uint_as_float(w & 0xffff0000u); }
__device__ __forceinline__ float rbf(float v) { return bf_hi(pack_bf2(0.f, v)); }
__device__ __forceinline__ float2 h2f(uint32_t w) { return __half22float2(*reinterpret_cast<__half2*>(&w)); }
__device__ __forceinline__ float ex2f(float v) { float r; asm("ex2.approx.ftz.f32 %0, %1;" : "=f"(r) : "f"(v)); return r; }
__device__ __forceinline__ float rcpf_(float v) { float r; asm("rcp.approx.ftz.f32 %0, %1;" : "=f"(r) : "f"(v)); return r; }
__device__ __forceinline__ float sqrtf_(float v) { float r; asm("sqrt.approx.ftz.f32 %0, %1;" : "=f"(r) : "f"(v)); return r; }
__device__ __forceinline__ float tanhf_(float v) { float r; asm volatile("tanh.approx.f32 %0, %1;" : "=f"(r) : "f"(v)); return r; }

__device__ __forceinline__ void wg_ss_bf16_n256(float* d, uint64_t da, uint64_t db, int sc) {
  asm volatile("{.reg .pred p; setp.ne.b32 p, %130, 0;\n"
    "wgmma.mma_async.sync.aligned.m64n256k16.f32.bf16.bf16 {%0, %1, %2, %3, %4, %5, %6, %7, %8, %9, %10, %11, %12, %13, %14, %15, %16, %17, %18, %19, %20, %21, %22, %23, %24, %25, %26, %27, %28, %29, %30, %31, %32, %33, %34, %35, %36, %37, %38, %39, %40, %41, %42, %43, %44, %45, %46, %47, %48, %49, %50, %51, %52, %53, %54, %55, %56, %57, %58, %59, %60, %61, %62, %63, %64, %65, %66, %67, %68, %69, %70, %71, %72, %73, %74, %75, %76, %77, %78, %79, %80, %81, %82, %83, %84, %85, %86, %87, %88, %89, %90, %91, %92, %93, %94, %95, %96, %97, %98, %99, %100, %101, %102, %103, %104, %105, %106, %107, %108, %109, %110, %111, %112, %113, %114, %115, %116, %117, %118, %119, %120, %121, %122, %123, %124, %125, %126, %127}, %128, %129, p, 1, 1, 0, 1;}\n"
    : "+f"(d[0]), "+f"(d[1]), "+f"(d[2]), "+f"(d[3]), "+f"(d[4]), "+f"(d[5]), "+f"(d[6]), "+f"(d[7]), "+f"(d[8]), "+f"(d[9]), "+f"(d[10]), "+f"(d[11]), "+f"(d[12]), "+f"(d[13]), "+f"(d[14]), "+f"(d[15]), "+f"(d[16]), "+f"(d[17]), "+f"(d[18]), "+f"(d[19]), "+f"(d[20]), "+f"(d[21]), "+f"(d[22]), "+f"(d[23]), "+f"(d[24]), "+f"(d[25]), "+f"(d[26]), "+f"(d[27]), "+f"(d[28]), "+f"(d[29]), "+f"(d[30]), "+f"(d[31]), "+f"(d[32]), "+f"(d[33]), "+f"(d[34]), "+f"(d[35]), "+f"(d[36]), "+f"(d[37]), "+f"(d[38]), "+f"(d[39]), "+f"(d[40]), "+f"(d[41]), "+f"(d[42]), "+f"(d[43]), "+f"(d[44]), "+f"(d[45]), "+f"(d[46]), "+f"(d[47]), "+f"(d[48]), "+f"(d[49]), "+f"(d[50]), "+f"(d[51]), "+f"(d[52]), "+f"(d[53]), "+f"(d[54]), "+f"(d[55]), "+f"(d[56]), "+f"(d[57]), "+f"(d[58]), "+f"(d[59]), "+f"(d[60]), "+f"(d[61]), "+f"(d[62]), "+f"(d[63]), "+f"(d[64]), "+f"(d[65]), "+f"(d[66]), "+f"(d[67]), "+f"(d[68]), "+f"(d[69]), "+f"(d[70]), "+f"(d[71]), "+f"(d[72]), "+f"(d[73]), "+f"(d[74]), "+f"(d[75]), "+f"(d[76]), "+f"(d[77]), "+f"(d[78]), "+f"(d[79]), "+f"(d[80]), "+f"(d[81]), "+f"(d[82]), "+f"(d[83]), "+f"(d[84]), "+f"(d[85]), "+f"(d[86]), "+f"(d[87]), "+f"(d[88]), "+f"(d[89]), "+f"(d[90]), "+f"(d[91]), "+f"(d[92]), "+f"(d[93]), "+f"(d[94]), "+f"(d[95]), "+f"(d[96]), "+f"(d[97]), "+f"(d[98]), "+f"(d[99]), "+f"(d[100]), "+f"(d[101]), "+f"(d[102]), "+f"(d[103]), "+f"(d[104]), "+f"(d[105]), "+f"(d[106]), "+f"(d[107]), "+f"(d[108]), "+f"(d[109]), "+f"(d[110]), "+f"(d[111]), "+f"(d[112]), "+f"(d[113]), "+f"(d[114]), "+f"(d[115]), "+f"(d[116]), "+f"(d[117]), "+f"(d[118]), "+f"(d[119]), "+f"(d[120]), "+f"(d[121]), "+f"(d[122]), "+f"(d[123]), "+f"(d[124]), "+f"(d[125]), "+f"(d[126]), "+f"(d[127])
    : "l"(da), "l"(db), "r"(sc));
}

__device__ __forceinline__ void wg_ss_bf16_n256k(float* d, uint64_t da, uint64_t db, int sc) {
  asm volatile("{.reg .pred p; setp.ne.b32 p, %130, 0;\n"
    "wgmma.mma_async.sync.aligned.m64n256k16.f32.bf16.bf16 {%0, %1, %2, %3, %4, %5, %6, %7, %8, %9, %10, %11, %12, %13, %14, %15, %16, %17, %18, %19, %20, %21, %22, %23, %24, %25, %26, %27, %28, %29, %30, %31, %32, %33, %34, %35, %36, %37, %38, %39, %40, %41, %42, %43, %44, %45, %46, %47, %48, %49, %50, %51, %52, %53, %54, %55, %56, %57, %58, %59, %60, %61, %62, %63, %64, %65, %66, %67, %68, %69, %70, %71, %72, %73, %74, %75, %76, %77, %78, %79, %80, %81, %82, %83, %84, %85, %86, %87, %88, %89, %90, %91, %92, %93, %94, %95, %96, %97, %98, %99, %100, %101, %102, %103, %104, %105, %106, %107, %108, %109, %110, %111, %112, %113, %114, %115, %116, %117, %118, %119, %120, %121, %122, %123, %124, %125, %126, %127}, %128, %129, p, 1, 1, 0, 0;}\n"
    : "+f"(d[0]), "+f"(d[1]), "+f"(d[2]), "+f"(d[3]), "+f"(d[4]), "+f"(d[5]), "+f"(d[6]), "+f"(d[7]), "+f"(d[8]), "+f"(d[9]), "+f"(d[10]), "+f"(d[11]), "+f"(d[12]), "+f"(d[13]), "+f"(d[14]), "+f"(d[15]), "+f"(d[16]), "+f"(d[17]), "+f"(d[18]), "+f"(d[19]), "+f"(d[20]), "+f"(d[21]), "+f"(d[22]), "+f"(d[23]), "+f"(d[24]), "+f"(d[25]), "+f"(d[26]), "+f"(d[27]), "+f"(d[28]), "+f"(d[29]), "+f"(d[30]), "+f"(d[31]), "+f"(d[32]), "+f"(d[33]), "+f"(d[34]), "+f"(d[35]), "+f"(d[36]), "+f"(d[37]), "+f"(d[38]), "+f"(d[39]), "+f"(d[40]), "+f"(d[41]), "+f"(d[42]), "+f"(d[43]), "+f"(d[44]), "+f"(d[45]), "+f"(d[46]), "+f"(d[47]), "+f"(d[48]), "+f"(d[49]), "+f"(d[50]), "+f"(d[51]), "+f"(d[52]), "+f"(d[53]), "+f"(d[54]), "+f"(d[55]), "+f"(d[56]), "+f"(d[57]), "+f"(d[58]), "+f"(d[59]), "+f"(d[60]), "+f"(d[61]), "+f"(d[62]), "+f"(d[63]), "+f"(d[64]), "+f"(d[65]), "+f"(d[66]), "+f"(d[67]), "+f"(d[68]), "+f"(d[69]), "+f"(d[70]), "+f"(d[71]), "+f"(d[72]), "+f"(d[73]), "+f"(d[74]), "+f"(d[75]), "+f"(d[76]), "+f"(d[77]), "+f"(d[78]), "+f"(d[79]), "+f"(d[80]), "+f"(d[81]), "+f"(d[82]), "+f"(d[83]), "+f"(d[84]), "+f"(d[85]), "+f"(d[86]), "+f"(d[87]), "+f"(d[88]), "+f"(d[89]), "+f"(d[90]), "+f"(d[91]), "+f"(d[92]), "+f"(d[93]), "+f"(d[94]), "+f"(d[95]), "+f"(d[96]), "+f"(d[97]), "+f"(d[98]), "+f"(d[99]), "+f"(d[100]), "+f"(d[101]), "+f"(d[102]), "+f"(d[103]), "+f"(d[104]), "+f"(d[105]), "+f"(d[106]), "+f"(d[107]), "+f"(d[108]), "+f"(d[109]), "+f"(d[110]), "+f"(d[111]), "+f"(d[112]), "+f"(d[113]), "+f"(d[114]), "+f"(d[115]), "+f"(d[116]), "+f"(d[117]), "+f"(d[118]), "+f"(d[119]), "+f"(d[120]), "+f"(d[121]), "+f"(d[122]), "+f"(d[123]), "+f"(d[124]), "+f"(d[125]), "+f"(d[126]), "+f"(d[127])
    : "l"(da), "l"(db), "r"(sc));
}

__device__ __forceinline__ void wg_rs_bf16_n64(float* d, uint32_t a0, uint32_t a1, uint32_t a2, uint32_t a3, uint64_t db, int sc) {
  asm volatile("{.reg .pred p; setp.ne.b32 p, %37, 0;\n"
    "wgmma.mma_async.sync.aligned.m64n64k16.f32.bf16.bf16 {%0, %1, %2, %3, %4, %5, %6, %7, %8, %9, %10, %11, %12, %13, %14, %15, %16, %17, %18, %19, %20, %21, %22, %23, %24, %25, %26, %27, %28, %29, %30, %31}, {%32,%33,%34,%35}, %36, p, 1, 1, 1;}\n"
    : "+f"(d[0]), "+f"(d[1]), "+f"(d[2]), "+f"(d[3]), "+f"(d[4]), "+f"(d[5]), "+f"(d[6]), "+f"(d[7]), "+f"(d[8]), "+f"(d[9]), "+f"(d[10]), "+f"(d[11]), "+f"(d[12]), "+f"(d[13]), "+f"(d[14]), "+f"(d[15]), "+f"(d[16]), "+f"(d[17]), "+f"(d[18]), "+f"(d[19]), "+f"(d[20]), "+f"(d[21]), "+f"(d[22]), "+f"(d[23]), "+f"(d[24]), "+f"(d[25]), "+f"(d[26]), "+f"(d[27]), "+f"(d[28]), "+f"(d[29]), "+f"(d[30]), "+f"(d[31])
    : "r"(a0), "r"(a1), "r"(a2), "r"(a3), "l"(db), "r"(sc));
}

__device__ __forceinline__ void wg_rs_f16_n64k(float* d, uint32_t a0, uint32_t a1, uint32_t a2, uint32_t a3, uint64_t db, int sc) {
  asm volatile("{.reg .pred p; setp.ne.b32 p, %37, 0;\n"
    "wgmma.mma_async.sync.aligned.m64n64k16.f32.f16.f16 {%0, %1, %2, %3, %4, %5, %6, %7, %8, %9, %10, %11, %12, %13, %14, %15, %16, %17, %18, %19, %20, %21, %22, %23, %24, %25, %26, %27, %28, %29, %30, %31}, {%32,%33,%34,%35}, %36, p, 1, 1, 0;}\n"
    : "+f"(d[0]), "+f"(d[1]), "+f"(d[2]), "+f"(d[3]), "+f"(d[4]), "+f"(d[5]), "+f"(d[6]), "+f"(d[7]), "+f"(d[8]), "+f"(d[9]), "+f"(d[10]), "+f"(d[11]), "+f"(d[12]), "+f"(d[13]), "+f"(d[14]), "+f"(d[15]), "+f"(d[16]), "+f"(d[17]), "+f"(d[18]), "+f"(d[19]), "+f"(d[20]), "+f"(d[21]), "+f"(d[22]), "+f"(d[23]), "+f"(d[24]), "+f"(d[25]), "+f"(d[26]), "+f"(d[27]), "+f"(d[28]), "+f"(d[29]), "+f"(d[30]), "+f"(d[31])
    : "r"(a0), "r"(a1), "r"(a2), "r"(a3), "l"(db), "r"(sc));
}

__device__ __forceinline__ void wg_rs_f16_n24t(float* d, uint32_t a0, uint32_t a1, uint32_t a2, uint32_t a3, uint64_t db, int sc) {
  asm volatile("{.reg .pred p; setp.ne.b32 p, %17, 0;\n"
    "wgmma.mma_async.sync.aligned.m64n24k16.f32.f16.f16 {%0, %1, %2, %3, %4, %5, %6, %7, %8, %9, %10, %11}, {%12,%13,%14,%15}, %16, p, 1, 1, 1;}\n"
    : "+f"(d[0]), "+f"(d[1]), "+f"(d[2]), "+f"(d[3]), "+f"(d[4]), "+f"(d[5]), "+f"(d[6]), "+f"(d[7]), "+f"(d[8]), "+f"(d[9]), "+f"(d[10]), "+f"(d[11])
    : "r"(a0), "r"(a1), "r"(a2), "r"(a3), "l"(db), "r"(sc));
}

__device__ __forceinline__ void wg_rs_f16_n16t(float* d, uint32_t a0, uint32_t a1, uint32_t a2, uint32_t a3, uint64_t db, int sc) {
  asm volatile("{.reg .pred p; setp.ne.b32 p, %13, 0;\n"
    "wgmma.mma_async.sync.aligned.m64n16k16.f32.f16.f16 {%0, %1, %2, %3, %4, %5, %6, %7}, {%8,%9,%10,%11}, %12, p, 1, 1, 1;}\n"
    : "+f"(d[0]), "+f"(d[1]), "+f"(d[2]), "+f"(d[3]), "+f"(d[4]), "+f"(d[5]), "+f"(d[6]), "+f"(d[7])
    : "r"(a0), "r"(a1), "r"(a2), "r"(a3), "l"(db), "r"(sc));
}

__device__ __forceinline__ void wg_ss_f16_n48t(float* d, uint64_t da, uint64_t db, int sc) {
  asm volatile("{.reg .pred p; setp.ne.b32 p, %26, 0;\n"
    "wgmma.mma_async.sync.aligned.m64n48k16.f32.f16.f16 {%0, %1, %2, %3, %4, %5, %6, %7, %8, %9, %10, %11, %12, %13, %14, %15, %16, %17, %18, %19, %20, %21, %22, %23}, %24, %25, p, 1, 1, 1, 1;}\n"
    : "+f"(d[0]), "+f"(d[1]), "+f"(d[2]), "+f"(d[3]), "+f"(d[4]), "+f"(d[5]), "+f"(d[6]), "+f"(d[7]), "+f"(d[8]), "+f"(d[9]), "+f"(d[10]), "+f"(d[11]), "+f"(d[12]), "+f"(d[13]), "+f"(d[14]), "+f"(d[15]), "+f"(d[16]), "+f"(d[17]), "+f"(d[18]), "+f"(d[19]), "+f"(d[20]), "+f"(d[21]), "+f"(d[22]), "+f"(d[23])
    : "l"(da), "l"(db), "r"(sc));
}

__device__ __forceinline__ void wg_rs_bf16_n16k(float* d, uint32_t a0, uint32_t a1, uint32_t a2, uint32_t a3, uint64_t db, int sc) {
  asm volatile("{.reg .pred p; setp.ne.b32 p, %13, 0;\n"
    "wgmma.mma_async.sync.aligned.m64n16k16.f32.bf16.bf16 {%0, %1, %2, %3, %4, %5, %6, %7}, {%8,%9,%10,%11}, %12, p, 1, 1, 0;}\n"
    : "+f"(d[0]), "+f"(d[1]), "+f"(d[2]), "+f"(d[3]), "+f"(d[4]), "+f"(d[5]), "+f"(d[6]), "+f"(d[7])
    : "r"(a0), "r"(a1), "r"(a2), "r"(a3), "l"(db), "r"(sc));
}

__device__ __forceinline__ void send_tile(void* dst, uint32_t tag, const float* a) {
  asm volatile(
    "{.reg .b32 w<16>;\n"
    "cvt.rn.bf16x2.f32 w0, %3, %2;\n"
    "cvt.rn.bf16x2.f32 w1, %5, %4;\n"
    "cvt.rn.bf16x2.f32 w2, %7, %6;\n"
    "cvt.rn.bf16x2.f32 w3, %9, %8;\n"
    "cvt.rn.bf16x2.f32 w4, %11, %10;\n"
    "cvt.rn.bf16x2.f32 w5, %13, %12;\n"
    "cvt.rn.bf16x2.f32 w6, %15, %14;\n"
    "cvt.rn.bf16x2.f32 w7, %17, %16;\n"
    "cvt.rn.bf16x2.f32 w8, %19, %18;\n"
    "cvt.rn.bf16x2.f32 w9, %21, %20;\n"
    "cvt.rn.bf16x2.f32 w10, %23, %22;\n"
    "cvt.rn.bf16x2.f32 w11, %25, %24;\n"
    "cvt.rn.bf16x2.f32 w12, %27, %26;\n"
    "cvt.rn.bf16x2.f32 w13, %29, %28;\n"
    "cvt.rn.bf16x2.f32 w14, %31, %30;\n"
    "cvt.rn.bf16x2.f32 w15, %33, %32;\n"
    "lop3.b32 w0, w0, 1, %1, 0xb8;\n"
    "lop3.b32 w4, w4, 1, %1, 0xb8;\n"
    "lop3.b32 w8, w8, 1, %1, 0xb8;\n"
    "lop3.b32 w12, w12, 1, %1, 0xb8;\n"
    "st.relaxed.gpu.global.v4.b32 [%0+0], {w0, w1, w2, w3};\n"
    "st.relaxed.gpu.global.v4.b32 [%0+2048], {w4, w5, w6, w7};\n"
    "st.relaxed.gpu.global.v4.b32 [%0+4096], {w8, w9, w10, w11};\n"
    "st.relaxed.gpu.global.v4.b32 [%0+6144], {w12, w13, w14, w15};\n"
    "}\n"
    ::"l"(dst), "r"(tag), "f"(a[0]), "f"(a[1]), "f"(a[2]), "f"(a[3]), "f"(a[4]), "f"(a[5]), "f"(a[6]), "f"(a[7]), "f"(a[8]), "f"(a[9]), "f"(a[10]), "f"(a[11]), "f"(a[12]), "f"(a[13]), "f"(a[14]), "f"(a[15]), "f"(a[16]), "f"(a[17]), "f"(a[18]), "f"(a[19]), "f"(a[20]), "f"(a[21]), "f"(a[22]), "f"(a[23]), "f"(a[24]), "f"(a[25]), "f"(a[26]), "f"(a[27]), "f"(a[28]), "f"(a[29]), "f"(a[30]), "f"(a[31]) : "memory");
}

struct cf { float x, y; };
__device__ __forceinline__ cf cmul(cf a, cf b) { cf r; r.x = fmaf(a.x, b.x, -a.y * b.y); r.y = fmaf(a.x, b.y, a.y * b.x); return r; }
__device__ __forceinline__ cf zpow(float rho2, float phi, float e) {
  const float m = ex2f(rho2 * e), ang = phi * e;
  cf r; r.x = m * __cosf(ang); r.y = m * __sinf(ang); return r;
}
__device__ __forceinline__ __half2 H2(uint32_t v) { return *reinterpret_cast<__half2*>(&v); }
__device__ __forceinline__ uint32_t U32(__half2 v) { return *reinterpret_cast<uint32_t*>(&v); }
struct h2c { __half2 x, y; };
template <bool CONJ>
__device__ __forceinline__ void hprod2(uint32_t re, uint32_t im, h2c r, uint32_t& ore, uint32_t& oim) {
  if (CONJ) {
    ore = U32(__hfma2(H2(re), r.x, __hmul2(H2(im), r.y)));
    oim = U32(__hfma2(H2(im), r.x, __hneg2(__hmul2(H2(re), r.y))));
  } else {
    ore = U32(__hfma2(H2(re), r.x, __hneg2(__hmul2(H2(im), r.y))));
    oim = U32(__hfma2(H2(re), r.y, __hmul2(H2(im), r.x)));
  }
}
__device__ __forceinline__ cf csq(cf a) { cf r; r.x = fmaf(a.x, a.x, -a.y * a.y); r.y = (a.x + a.x) * a.y; return r; }
__device__ __forceinline__ cf cmulc(cf a, cf b) { cf r; r.x = fmaf(a.x, b.x, a.y * b.y); r.y = fmaf(a.y, b.x, -a.x * b.y); return r; }
__device__ __forceinline__ h2c pk(cf a) { h2c r; const __half2 q = H2(pack_h2(a.x, a.y)); r.x = __low2half2(q); r.y = __high2half2(q); return r; }
__device__ __forceinline__ uint32_t ldg32(const void* p, int o) { uint32_t v; asm volatile("ld.global.nc.b32 %0, [%1];" : "=r"(v) : "l"((const char*)p + o)); return v; }
__device__ __forceinline__ uint32_t hadd2u(uint32_t a, uint32_t b) { return U32(__hadd2(H2(a), H2(b))); }

struct KgIn { uint32_t cur[6], nxt[6], ldt, dk; };
__device__ __forceinline__ float pow2_floor(float v) { return __uint_as_float(__float_as_uint(fminf(fmaxf(v, 1e-30f), 1e30f)) & 0x7f800000u); }
template <class Mid>
__device__ __forceinline__ void kgen_wg(KgIn& k, bool odd, int nw, uint32_t stg, uint32_t dmp, uint32_t mxa, int w, int lane, int barid,
                                        int ebar, int ecnt, Mid mid) {
  const float dt = fmaxf(rbf(ex2f((odd ? bf_hi(k.ldt) : bf_lo(k.ldt)) * 1.4426950408889634f)), 1e-30f), dl = dt * 1.4426950408889634f;
  const float dsk = (odd ? bf_hi(k.dk) : bf_lo(k.dk)) * rcpf_(dt);
  {
    const uint32_t M = 0x7fff7fffu;
    uint32_t mx[2];
#pragma unroll
    for (int i = 0; i < 2; i++) {
      const uint32_t m = __vmaxu2(__vmaxu2(k.cur[2 + 2 * i] & M, k.cur[3 + 2 * i] & M), __vmaxu2(k.nxt[2 + 2 * i] & M, k.nxt[3 + 2 * i] & M));
      mx[i] = __reduce_max_sync(0xffffffffu, max(m << 16, m & 0xffff0000u));
    }
    if (lane == 0) sts32f(mxa + w * 4, __uint_as_float(mx[0]) * __uint_as_float(mx[1]));
    mid(-1);
  }
  const uint32_t sa = stg + (w >> 1) * 8192 + (32 * (w & 1) + lane) * 16, sc_ = sa + 16384 - (w >> 1) * 2048;
  const uint64_t dA = mkdesc(stg, 128, 2048, 0), dB = mkdesc(stg + 16384, 128, 2048, 0);
  float acc[24], sc = 0.f;
#pragma unroll
  for (int i = 0; i < 24; i++) acc[i] = 0.f;
  fence_regs<24>(acc);
#pragma unroll 1
  for (int it = 0; it < 2 * nw; it++) {
    const uint32_t sel = (it & 1) ? 0x3244u : 0x1044u;
    float v[6];
#pragma unroll
    for (int i = 0; i < 6; i++) { v[i] = __uint_as_float(__byte_perm(k.cur[i], 0, sel)); if (it == 1) k.cur[i] = k.nxt[i]; }
    const float rho2 = v[0] * dl, phi = v[1] * dt;
    const cf z1 = zpow(rho2, phi, 1.f), z8 = zpow(rho2, phi, 8.f), z64 = zpow(rho2, phi, 64.f);
    const cf z16 = csq(z8), z24 = cmul(z16, z8), z32 = csq(z16), z128 = csq(z64);
    uint32_t re[4], im[4], r2[4], i2[4], r3[4], i3[4];
    re[0] = pack_h2(1.f, z32.x); im[0] = pack_h2(0.f, z32.y);
    hprod2<false>(re[0], im[0], pk(z8), re[1], im[1]);
    hprod2<false>(re[0], im[0], pk(z16), re[2], im[2]);
    hprod2<false>(re[0], im[0], pk(z24), re[3], im[3]);
    asm volatile("" : "+r"(re[1]), "+r"(im[1]), "+r"(re[2]), "+r"(im[2]), "+r"(re[3]), "+r"(im[3]) :: "memory");
    wg_wait<0>();
    bar_sync(barid, 128);
    sts128(sa, re[0], re[1], re[2], re[3]);
    sts128(sa + 1024, im[0], im[1], im[2], im[3]);
    const float2 m0 = lds64f(mxa + (w & 2) * 4), m1 = lds64f(mxa + (nw == 1 ? (w & 2) ^ 2 : (w & 2)) * 4);
    const h2c h64 = pk(z64), h128 = pk(z128);
#pragma unroll
    for (int j = 0; j < 4; j++) hprod2<false>(re[j], im[j], h64, r2[j], i2[j]);
    sts128(sa + 2048, r2[0], r2[1], r2[2], r2[3]);
    sts128(sa + 3072, i2[0], i2[1], i2[2], i2[3]);
#pragma unroll
    for (int j = 0; j < 4; j++) hprod2<false>(re[j], im[j], h128, r3[j], i3[j]);
    sts128(sa + 4096, r3[0], r3[1], r3[2], r3[3]);
    sts128(sa + 5120, i3[0], i3[1], i3[2], i3[3]);
    uint32_t r4[4], i4[4];
#pragma unroll
    for (int j = 0; j < 4; j++) hprod2<false>(r2[j], i2[j], h128, r4[j], i4[j]);
    sts128(sa + 6144, r4[0], r4[1], r4[2], r4[3]);
    sts128(sa + 7168, i4[0], i4[1], i4[2], i4[3]);
    sc = pow2_floor(fmaxf(0.125f * fmaxf(fmaxf(m0.x, m0.y), fmaxf(m1.x, m1.y)), fabsf(dsk) * (1.f / 4096.f)));
    const float inv_sc = __uint_as_float(0x7f000000u - __float_as_uint(sc));
    const cf bb = {v[2] * inv_sc, v[3] * -inv_sc}, cc = {v[4], v[5]};
    const cf X0 = cmulc(bb, cc);
    const cf z2 = csq(z1), z3 = cmul(z2, z1), z4 = csq(z2), X4 = cmulc(X0, z4);
    uint32_t g0[4], j0[4], g1[4], j1[4];
    g0[0] = pack_h2(X0.x, X4.x); j0[0] = pack_h2(X0.y, X4.y);
    hprod2<true>(g0[0], j0[0], pk(z1), g0[1], j0[1]);
    hprod2<true>(g0[0], j0[0], pk(z2), g0[2], j0[2]);
    hprod2<true>(g0[0], j0[0], pk(z3), g0[3], j0[3]);
    sts128(sc_, g0[0], g0[1], g0[2], g0[3]);
    sts128(sc_ + 1024, j0[0], j0[1], j0[2], j0[3]);
    const cf y1 = csq(z128), y2 = csq(y1), y3 = cmul(y2, y1), y4 = csq(y2);
    const h2c hy1 = pk(y1), hy2 = pk(y2);
    hprod2<true>(g0[0], j0[0], hy1, g1[0], j1[0]);
    hprod2<true>(g0[2], j0[2], hy1, g1[1], j1[1]);
    hprod2<true>(g0[0], j0[0], hy2, g1[2], j1[2]);
    hprod2<true>(g0[0], j0[0], pk(y3), g1[3], j1[3]);
    sts128(sc_ + 2048, g1[0], g1[1], g1[2], g1[3]);
    sts128(sc_ + 3072, j1[0], j1[1], j1[2], j1[3]);
    const cf W4 = cmulc(X0, y4), W8 = cmulc(W4, y4), W5 = cmulc(W4, y1);
    uint32_t g2[2], j2[2];
    g2[0] = pack_h2(W4.x, W5.x); j2[0] = pack_h2(W4.y, W5.y);
    hprod2<true>(g2[0], j2[0], hy2, g2[1], j2[1]);
    sts128(sc_ + 4096, g2[0], g2[1], pack_h2(W8.x, 0.f), 0u);
    sts128(sc_ + 5120, j2[0], j2[1], pack_h2(W8.y, 0.f), 0u);
    fence_async();
    bar_sync(barid, 128);
    wg_fence();
#pragma unroll
    for (int ks = 0; ks < 8; ks++) wg_ss_f16_n48t(acc, dA + 16 * ks, dB + 16 * ks, 1);
    wg_commit();
    mid(it);
  }
  const float os = dt * sc, skip = dsk * rcpf_(sc);
  wg_wait<0>();
  fence_regs<24>(acc);
  bar_sync(ebar, ecnt);
  if (lane == 0) sts64f(dmp + 6144 + (w >> 1) * 8, os, skip);
#pragma unroll
  for (int h = 0; h < 2; h++)
#pragma unroll
    for (int nt = 0; nt < 3; nt++) {
      const int i = 4 * nt + 2 * h;
      sts64f(dmp + (w * 2 + h) * 768 + nt * 256 + lane * 8, (w & 2) ? acc[12 + i] : acc[i], (w & 2) ? acc[13 + i] : acc[1 + i]);
    }
}

__device__ __forceinline__ void tput(uint32_t tbl, int X, uint32_t h) {
  sts16(tbl + 2 * (1296 - X), (uint16_t)h);
  sts16(tbl + TBL_C1 + 2 * (1297 - X), (uint16_t)h);
}
__device__ __forceinline__ void ktab_build(uint32_t src, uint32_t sca, bool two, int q, uint32_t tbl, int lane) {
  const int tq = lane & 3, r = 8 * q + (lane >> 3) + ((lane >> 2) & 1) * 4;
  float v[6];
  src += q * 768 + lane * 8;
#pragma unroll
  for (int nt = 0; nt < 3; nt++) {
    const float2 a = lds64f(src + nt * 256);
    v[2 * nt] = a.x; v[2 * nt + 1] = a.y;
    if (two) { const float2 c = lds64f(src + nt * 256 + 3072); v[2 * nt] += c.x; v[2 * nt + 1] += c.y; }
  }
  const bool first = (r == 0);
  if (first && tq == 0) { const float2 sc = lds64f(sca); v[0] += sc.y; sts64f(tbl + TBL_SC, v[4], sc.x); }
  const uint32_t h0 = pack_h2(v[0], v[1]), h1 = pack_h2(v[2], v[3]), h2 = pack_h2(v[4], v[5]);
  const bool lo = tq < 2, sp = first && tq == 2, tri = tq == 0;
  const int k2 = 32 * (tq - 2) + r;
  const int Xa = lo ? 320 + 8 * r + 2 * tq : (sp ? 576 : 911 + k2), Xb = lo ? Xa + 4 : 720 + k2;
  const int X3 = ((r & 1) ? 1104 : 1231) + 32 * tq + (r >> 1);
  tput(tbl, 64 + 8 * r + tq, h0);
  tput(tbl, 68 + 8 * r + tq, h0 >> 16);
  tput(tbl, Xa, h1);
  tput(tbl, Xb, h1 >> 16);
  tput(tbl, (tri || sp) ? Xa + 1 : 4, h1);
  tput(tbl, ((tri && !first) || sp) ? Xa - 1 : 4, h1);
  tput(tbl, tri ? Xb + 1 : (sp ? 578 : 4), sp ? h1 : h1 >> 16);
  tput(tbl, tri ? Xb - 1 : 4, h1 >> 16);
  tput(tbl, lo ? (X3 == 1231 ? 975 : X3) : (sp ? 1295 : 4), h2);
  tput(tbl, lo ? X3 + 16 : 4, h2 >> 16);
}

__device__ __forceinline__ void sig_store(uint32_t sig, int t, const uint4* v) {
  sts128(sig + SIG_V3 - 1024 + (t >> 6) * 4096 + (t & 63) * 16, 0u, 0u, 0u, 0u);
  const uint32_t a = sig + SIG_U + (t & 3) * U_LBO + (t >> 2) * 16;
  if (t < 64) sts128(a, 0u, 0u, 0u, 0u);
#pragma unroll
  for (int q = 0; q < 2; q++) sts128(a + 256 + q * 512, v[q].x & ~1u, v[q].y & ~1u, v[q].z & ~1u, v[q].w & ~1u);
}
__device__ __forceinline__ void sig_windows(uint32_t sig, int t) {
  uint32_t U[20];
#pragma unroll
  for (int c = 0; c < 5; c++) {
    const int kap = 2 * t - 3 + c + 64;
    const uint4 v = lds128(sig + SIG_U + (kap & 3) * U_LBO + (kap >> 2) * 16);
    U[4 * c] = v.x; U[4 * c + 1] = v.y; U[4 * c + 2] = v.z; U[4 * c + 3] = v.w;
  }
  uint32_t O[19], A2[17], A4[17], V2[8], V5[8];
#pragma unroll
  for (int i = 3; i < 19; i++) O[i] = __byte_perm(U[i - 1], U[i], 0x5432);
#pragma unroll
  for (int i = 3; i < 17; i++) A2[i] = hadd2u(U[i], O[i]);
#pragma unroll
  for (int i = 4; i < 17; i++) A4[i] = hadd2u(A2[i], A2[i - 1]);
#pragma unroll
  for (int k = 0; k < 8; k++) { V2[k] = hadd2u(O[11 + k], U[10 + k]); V5[k] = hadd2u(A4[9 + k], U[7 + k]); }
#pragma unroll
  for (int h = 0; h < 2; h++) {
    sts128(sig + SIG_V3 + t * 32 + h * 16, hadd2u(V2[4 * h], O[10 + 4 * h]), hadd2u(V2[4 * h + 1], O[11 + 4 * h]),
           hadd2u(V2[4 * h + 2], O[12 + 4 * h]), hadd2u(V2[4 * h + 3], O[13 + 4 * h]));
    sts128(sig + SIG_V5 + t * 32 + h * 16, V5[4 * h], V5[4 * h + 1], V5[4 * h + 2], V5[4 * h + 3]);
  }
  if (t < 64) {
    uint32_t V7[8], V9[8];
#pragma unroll
    for (int k = 0; k < 8; k++) {
      V7[k] = hadd2u(V5[k], hadd2u(O[10 + k], O[7 + k]));
      V9[k] = hadd2u(hadd2u(A4[6 + k], A4[4 + k]), U[2 + k]);
    }
#pragma unroll
    for (int h = 0; h < 2; h++) {
      sts128(sig + SIG_V7 + h * 1024 + t * 16, V7[4 * h], V7[4 * h + 1], V7[4 * h + 2], V7[4 * h + 3]);
      sts128(sig + SIG_V9 + h * 1024 + t * 16, V9[4 * h], V9[4 * h + 1], V9[4 * h + 2], V9[4 * h + 3]);
      sts128(sig + SIG_V2 + h * 1024 + t * 16, V2[4 * h], V2[4 * h + 1], V2[4 * h + 2], V2[4 * h + 3]);
    }
  }
}

__device__ __forceinline__ void conv_channel(uint32_t tbl, uint32_t sig, float k1024, int w, int lane, int barid, float* res) {
  const int g = lane >> 2, tq = lane & 3;
  const uint32_t tb = tbl + ((g & 1) ? TBL_C1 + 2 : 0) + 2 * (1296 - (g - 2 * tq)) - 32 * w + 112;
  float ad[32], a2[12], a3[8];
#pragma unroll
  for (int i = 0; i < 32; i++) ad[i] = 0.f;
#pragma unroll
  for (int i = 0; i < 12; i++) a2[i] = 0.f;
#pragma unroll
  for (int q = 0; q < 4; q++) {
    const float2 f = h2f(lds32(sig + SIG_V2 + (q >> 1) * 1024 + (16 * w + 8 * (q & 1) + g) * 16 + tq * 4));
    a3[2 * q] = k1024 * f.x;
    a3[2 * q + 1] = k1024 * f.y;
  }
  const uint32_t sigu = __shfl_sync(0xffffffffu, opaque(sig), 0);
  const uint64_t dU = mkdesc(sigu + SIG_U, U_LBO, 128, 0);
  const uint64_t dV = mkdesc(sigu, 128, 1024, 0);
  fence_regs<32>(ad); fence_regs<12>(a2); fence_regs<8>(a3);
  constexpr int LB = 2 * U_LBO / 16;
  uint32_t Rd[30], R2[26], R3[14];
  uint32_t td = tb - 192, t2 = tb - 1440, t3 = tb - 2208;
  uint64_t dd = dU + 16, d2 = dV + (SIG_V3 + 768) / 16, d3 = dV + (SIG_V7 + 768) / 16;
  auto load_group = [&](int gi) {
    const int bd = 5 * (gi >> 1);
#pragma unroll
    for (int i = (gi & 1) ? 3 : 0; i < ((gi & 1) ? 5 : 3); i++) Rd[bd + i] = lds32(td - 128 * (gi >> 1) - 16 * i);
    const int e = gi >> 3;
    if ((gi & 7) == 0) { R2[2 * gi + e] = lds32(t2 - 384 * e); R3[gi + e] = lds32(t3 - 256 * e); }
    R2[2 * gi + e + 1] = lds32(t2 - 384 * e - 16 * (2 * (gi & 7) + 1));
    R2[2 * gi + e + 2] = lds32(t2 - 384 * e - 16 * (2 * (gi & 7) + 2));
    if (!(gi & 1)) {
      R3[gi + e + 1] = lds32(t3 - 256 * e - 16 * ((gi & 7) + 1));
      R3[gi + e + 2] = lds32(t3 - 256 * e - 16 * ((gi & 7) + 2));
    }
  };
  auto dense = [&](int gi) {
    const int m = 5 * (gi >> 1) + 1 + 2 * (gi & 1);
    wg_rs_f16_n64k(ad, Rd[m], Rd[m + 1], Rd[m - 1], Rd[m], dd + ((1 - (gi & 1)) * LB + 8 - 2 * (gi >> 1)) - 8, 1);
  };
#pragma unroll
  for (int gi = 0; gi < 4; gi++) load_group(gi);
#pragma unroll 1
  for (int sg = 0; sg < 2; sg++) {
#pragma unroll
    for (int gi = 0; gi < 8; gi++) {
      if (!(gi & 1)) wg_fence();
      dense(gi);
      wg_rs_f16_n24t(a2, R2[2 * gi + 1], R2[2 * gi + 2], R2[2 * gi], R2[2 * gi + 1], d2 - (16 * (gi & 3) + 64 * (gi >> 2)), 1);
      if (!(gi & 1)) wg_rs_f16_n16t(a3, R3[gi + 1], R3[gi + 2], R3[gi], R3[gi + 1], d3 - 8 * gi, 1);
      if (gi & 1) {
        wg_commit();
        wg_wait<1>();
        load_group(gi + 3);
        load_group(gi + 4);
      }
    }
#pragma unroll
    for (int i = 0; i < 10; i++) Rd[i] = Rd[20 + i];
#pragma unroll
    for (int i = 0; i < 9; i++) R2[i] = R2[17 + i];
#pragma unroll
    for (int i = 0; i < 5; i++) R3[i] = R3[9 + i];
    td -= 512; t2 -= 384; t3 -= 256;
    dd -= 8; d2 += 256; d3 += 128;
  }
  wg_fence();
  dense(0);
  dense(1);
  wg_commit();
  wg_wait<1>();
  fence_regs<12>(a2); fence_regs<8>(a3);
  const uint32_t y3b = sig - YB, y2b = y3b + Y3B, ydb = sig + SIG_V3;
  {
    const uint32_t o2 = y2b + (144 * w + 8 * g + 2 * tq) * 4, o3 = y3b + (288 * w + 16 * g + 8 * (g >> 2) + 2 * tq) * 4;
#pragma unroll
    for (int q = 0; q < 6; q++) sts64f(o2 + (576 * (q >> 1) + 72 * (q & 1)) * 4, a2[2 * q], a2[2 * q + 1]);
#pragma unroll
    for (int q = 0; q < 4; q++) sts64f(o3 + (8 * (q >> 1) + 144 * (q & 1)) * 4, a3[2 * q], a3[2 * q + 1]);
  }
  bar_sync(barid, 128);
  const uint32_t go = (72 * tq + 16 * w + g) * 4;
  float ex[12];
#pragma unroll
  for (int i = 0; i < 12; i++) {
    const int o = 288 * (i >> 1) + 8 * (i & 1);
    ex[i] = lds32f(y2b + go + o * 4);
    if (i >= 4) ex[i] += lds32f(y3b + go + (o - 576) * 4);
  }
  wg_wait<0>();
  fence_regs<32>(ad);
#pragma unroll
  for (int nt = 0; nt < 8; nt++) sts64f(ydb + (4 * nt + tq + (w >> 1)) * 288 + (w ^ 2) * 64 + g * 8, ad[4 * nt + 1], ad[4 * nt + 3]);
  bar_sync(barid, 128);
#pragma unroll
  for (int nt = 0; nt < 8; nt++) {
    float2 o = lds64f(ydb + (4 * nt + tq) * 288 + w * 64 + g * 8);
    if (nt == 0 && tq == 0 && w < 2) o = make_float2(0.f, 0.f);
    res[2 * nt] = ad[4 * nt] + o.x + (nt >= 2 ? ex[2 * nt - 4] : 0.f);
    res[2 * nt + 1] = ad[4 * nt + 2] + o.y + (nt >= 2 ? ex[2 * nt - 3] : 0.f);
  }
}

__device__ __forceinline__ void ln_block(Scratch* sc, uint32_t xs, int rb, uint32_t red, uint32_t ep1, int w, int lane) {
  const uint32_t tag = ep1 & 1;
  uint32_t u[28];
  const int row = (lane & 1) + 2 * (lane & 6) + ((lane >> 2) & 2);
#pragma unroll
  for (int k = 0; k < 7; k++) {
    const int db = 14 * w + 2 * k + (lane >> 4);
    ldsm4t(xs + (db >> 3) * 2048 + row * 128 + (((db ^ row) & 7) << 4), u[4 * k], u[4 * k + 1], u[4 * k + 2], u[4 * k + 3]);
  }
  float f[56], s[8];
#pragma unroll
  for (int k = 0; k < 8; k++) s[k] = 0.f;
#pragma unroll
  for (int i = 0; i < 56; i++) {
    f[i] = (i & 1) ? bf_hi(u[i >> 1]) : bf_lo(u[i >> 1]);
    s[2 * (i & 3)] += f[i];
    s[2 * (i & 3) + 1] = fmaf(f[i], f[i], s[2 * (i & 3) + 1]);
  }
#pragma unroll
  for (int st = 0; st < 3; st++) {
    const int n = 4 >> st;
    const bool up = (lane >> (4 - st)) & 1;
#pragma unroll
    for (int k = 0; k < n; k++) {
      const float give = up ? s[k] : s[k + n], keep = up ? s[k + n] : s[k];
      s[k] = keep + __shfl_xor_sync(0xffffffffu, give, 16 >> st);
    }
  }
  const int g = lane >> 2, tq = lane & 3;
  sts32f(red + ((tq * 8 + g) * 4 + w) * 4, s[0]);
  bar_arrive(8, 384);
  bar_sync(6, 128);
  const uint4 ps = lds128(red + (tq * 8 + 2 * (g & 3)) * 16), pq = lds128(red + (tq * 8 + 2 * (g & 3) + 1) * 16);
  const float mean = ((__uint_as_float(ps.x) + __uint_as_float(ps.y)) + (__uint_as_float(ps.z) + __uint_as_float(ps.w))) * (1.f / D_);
  const float var = fmaxf(fmaf(-mean, mean, ((__uint_as_float(pq.x) + __uint_as_float(pq.y)) + (__uint_as_float(pq.z) + __uint_as_float(pq.w))) * (1.f / D_)), 0.f);
  const float m1 = rbf(mean), den = rbf(sqrtf_(rbf(rbf(var) + 1e-5f))), rr = rcpf_(den);
  float rd[4], nm[4];
#pragma unroll
  for (int r = 0; r < 4; r++) { rd[r] = __shfl_sync(0xffffffffu, rr, 4 * r + tq); nm[r] = __shfl_sync(0xffffffffu, -m1 * rr, 4 * r + tq); }
  if (rb < 128) {
    uint2* dst = (uint2*)(sc->xnT + (uint32_t)((56 * w + (lane >> 3)) * 512 + 4 * rb)) + (lane & 7);
#pragma unroll
    for (int k = 0; k < 14; k++)
      st_relaxed2(dst + k * 4096, (pack_h2(fmaf(f[4 * k], rd[0], nm[0]), fmaf(f[4 * k + 1], rd[1], nm[1])) & ~1u) | tag,
                  (pack_h2(fmaf(f[4 * k + 2], rd[2], nm[2]), fmaf(f[4 * k + 3], rd[3], nm[3])) & ~1u) | tag);
    if (w == 3 && lane < 16) {
      const float m2 = rbf((mean - m1) * rr), den2 = rbf(sqrtf_(rbf(rbf(var * rr * rr) + 1e-5f)));
      const float ir = den * den2, mu = fmaf(m2, den, m1);
      const float ih = rbf(ir), mh = rbf(mu);
      const uint32_t mm = pack_bf2(mh, mh);
      st_b128(sc->ax + 16 * rb + 4 * tq + g, (pack_bf2(mu - mh, ih) & ~1u) | tag, mm, pack_bf2(mu - mh, ir - ih), mm);
    }
    __syncwarp();
    if (lane == 0 && w == 3) st_relaxed1(sc->hx + 128 * 3 + rb, ep1);
  }
}

__device__ __noinline__ void repair(const uint4* src, uint32_t dst, int n, int stride, uint32_t mask, uint32_t tag) {
#pragma unroll 1
  for (int i = 0; i < n; i++) {
    uint4 v;
#pragma unroll 1
    for (int it = 0; it < 16 * RETRY_MAX; it++) {
      v = ld_b128(src + i * stride);
      if (!((((v.x ^ tag) & mask) | ((v.y ^ tag) & (mask >> 1)) | ((v.z ^ tag) & (mask >> 2)) | ((v.w ^ tag) & (mask >> 3))) & 1)) break;
      __nanosleep(100);
    }
    sts128(dst + i * stride * 16, v.x, v.y, v.z, v.w);
  }
}
__device__ __forceinline__ bool last_release(uint32_t cnt) {
  unsigned old;
  asm volatile("atom.relaxed.cta.shared.inc.u32 %0, [%1], 7;" : "=r"(old) : "r"(cnt) : "memory");
  return old == 7;
}
__device__ __forceinline__ int mod7(int v) { return v >= 7 ? v - 7 : v; }

#define IDS const int tid = opaque(tid0), lane = tid & 31, t = tid & 127; (void)lane; (void)t;

__global__ void __launch_bounds__(384, 1)
fused_kernel(const Params p, const __grid_constant__ CUtensorMap tm_x, const __grid_constant__ CUtensorMap tm_w1,
             const __grid_constant__ CUtensorMap tm_w2, const __grid_constant__ CUtensorMap tm_out,
             const __grid_constant__ CUtensorMap tm_c, const __grid_constant__ CUtensorMap tm_l) {
  const uint32_t sb = smem_u32(smem_raw);
  const uint32_t ms = sb + OFF_M;
  const uint32_t bar0 = ms + M_BAR;
  const int tid0 = threadIdx.x;
  const int wi = __shfl_sync(0xffffffffu, tid0 >> 5, 0), wg = wi >> 2, w = wi & 3;
  const int b = blockIdx.x;
  const bool is_ssm = b >= NMLP;
  const int G = b / NRK, rk = b - G * NRK;
  const bool is_mma = !is_ssm && wg < 2, is_aux = !is_ssm && wg == 2;
  const uint32_t work = sb + (wg ? OFF_A + (wg - 1) * 32768 : OFF_W + 2 * 32768);
  const uint32_t epa = ms + M_EP;
  const int d0 = is_ssm ? 2 * min(112 + 3 * (b - NMLP) + wg, 167) : 2 * b;
  const uint32_t tbl0 = sb + (is_ssm ? 256 + 2 * wg * TBL : OFF_T);
  GT(0);
  TSINIT();
  TSTAMP(0);
  {
    KgIn kin;
    const int d = is_ssm ? d0 + (w >> 1) : (wg < 2 ? d0 + wg : 336 + b);
    {
      IDS
      const int off = d * NST + 64 * (is_ssm ? 2 * (w & 1) : w) + 2 * lane;
      const __nv_bfloat16* P[8] = {p.a_re + off, p.a_im + off, p.b_re + off, p.b_im + off, p.c_re + off, p.c_im + off,
                                   p.log_dt + (d & ~1), p.dskip + (d & ~1)};
      asm volatile("" : "+l"(P[0]), "+l"(P[1]), "+l"(P[2]), "+l"(P[3]), "+l"(P[4]), "+l"(P[5]), "+l"(P[6]), "+l"(P[7]));
#pragma unroll
      for (int i = 0; i < 6; i++) kin.cur[i] = ldg32(P[i], 0);
      kin.ldt = ldg32(P[6], 0); kin.dk = ldg32(P[7], 0);
#pragma unroll
      for (int i = 0; i < 6; i++) kin.nxt[i] = 0u;
      if (is_ssm) {
#pragma unroll
        for (int i = 0; i < 6; i++) kin.nxt[i] = ldg32(P[i], 128);
      }
      asm volatile("" :: "l"(P[0]), "l"(P[1]), "l"(P[2]), "l"(P[3]), "l"(P[4]), "l"(P[5]), "l"(P[6]), "l"(P[7]));
    }
    unsigned ep = 0, b1w, b2w;
    {
      IDS
      b1w = ldg32(p.b1 + 64 * (is_ssm ? 0 : b >> 2) + (t & 62), 0); b2w = ldg32(p.b2 + 64 * rk + (t & 62), 0);
      if (tid == 352 || tid == 224) ep = ld_relaxed1(&p.s->epoch);
      if (lane == 0 && wi < 5)
        asm volatile("prefetch.tensormap [%0];" ::"l"(wi == 0 ? &tm_x : wi == 1 ? &tm_w1 : wi == 2 ? &tm_w2 : wi == 3 ? &tm_l : &tm_c) : "memory");
      __syncwarp();
#pragma unroll 1
      for (int i = t; i < (is_ssm ? 2 : 1) * (TBL / 16); i += 128) sts128(tbl0 + (is_ssm ? 0 : wg * TBL) + i * 16, 0u, 0u, 0u, 0u);
      if (wg == 0)
        asm volatile("st.shared.b32 [%0], %1;" ::"r"(ms + M_ID + t * 4),
                     "r"((w == 0 || w == 3) && (lane >> 3) == (lane & 3) ? ((lane & 4) ? 0x3f800000u : 0x00003f80u) : 0u) : "memory");
      if (wi == 5 && lane < 16) asm volatile("st.shared.b32 [%0], 0;" ::"r"(ms + M_REL + 4 * lane) : "memory");
    }
    auto stage = [&](int i, bool wpart, bool xpart) {
      if (wpart) {
        mbar_expect(bar0 + 8 * i, 49152);
        tma_3d(sb + OFF_W + i * 32768, &tm_w1, 0, 64 * i, 4 * rk, bar0 + 8 * i);
      }
      if (xpart) tma_2d(sb + OFF_X + i * 16384, &tm_x, 64 * i, 128 * G, bar0 + 8 * i);
    };
    auto mid = [&](int it) {
      IDS
      TSTAMP(25 + it);
      if (it < 0) {
        const int bi = (0xba9387146250ull >> (4 * wi)) & 15;
        if (lane == 0) {
          mbar_init(bar0 + 8 * bi, 1);
          if (w == 3) mbar_init(bar0 + 96 + 8 * wg, 1);
          asm volatile("fence.mbarrier_init.release.cluster;" ::: "memory");
          if (bi == 3) { mbar_expect(bar0 + 24, 14336); tma_3d(sb + OFF_X + 32768, &tm_l, 0, 16 * (b & 127), 0, bar0 + 24); }
          if (bi == 4 && !is_ssm) { mbar_expect(bar0 + 32, 14336); tma_2d(sb + OFF_X + 16384, &tm_c, 64 * (b >> 2), 112 * (b & 3), bar0 + 32); }
        }
        if (tid == 352 || tid == 224) { asm volatile("st.shared.b32 [%0], %1;" ::"r"(epa), "r"(ep + 1) : "memory"); red_relaxed(&p.s->cntA); }
        __syncwarp();
      } else if (it == 1) {
        if (is_ssm) return;
        if (tid == 160) stage(1, false, true);
        __syncwarp();
        if (wi == 6 || wi == 7) {
          const unsigned ep1 = lds32(epa);
          const uint32_t a = ms + M_CS + (t & 63) * 4;
          const float c = -((lds32f(a) + lds32f(a + 256)) + (lds32f(a + 512) + lds32f(a + 768)));
          const float ch = rbf(c);
          uint2* dx = (uint2*)(p.s->bx + (b >> 4) * 512 + ((b >> 1) & 1) * 256 + ((b >> 2) & 3) * 64 + (t & 63)) + (b & 1);
          const float b1v = (b & 2) ? 0.f : ((t & 1) ? bf_hi(b1w) : bf_lo(b1w));
          asm volatile("{.reg .b64 a; mov.b64 a, {%1,%2}; st.relaxed.gpu.global.b64 [%0], a;}"
                       ::"l"(dx), "r"(pack_bf2(ch, b1v)), "r"((pack_bf2(c - ch, ch) & ~1u) | (ep1 & 1)) : "memory");
          __syncwarp();
          if (lane == 0) st_relaxed1(p.s->hb + 2 * b + (w & 1), ep1);
          sts32f(ms + M_B2 + (t & 63) * 4, 0.5f * ((t & 1) ? bf_hi(b2w) : bf_lo(b2w)));
        }
      } else if (it == 0 && wg != 1) {
        if (tid == 0 && !is_ssm) stage(0, true, true);
        __syncwarp();
        if (wg == 2) {
          mbar_wait(bar0 + 24, 0);
          TSTAMP(29);
          ln_block(p.s, sb + OFF_X + 32768, b, ms + M_RED, lds32(epa), w, lane);
          TSTAMP(30);
        }
      } else if (!is_ssm) {
        float cs[4] = {0.f, 0.f, 0.f, 0.f}, c2[4] = {0.f, 0.f, 0.f, 0.f};
        const int g = lane >> 2, rr = 4 * w + (lane & 3);
        const uint32_t one = (g & 1) ? 0x3f800000u : 0x00003f80u;
        const uint32_t s0 = (g >> 1) == 0 ? one : 0u, s1 = (g >> 1) == 1 ? one : 0u, s2 = (g >> 1) == 2 ? one : 0u, s3 = (g >> 1) == 3 ? one : 0u;
        mbar_wait(bar0 + 32, 0);
        if (tid == 160) stage(1, true, false);
        __syncwarp();
#pragma unroll
        for (int i = 0; i < 7; i++) {
          const uint4 q = lds128(sb + OFF_X + 16384 + (rr + 16 * i) * 128 + ((g ^ (rr & 7)) << 4));
          mma_bf16(cs, s0, 0u, s1, 0u, q.x, q.y);
          mma_bf16(c2, s2, 0u, s3, 0u, q.z, q.w);
        }
        sts32f(ms + M_CS + (w * 64 + (lane & 3) * 16 + g) * 4, cs[0] + c2[0]);
        sts32f(ms + M_CS + (w * 64 + (lane & 3) * 16 + g + 8) * 4, cs[1] + c2[1]);
      }
    };
    kgen_wg(kin, d & 1, is_ssm ? 2 : 1, work, is_mma ? sb + OFF_A + 10240 + wg * 6400 : work, ms + M_MX + wg * 16, w, opaque(tid0) & 31, 4 + wg,
            is_mma ? 8 : 4 + wg, is_mma ? 384 : 128, mid);
    TSTAMP(1);
    if (is_mma) {
      if (tid0 == 64) { fence_async(); stage(2, true, true); }
      __syncwarp();
      bar_arrive(10, 288);
    }
    if (is_ssm && wg < 2) bar_sync(8, 384);
    bar_sync(4 + wg, 128);
    if (!is_mma) {
      IDS
      const unsigned ep1 = lds32(epa);
      if (is_aux) {
        if (t == 96)
          asm volatile("cp.async.bulk.prefetch.L2.global [%0], %1;" ::"l"(p.w2 + (uint32_t)((256 * rk + 16 * G) * D_)), "r"(16 * D_ * 2) : "memory");
        __syncwarp();
      }
      if (is_aux && w == 2) {
        bar_sync(10, 288);
        wait_hint(lane < 8 ? p.s->hb + 32 * rk + 4 * lane : p.s->hx + 128 * 3 + 8 * G + 4 * (lane & 1), ep1);
        if (lane == 0) {
          fence_async();
          mbar_expect(bar0 + 32, 10240);
          bulk_g2s(sb + OFF_AX, p.s->ax + 128 * G, 2048, bar0 + 32);
          bulk_g2s(sb + OFF_BX, p.s->bx + 512 * rk, 8192, bar0 + 32);
        }
        __syncwarp();
      }
      if (w == 3) {
        wait_hint(p.s->hx + 128 * 3 + 4 * lane, ep1);
        if (lane == 0) {
          fence_async();
          mbar_expect(bar0 + 96 + 8 * wg, is_aux ? 16384 : 8192);
          bulk_g2s(work + 8192, p.s->xnT + (uint32_t)((d0 >> 1) * 512), 8192, bar0 + 96 + 8 * wg);
          if (is_aux) bulk_g2s(work + 16384, p.s->xnT + (uint32_t)((168 + (b >> 1)) * 512), 8192, bar0 + 96 + 8 * wg);
        }
        __syncwarp();
      }
    }
#pragma unroll 1
    for (int c = is_ssm ? 1 : wg; c >= (is_ssm ? 0 : wg); c--) {
      const uint32_t src = (is_ssm || c == 2) ? work : sb + OFF_A + 10240 + c * 6400;
      ktab_build(src + (is_ssm ? c * 3072 : 0), src + 6144 + (is_ssm ? c * 8 : 0), !is_ssm, w, tbl0 + c * TBL, opaque(tid0) & 31);
    }
    TSTAMP(2);
    if (is_mma) bar_arrive(2, 384);
  }

  if (!is_mma) {
    uint4 vc[2];
    {
      IDS
      uint4 va[2], vb[2];
      const unsigned ep1 = lds32(epa);
      const int o0 = (t >> 1) * 4 + (t & 1), oa = o0 + (is_aux ? 512 + (b & 1) * 2 : 2);
      mbar_wait(bar0 + 96 + 8 * wg, 0);
#pragma unroll
      for (int q = 0; q < 2; q++) {
        va[q] = lds128(work + 8192 + (oa + q * 256) * 16); vb[q] = lds128(work + 8192 + (o0 + 2 + q * 256) * 16);
        vc[q] = lds128(work + 8192 + (o0 + q * 256) * 16);
      }
#pragma unroll 1
      for (int it = 0; it < 16 * RETRY_MAX; it++) {
        uint32_t bad = 0;
#pragma unroll
        for (int q = 0; q < 2; q++)
          bad |= (va[q].x ^ ep1) | (va[q].y ^ ep1) | (va[q].z ^ ep1) | (va[q].w ^ ep1) | (vb[q].x ^ ep1) | (vb[q].y ^ ep1) | (vb[q].z ^ ep1) |
                 (vb[q].w ^ ep1) | (vc[q].x ^ ep1) | (vc[q].y ^ ep1) | (vc[q].z ^ ep1) | (vc[q].w ^ ep1);
        if (__builtin_expect(!__any_sync(0xffffffffu, bad & 1), 1)) break;
        __nanosleep(100);
        const uint4* s0 = p.s->xnT + (uint32_t)((d0 >> 1) * 512 + o0);
        const uint4* sa = p.s->xnT + (uint32_t)((is_aux ? 167 + (b >> 1) : d0 >> 1) * 512 + oa);
#pragma unroll
        for (int q = 0; q < 2; q++) { va[q] = ld_relaxed4(sa + q * 256); vb[q] = ld_relaxed4(s0 + q * 256 + 2); vc[q] = ld_relaxed4(s0 + q * 256); }
      }
      TSTAMP(15);
      bar_sync(is_aux ? 2 : 4 + wg, is_aux ? 384 : 128);
      sig_store(work + YB, t, va);
      if (is_aux) sig_store(sb + OFF_A + YB, t, vb);
    }
    const int nops = is_aux ? 4 : 2;
#pragma unroll 1
      for (int op = 0; op < nops; op++) {
        const int pc = is_ssm ? 1 - op : (0x0312 >> (4 * op)) & 3, cc = is_ssm ? 1 - op : (0x0123 >> (4 * op)) & 3;
        if (op == 2) {
          bar_sync(12, 384);
          if (tid0 == 256) {
            fence_async();
            mbar_expect(bar0 + 24, 32768);
            tma_2d(sb + OFF_A + 32768, &tm_w2, 64 * mod7(rk + 5), 256 * rk, bar0 + 24);
          }
          __syncwarp();
        }
        if (pc < 3) {
          IDS
          const uint32_t sig = (is_ssm ? work : sb + OFF_A + (pc >> 1) * 32768) + YB;
          if (pc == 0) {
            bar_sync(4 + wg, 128);
            sig_store(sig, t, vc);
          }
          if (op != 1 || is_ssm) bar_sync(4 + wg, 128);
          if (w < 3) sig_windows(sig, t);
          else if (is_aux && op == 0) {
            const unsigned ep1 = lds32(epa);
            mbar_wait(bar0 + 32, 1);
            uint32_t bad = 0;
#pragma unroll
            for (int k = 0; k < 20; k++) {
              const uint4 v = lds128(sb + OFF_AX + (k * 32 + lane) * 16);
              bad |= k < 4 ? v.x ^ ep1 : (v.y ^ ep1) | (v.w ^ ep1);
            }
            if (__builtin_expect(__any_sync(0xffffffffu, bad & 1), 0)) {
              repair(p.s->ax + 128 * G + lane, sb + OFF_AX + lane * 16, 4, 32, 1, ep1);
              repair(p.s->bx + 512 * rk + lane, sb + OFF_BX + lane * 16, 16, 32, 10, ep1);
            }
            fence_async();
            bar_arrive(1, 288);
          }
          fence_async();
          TSTAMP(3 + op);
        }
        if (cc < 3) {
          if (op != 2) bar_sync(4 + wg, 128);
          IDS
          const int ch = cc < 2 ? d0 + cc : 336 + b;
          const uint32_t sig = (is_ssm ? work : sb + OFF_A + (cc >> 1) * 32768) + YB, tbl = tbl0 + cc * TBL;
          float res[16];
          conv_channel(tbl, sig, lds32f(tbl + TBL_SC), w, lane, 4 + wg, res);
          const float os = lds32f(tbl + TBL_SC + 4);
          uint2* dst = (uint2*)(p.s->s2 + (uint32_t)(((2 * (lane & 1) + ((lane >> 1) & 1)) * 224 + (ch >> 1)) * 32 + w * 8 + ((lane >> 2) ^ (ch & 6)))) + (ch & 1);
          const uint32_t ep1 = lds32(epa), tag = ep1 & 1;
#pragma unroll
          for (int k = 0; k < 4; k++) {
            const uint32_t w0 = pack_bf2(res[4 * k] * os, res[4 * k + 1] * os), w1 = pack_bf2(res[4 * k + 2] * os, res[4 * k + 3] * os);
            const uint32_t got = __shfl_xor_sync(0xffffffffu, (lane & 1) ? w0 : w1, 1);
            asm volatile("{.reg .b64 a; mov.b64 a, {%1,%2}; st.relaxed.gpu.global.b64 [%0], a;}"
                         ::"l"(dst + k * 4 * 224 * 64), "r"((((lane & 1) ? got : w0) & ~1u) | tag), "r"((lane & 1) ? w1 : got) : "memory");
          }
          __syncwarp();
          if (lane == 0) st_relaxed1(p.s->hs + 4 * ch + w, ep1);
          TSTAMP(7 + op);
        }
      }
    if (is_aux && w >= 2) {
      IDS
      const unsigned ep1 = lds32(epa);
      wait_hint(p.s->hs + 4 * (64 * rk + (t & 63)), ep1);
      bar_sync(13, 320);
      if (t == 64) {
        fence_async();
        mbar_expect(bar0 + 88, 16384);
        bulk_g2s(sb + OFF_W + 32768, p.s->s2 + (uint32_t)((G * 224 + 32 * rk) * 32), 16384, bar0 + 88);
      }
    }
    TSDUMP();
    if (b == 0 && tid0 == 256) {
      const unsigned ep1 = lds32(epa);
      wait_count(&p.s->cntA, ep1 * (2 * NCTA));
      *(volatile unsigned*)&p.s->epoch = ep1;
    }
  } else {
    float r0, r1;
    uint32_t H[64];
    {
      float acc[128];
      float p0, q0, p1, q1;
      {
        IDS
        int sl = 0;
#pragma unroll 1
        for (int s = 0; s < 7; s++) {
          mbar_wait(bar0 + 8 * sl, (s >= 3 && s < 6));
          TSTAMP(17 + s);
          const uint64_t da = mkdesc(sb + OFF_X + sl * 16384 + wg * 8192, 16, 1024, 1);
          const uint64_t db = mkdesc(sb + OFF_W + sl * 32768, 8192, 1024, 1);
          wg_fence();
#pragma unroll
          for (int k = 0; k < 4; k++) wg_ss_bf16_n256(acc, da + 2 * k, db + 128 * k, (s | k) != 0);
          wg_commit();
          wg_wait<1>();
          const int pl = sl == 0 ? 2 : sl - 1;
          sl = sl == 2 ? 0 : sl + 1;
          if (s > 0 && lane == 0 && last_release(ms + M_REL + 4 * s)) {
            mbar_expect(bar0 + 8 * pl, s == 5 ? 32768 : 49152);
            if (s < 5) tma_3d(sb + OFF_W + pl * 32768, &tm_w1, 0, 64 * (s + 2), 4 * rk, bar0 + 8 * pl);
            else tma_2d(sb + OFF_W + pl * 32768, &tm_w2, 64 * mod7(rk + s - 4), 256 * rk, bar0 + 8 * pl);
            if (s != 5) tma_2d(sb + OFF_X + pl * 16384, &tm_x, 64 * (s < 5 ? (s + 2) : rk), 128 * G, bar0 + 8 * pl);
          }
        }
        TSTAMP(15);
        bar_sync(1, 288);
        wg_fence();
        wg_ss_bf16_n256k(acc, mkdesc(sb + OFF_AX + wg * 1024, 0, 128, 0), mkdesc(sb + OFF_BX, 4096, 128, 0), 1);
        wg_commit();
        wg_wait<1>();
        if (lane == 0 && last_release(ms + M_REL + 4 * 7)) {
          mbar_expect(bar0, 65536);
#pragma unroll 1
          for (int c = 2; c < 4; c++) tma_2d(sb + (c - 2) * OFF_X, &tm_w2, 64 * mod7(rk + 1 + c), 256 * rk, bar0);
        }
        const uint32_t ra = sb + OFF_AX + (16 * wi + (lane >> 2)) * 16;
        r0 = rcpf_(bf_hi(lds32(ra)) + bf_hi(lds32(ra + 8))); r1 = rcpf_(bf_hi(lds32(ra + 128)) + bf_hi(lds32(ra + 136)));
        p0 = 0.7978845608028654f * r0; q0 = 0.0356774081363001f * r0 * r0 * r0;
        p1 = 0.7978845608028654f * r1; q1 = 0.0356774081363001f * r1 * r1 * r1;
      }
      wg_wait<0>();
      fence_regs<128>(acc);
      bar_arrive(12, 384);
      {
        const uint32_t z = lds32(ms + M_REL + 60);
        p0 = __uint_as_float(__float_as_uint(p0) | z); p1 = __uint_as_float(__float_as_uint(p1) | z);
      }
      TSTAMP(16);
      float th[8];
#pragma unroll
      for (int i = 0; i < 67; i++) {
        if (i < 64) {
          const float pp = (i & 1) ? p1 : p0, qq = (i & 1) ? q1 : q0;
          const float a = acc[2 * i], c = acc[2 * i + 1];
          th[2 * (i & 3)] = tanhf_(a * fmaf(a * a, qq, pp)); th[2 * (i & 3) + 1] = tanhf_(c * fmaf(c * c, qq, pp));
        }
        if (i >= 3) {
          const int j = i - 3;
          asm volatile("{.reg .f32 x, y; fma.rn.f32 x, %1, %3, %1; fma.rn.f32 y, %2, %4, %2; cvt.rn.bf16x2.f32 %0, y, x;}"
                       : "=r"(H[j]) : "f"(acc[2 * j]), "f"(acc[2 * j + 1]), "f"(th[2 * (j & 3)]), "f"(th[2 * (j & 3) + 1]));
        }
      }
    }
    TSTAMP(14);
    IDS
    float oac[32];
    unsigned old = 0;
    const uint32_t ep1 = lds32(epa), tag = ep1 & 1;
    const uint4* inbox = p.s->part + (uint32_t)(b * 6 * 1024);
    auto fetch = [&](int j) {
      mbar_expect(bar0 + 40 + 8 * j, 16384);
      bulk_g2s(sb + ((0xcb7610u >> (4 * j)) & 15) * 16384, inbox + j * 1024, 16384, bar0 + 40 + 8 * j);
    };
#pragma unroll 1
    for (int s = 0; s < 7; s++) {
      if (s != 3) mbar_wait(bar0 + 8 * ((0x2130021u >> (4 * s)) & 7), (0x74 >> s) & 1);
      const uint64_t db = mkdesc(sb + ((0x42b6042u >> (4 * s)) & 15) * 16384, 8192, 1024, 1);
      const int slot = (G * 7 + mod7(rk + s + 1)) * 6 + s;
      uint4* dst = p.s->part + (uint32_t)(slot * 1024 + wg * 512 + t);
      unsigned* hint = p.s->hp + (uint32_t)(8 * slot + wi);
      if (s + wg) bar_sync(14 + wg, 256);
      wg_fence();
#pragma unroll
      for (int k = 0; k < 16; k++) wg_rs_bf16_n64(oac, H[4 * k], H[4 * k + 1], H[4 * k + 2], H[4 * k + 3], db + 128 * k, k != 0);
      wg_commit();
      if (s + wg < 7) bar_arrive(15 - wg, 256);
      if (old == 7) {
        if (s == 1 || s == 2) {
          mbar_expect(bar0 + 8 * s, 32768);
          tma_2d(sb + OFF_W + s * 32768, &tm_w2, 64 * mod7(mod7(rk + 5 + s)), 256 * rk, bar0 + 8 * s);
        }
        if (s >= 3) fetch(s - 3);
      }
      __syncwarp();
      asm volatile("" : "+l"(dst), "+l"(hint));
      wg_wait<0>();
      fence_regs<32>(oac);
      if (s == 6) break;
      send_tile(dst, tag, oac);
      if (lane == 0) {
        st_relaxed1(hint, ep1);
        asm volatile("atom.relaxed.cta.shared.inc.u32 %0, [%1], 7;" : "=r"(old) : "r"(ms + M_REL + 4 * (8 + s)) : "memory");
      }
      __syncwarp();
      if (s == 5) bar_arrive(13, 320);
      TSTAMP(5 + s);
    }
    TSTAMP(11);
    const uint32_t barl = bar0 + 40 + wg * 24;
    if (w < 2) {
      mbar_wait(bar0 + 56, 0);
      wait_hint(p.s->hp + 8 * (b * 6 + 5 - w) + 4 * wg, ep1);
      if (lane == 0) {
        mbar_expect(barl + 40 - 8 * w, 8192);
        bulk_g2s(sb + (12 - w) * 16384 + wg * 8192, inbox + (5 - w) * 1024 + wg * 512, 8192, barl + 40 - 8 * w);
      }
      __syncwarp();
    }
    TSTAMP(31);
    float pre[32];
#pragma unroll
    for (int i = 0; i < 32; i++) asm volatile("mov.f32 %0, %1;" : "=f"(pre[i]) : "f"(oac[i]));
    const int tq = lane & 3, so = tq * 32 + w * 8 + ((lane >> 2) ^ (2 * tq));
    const uint32_t xa = sb + OFF_X + 2 * 16384 + (16 * wi + (lane & 15)) * 128;
    r0 *= 0.25f; r1 *= 0.25f;
    uint4 rv[24];
    uint32_t xw[16];
    float2 bb[8];
#pragma unroll
    for (int j = 0; j < 6; j += 3) {
#pragma unroll
      for (int q = 4 * j; q < 4 * j + 12; q++) {
        if (!(q & 3)) mbar_wait((q < 16 ? bar0 + 40 : barl) + 2 * q, 0);
        rv[q] = lds128(sb + ((0xcb7610u >> (q & ~3)) & 15) * 16384 + (wg * 512 + (q & 3) * 128 + t) * 16);
      }
#pragma unroll 1
      for (int it = 0; it < 16 * RETRY_MAX; it++) {
        uint32_t bad = 0;
#pragma unroll
        for (int q = 4 * j; q < 4 * j + 12; q++) bad |= rv[q].x ^ tag;
        if (__builtin_expect(!__any_sync(0xffffffffu, bad & 1), 1)) break;
        __nanosleep(100);
#pragma unroll
        for (int q = 4 * j; q < 4 * j + 12; q++) rv[q] = ld_relaxed4(inbox + (q >> 2) * 1024 + wg * 512 + (q & 3) * 128 + t);
      }
      wg_fence();
#pragma unroll
      for (int q = 4 * j; q < 4 * j + 12; q++) wg_rs_bf16_n16k(pre + 8 * (q & 3), rv[q].x, rv[q].y, rv[q].z, rv[q].w, mkdesc(ms + M_ID, 128, 256, 0), 1);
      wg_commit();
      TSTAMP(27 + j);
      if (j == 0) {
        wg_wait<0>();
#pragma unroll
        for (int i = 0; i < 8; i++) bb[i] = lds64f(ms + M_B2 + (8 * i + 2 * tq) * 4);
#pragma unroll
        for (int q = 0; q < 4; q++) ldsm4(xa + (((2 * q + (lane >> 4)) ^ (lane & 7)) << 4), xw[4 * q], xw[4 * q + 1], xw[4 * q + 2], xw[4 * q + 3]);
      }
    }
    wg_wait<0>();
    fence_regs<32>(pre);
    TSTAMP(12);
    uint32_t gw[16];
#pragma unroll
    for (int k = 0; k < 16; k++) {
      const float h0 = fmaf(pre[2 * k], (k & 1) ? r1 : r0, bb[k >> 1].x), h1 = fmaf(pre[2 * k + 1], (k & 1) ? r1 : r0, bb[k >> 1].y);
      gw[k] = pack_bf2(fmaf(h0, tanhf_(h0), h0), fmaf(h1, tanhf_(h1), h1));
      asm volatile("" : "+r"(gw[k]));
    }
    TSTAMP(3);
    mbar_wait(bar0 + 88, 0);
    uint4 sv[8];
#pragma unroll 1
    for (int it = 0; it < 2; it++) {
      uint32_t bad = 0;
#pragma unroll
      for (int i = 0; i < 8; i++) { sv[i] = lds128(sb + OFF_W + 32768 + (so + i * 128) * 16); bad |= (sv[i].x ^ tag) | (sv[i].z ^ tag); }
      if (__builtin_expect(!__any_sync(0xffffffffu, bad & 1), 1)) break;
      repair(p.s->s2 + (uint32_t)((G * 224 + 32 * rk) * 32 + so), sb + OFF_W + 32768 + so * 16, 8, 128, 5, tag);
    }
    TSTAMP(4);
#pragma unroll
    for (int i = 0; i < 8; i++) {
      const uint32_t c0 = wg ? sv[i].y : sv[i].x, c1 = wg ? sv[i].w : sv[i].z;
      asm("fma.rn.bf16x2 %0, %1, %2, %0;" : "+r"(xw[2 * i]) : "r"(__byte_perm(c0, c1, 0x5410)), "r"(gw[2 * i]));
      asm("fma.rn.bf16x2 %0, %1, %2, %0;" : "+r"(xw[2 * i + 1]) : "r"(__byte_perm(c0, c1, 0x7632)), "r"(gw[2 * i + 1]));
    }
#pragma unroll
    for (int q = 0; q < 4; q++) stsm4(xa + (((2 * q + (lane >> 4)) ^ (lane & 7)) << 4), xw[4 * q], xw[4 * q + 1], xw[4 * q + 2], xw[4 * q + 3]);
    fence_async();
    __syncwarp();
    if (lane == 0) {
      tma_store_2d(&tm_out, sb + OFF_X + 2 * 16384 + wi * 2048, 64 * rk, 128 * G + 16 * wi);
      bulk_commit();
      bulk_wait0_read();
    }
    TSTAMP(13);
    GT(1);
    TSDUMP();
  }
}

typedef CUresult (*EncodeFn)(CUtensorMap*, CUtensorMapDataType, cuuint32_t, void*, const cuuint64_t*, const cuuint64_t*,
                             const cuuint32_t*, const cuuint32_t*, CUtensorMapInterleave, CUtensorMapSwizzle,
                             CUtensorMapL2promotion, CUtensorMapFloatOOBfill);

void make_map(EncodeFn fn, CUtensorMap* m, const void* ptr, int rank, const cuuint64_t* dims, const cuuint64_t* strides, const cuuint32_t* box) {
  const cuuint32_t es[3] = {1, 1, 1};
  fn(m, CU_TENSOR_MAP_DATA_TYPE_BFLOAT16, rank, const_cast<void*>(ptr), dims, strides, box, es, CU_TENSOR_MAP_INTERLEAVE_NONE,
     CU_TENSOR_MAP_SWIZZLE_128B, CU_TENSOR_MAP_L2_PROMOTION_L2_128B, CU_TENSOR_MAP_FLOAT_OOB_FILL_NONE);
}

}

extern "C" void kernel_launch(void* const* d_in, const int* in_sizes, int n_in, void* d_out, int out_size) {
  (void)in_sizes; (void)n_in; (void)out_size;
  void* fnp = nullptr;
  cudaDriverEntryPointQueryResult qr;
  cudaGetDriverEntryPoint("cuTensorMapEncodeTiled", &fnp, cudaEnableDefault, &qr);
  EncodeFn fn = (EncodeFn)fnp;
  Params p;
  p.a_re = (const __nv_bfloat16*)d_in[1]; p.a_im = (const __nv_bfloat16*)d_in[2];
  p.b_re = (const __nv_bfloat16*)d_in[3]; p.b_im = (const __nv_bfloat16*)d_in[4];
  p.c_re = (const __nv_bfloat16*)d_in[5]; p.c_im = (const __nv_bfloat16*)d_in[6];
  p.log_dt = (const __nv_bfloat16*)d_in[7]; p.dskip = (const __nv_bfloat16*)d_in[8];
  const void *px = d_in[0], *pw1 = d_in[10];
  p.b1 = (const __nv_bfloat16*)d_in[11];
  p.w2 = (const __nv_bfloat16*)d_in[12]; p.b2 = (const __nv_bfloat16*)d_in[13];
  void* sp = nullptr;
  cudaGetSymbolAddress(&sp, g_scr);
  p.s = (Scratch*)(((uintptr_t)sp + (2 << 20) - 1) & ~(uintptr_t)((2 << 20) - 1));
  CUtensorMap mx, mw1, mw2, mo, mc, ml;
  {
    const cuuint64_t dims[2] = {448, 2048}, str[1] = {896};
    const cuuint32_t box[2] = {64, 128}, boxo[2] = {64, 16};
    make_map(fn, &mx, px, 2, dims, str, box);
    make_map(fn, &mo, d_out, 2, dims, str, boxo);
    const cuuint64_t dims3[3] = {64, 2048, 7}, str3[2] = {896, 128};
    const cuuint32_t box3[3] = {64, 16, 7};
    make_map(fn, &ml, px, 3, dims3, str3, box3);
  }
  {
    const cuuint64_t dims[3] = {64, 448, 28}, str[2] = {3584, 128};
    const cuuint32_t box[3] = {64, 64, 4};
    make_map(fn, &mw1, pw1, 3, dims, str, box);
    const cuuint64_t dims2[2] = {1792, 448};
    const cuuint32_t box2[2] = {64, 112};
    make_map(fn, &mc, pw1, 2, dims2, str, box2);
  }
  {
    const cuuint64_t dims[2] = {448, 1792}, str[1] = {896};
    const cuuint32_t box[2] = {64, 256};
    make_map(fn, &mw2, p.w2, 2, dims, str, box);
  }
  cudaFuncSetAttribute(fused_kernel, cudaFuncAttributeMaxDynamicSharedMemorySize, SMEM_BYTES);
  fused_kernel<<<NCTA, 384, SMEM_BYTES>>>(p, mx, mw1, mw2, mo, mc, ml);
}
```
